```python
import torch

def _softmax(x, axis=-1):
    return torch.softmax(x, dim=axis)
def _gelu(x):
    return torch.nn.functional.gelu(x, approximate="tanh")
def _silu(x):
    return torch.nn.functional.silu(x)
def _sigmoid(x):
    return torch.sigmoid(x)
def _layernorm(x, axis=-1, eps=1e-5):
    m = x.mean(dim=axis, keepdim=True)
    v = x.var(dim=axis, keepdim=True, unbiased=False)
    return (x - m) / torch.sqrt(v + eps)
def _scatter_add(tgt, idx, src, axis=0):
    return tgt.clone().index_add_(axis, idx, src)
def _segment_sum(src, seg, n):
    out = torch.zeros((n,) + src.shape[1:], dtype=src.dtype)
    return out.index_add_(0, seg, src)
def _pad(x, pw):
    flat = tuple(v for pair in reversed(pw) for v in pair)
    return torch.nn.functional.pad(x, flat)

kernel_name = 'concat_heads__gqa_block_cached__compressed_kv_cla__decode'

def setup_inputs():

    _w = (lambda a: (lambda t: t.to(torch.bfloat16) if t.is_floating_point() else t)(torch.as_tensor(a)))
    def _A_setup():
        B, Sq, D = 2, 1, 512
        Hq, Hkv, Sk, Dh = 32, 32, 8192, 128
        assert Hq % Hkv == 0, (Hq, Hkv)
        return {
            "x": _w((lambda *s: torch.randn(*s, dtype=torch.bfloat16) * 1.6)(B, Sq, D)),
            "k_cache": _w((lambda *s: torch.randn(*s, dtype=torch.bfloat16) * 1.6)(B, Hkv, Sk, Dh)),
            "v_cache": _w((lambda *s: torch.randn(*s, dtype=torch.bfloat16) * 0.05)(B, Hkv, Sk, Dh)),
            "wq": _w((lambda *s: torch.randn(*s, dtype=torch.bfloat16) * 1.6)(D, Hq * Dh) * (D ** -0.5)),
            "wo": _w((lambda *s: torch.randn(*s, dtype=torch.bfloat16) * 0.05)(Hq * Dh, D) * ((Hq * Dh) ** -0.5)),
        }
    _A_in = _A_setup()

    def _B_setup():
        B, H, Sq, Sk, D, M = 2, 32, 1, 8192, 128, 512
        Dc = 4 * D
        return {
            "x": _w((lambda *s: torch.randn(*s, dtype=torch.bfloat16) * 3.2)(B, Sq, M)),
            "c_kv": _w((lambda *s: torch.randn(*s, dtype=torch.bfloat16) * 0.1)(B, Sk, Dc)),
            "w_q": _w((lambda *s: torch.randn(*s, dtype=torch.bfloat16) * 6.4)(M, H, D) * (M ** -0.5)),
            "w_uk": _w((lambda *s: torch.randn(*s, dtype=torch.bfloat16) * 6.4)(Dc, H, D) * (Dc ** -0.5)),
            "w_uv": _w((lambda *s: torch.randn(*s, dtype=torch.bfloat16) * 0.1)(Dc, H, D) * (Dc ** -0.5)),
            "w_o": _w((lambda *s: torch.randn(*s, dtype=torch.bfloat16) * 0.1)(H, D, M) * ((H * D) ** -0.5)),
        }
    _B_in = _B_setup()

    return {
        "A_x": _A_in["x"],
        "A_k_cache": _A_in["k_cache"],
        "A_v_cache": _A_in["v_cache"],
        "A_wq": _A_in["wq"],
        "A_wo": _A_in["wo"],
        "B_x": _B_in["x"],
        "B_c_kv": _B_in["c_kv"],
        "B_w_q": _B_in["w_q"],
        "B_w_uk": _B_in["w_uk"],
        "B_w_uv": _B_in["w_uv"],
        "B_w_o": _B_in["w_o"],
    }

def reference(A_x, A_k_cache, A_v_cache, A_wq, A_wo, B_x, B_c_kv, B_w_q, B_w_uk, B_w_uv, B_w_o):
    def _A_ref(x, k_cache, v_cache, wq, wo):
        B, Sq, D = x.shape
        Hq, Dh = 32, 128
        Hkv = k_cache.shape[1]
        rep = Hq // Hkv
        q = (lambda x, *d: x.permute(*d))((x @ wq).reshape(B, Sq, Hq, Dh), 0, 2, 1, 3)
        k = (lambda x, n, axis: torch.repeat_interleave(x, n, dim=axis))(k_cache, rep, axis=1)
        v = (lambda x, n, axis: torch.repeat_interleave(x, n, dim=axis))(v_cache, rep, axis=1)
        scores = torch.einsum("bhqd,bhkd->bhqk", q, k) * (Dh ** -0.5)
        p = _softmax(scores, axis=-1)
        o = torch.einsum("bhqk,bhkd->bhqd", p, v)
        return (lambda x, *d: x.permute(*d))(o, 0, 2, 1, 3).reshape(B, Sq, Hq * Dh) @ wo

    def _B_ref(x, c_kv, w_q, w_uk, w_uv, w_o):
        B, Sq, M = x.shape[0], x.shape[1], x.shape[2]
        Sk = c_kv.shape[1]
        H, D = w_q.shape[1], w_q.shape[2]
        q = torch.einsum("bqm,mhd->bhqd", x, w_q)
        k = torch.einsum("bkc,chd->bhkd", c_kv, w_uk)
        v = torch.einsum("bkc,chd->bhkd", c_kv, w_uv)
        scores = torch.einsum("bhqd,bhkd->bhqk", q, k) * (D ** -0.5)
        off = Sk - Sq
        qi = torch.arange(Sq)[:, None]
        kj = torch.arange(Sk)[None, :]
        cmask = kj <= (qi + off)
        scores = torch.where(cmask[None, None], scores, -1e9)
        p = _softmax(scores, axis=-1)
        ctx = torch.einsum("bhqk,bhkd->bhqd", p, v)
        return torch.einsum("bhqd,hdm->bqm", ctx, w_o)

    a = _A_ref(A_x, A_k_cache, A_v_cache, A_wq, A_wo)
    b = _B_ref(B_x, B_c_kv, B_w_q, B_w_uk, B_w_uv, B_w_o)
    return torch.concatenate([a, b], axis=-1)
```

```cpp
#include <cuda_runtime.h>
#include <cuda_bf16.h>
#include <cuda.h>
#include <stdint.h>
#include <float.h>

#define NW 4
#define LIM 12
#define ROT 32
#define BDELAY 1000
#define POLL_NS 300
#define FIRE_T 60
#define FIRE_NS 2500
#define FIRE_DT 80
#define FIRE_B 0
#define FIRE_C 0
#define SPEC_K 3

#define BAL 4
#define BALD 1
#define BALD2 1
#define DIRECT7 1
#define PLACE 1
#define POLL0_NS 2000
#define NI 1
#define LIM0 10
#define RAMP_S 256
#define RAMP_T0 300
#define PFA 3
#define PFQ 4096
#define BPOLL 1000
#define PADW 1088
#define FPOLL 300
#define QPOLL 0
#define XBULK 1
#define QSLEEP 1500
#define LATET 1
#define CSLEEP 8000
#define WPROMO CU_TENSOR_MAP_L2_PROMOTION_L2_128B
#define QPROMO CU_TENSOR_MAP_L2_PROMOTION_NONE

namespace {

constexpr int NG = 8, CPG = 8;
constexpr int UPG = 2048;
constexpr int NSL = 12, SPW = NSL / NW;
constexpr unsigned TICK_INC = UPG - NSL * CPG + NW * CPG;
static_assert(NSL % NW == 0 && NW <= 4, "slot rotation");
constexpr int SPIN_MAX = 1 << 22;
constexpr float LOG2E = 1.4426950408889634f;
constexpr float SCALE = 0.08838834764831845f;
constexpr uint64_t EVICT_FIRST = 0x12F0000000000000ull;

constexpr int SA_SLOT = NSL * 16384;
constexpr int SA_Q    = SA_SLOT + 8 * NW * 132 * 4;
constexpr int SA_FULL = SA_Q + 2048;
constexpr int SA_EMPTY = SA_FULL + NSL * 16;
constexpr int SA_QBAR = SA_EMPTY + NSL * 8;
constexpr int SA_META = SA_QBAR + 8;
constexpr int SA_LIM  = SA_META + NSL * 4;
constexpr int SA_CNT  = SA_LIM + 16;
constexpr int SA_END  = SA_CNT + 64;
constexpr int PROW    = 2080;
constexpr int SB_STG  = 0;
constexpr int SB_QIMG = 131072;
constexpr int SB_P    = SB_QIMG + 32 * PROW;
constexpr int SB_AL   = SB_P + 8192;
constexpr int SB_X    = SB_AL + 256;
static_assert(SB_P % 1024 == 0, "swizzle atom");
constexpr int SB_RED  = SB_X + 4352;
constexpr int SB_QB   = SB_RED + 2560;
constexpr int SB_BAR  = SB_QB + 1024;
constexpr int SB_CNT  = SB_BAR + 44 * 8;
constexpr int SB_END  = SB_CNT + 64;
constexpr int SMEM_BYTES = (SA_END > SB_END ? SA_END : SB_END);
static_assert(SMEM_BYTES <= 232448, "shared memory");

struct Scratch {
    uint4    bpart[32 * 32 * (PROW / 16)];
    uint4    apart[64 * CPG * 32];
    uint4    qimg[2 * 4096];
    uint4    qpub[64 * 32];
    uint4    ctx[64 * 32];
    uint2    aml[64 * CPG * 4];
    unsigned epoch[128 * 8];
    unsigned ctr[PADW];
    uint2    fire[PADW / 2];
    unsigned qflag[PADW], bflag[PADW];
};
__device__ __align__(1024) Scratch g_scr;

#define TRARG
#define TRPASS
#define TR(k)
#define TROUT()

__device__ __forceinline__ uint32_t s2u(const void* p) { return (uint32_t)__cvta_generic_to_shared(p); }
__device__ __forceinline__ bool elect() {
    uint32_t ok;
    asm volatile("{\n.reg .pred p;\nelect.sync _|p, 0xffffffff;\nselp.u32 %0,1,0,p;\n}" : "=r"(ok));
    return ok;
}
__device__ __forceinline__ void mbar_init(uint32_t b, int c) {
    asm volatile("mbarrier.init.shared::cta.b64 [%0], %1;" ::"r"(b), "r"(c) : "memory");
}
__device__ __forceinline__ void mbar_init_fence() { asm volatile("fence.mbarrier_init.release.cluster;" ::: "memory"); }
__device__ __forceinline__ void mbar_expect(uint32_t b, uint32_t bytes) {
    asm volatile("mbarrier.arrive.expect_tx.shared::cta.b64 _, [%0], %1;" ::"r"(b), "r"(bytes) : "memory");
}
__device__ __forceinline__ void mbar_arrive(uint32_t b) {
    asm volatile("mbarrier.arrive.shared::cta.b64 _, [%0];" ::"r"(b) : "memory");
}
__device__ __forceinline__ bool mbar_try(uint32_t b, uint32_t ph) {
    uint32_t ok;
    asm volatile("{\n.reg .pred p;\nmbarrier.try_wait.parity.shared::cta.b64 p, [%1], %2;\nselp.u32 %0,1,0,p;\n}"
                 : "=r"(ok) : "r"(b), "r"(ph) : "memory");
    return ok;
}
__device__ __forceinline__ bool mbar_test(uint32_t b, uint32_t ph) {
    uint32_t ok;
    asm volatile("{\n.reg .pred p;\nmbarrier.test_wait.parity.shared::cta.b64 p, [%1], %2;\nselp.u32 %0,1,0,p;\n}"
                 : "=r"(ok) : "r"(b), "r"(ph) : "memory");
    return ok;
}
__device__ __forceinline__ void mbar_wait(uint32_t b, uint32_t ph) {
#pragma unroll 1
    for (int i = 0; i < SPIN_MAX; i++) if (mbar_try(b, ph)) return;
    __trap();
}
__device__ __forceinline__ void tma2d(uint32_t dst, const CUtensorMap* map, int c0, int c1, uint32_t bar) {
    asm volatile("cp.async.bulk.tensor.2d.shared::cluster.global.mbarrier::complete_tx::bytes [%0], [%1, {%3, %4}], [%2];"
                 ::"r"(dst), "l"(map), "r"(bar), "r"(c0), "r"(c1) : "memory");
}
__device__ __forceinline__ void tma2d_ef(uint32_t dst, const CUtensorMap* map, int c0, int c1, uint32_t bar) {
    asm volatile("cp.async.bulk.tensor.2d.shared::cluster.global.mbarrier::complete_tx::bytes.L2::cache_hint [%0], [%1, {%3, %4}], [%2], %5;"
                 ::"r"(dst), "l"(map), "r"(bar), "r"(c0), "r"(c1), "l"(EVICT_FIRST) : "memory");
}
__device__ __forceinline__ void bulk_g2s(uint32_t dst, const void* src, uint32_t bytes, uint32_t bar) {
    asm volatile("cp.async.bulk.shared::cluster.global.mbarrier::complete_tx::bytes [%0], [%1], %2, [%3];"
                 ::"r"(dst), "l"(src), "r"(bytes), "r"(bar) : "memory");
}
__device__ __forceinline__ void prefetch_l2(const void* src, uint32_t bytes) {
    asm volatile("cp.async.bulk.prefetch.L2.global.L2::cache_hint [%0], %1, %2;" ::"l"(src), "r"(bytes), "l"(EVICT_FIRST) : "memory");
}
__device__ __forceinline__ void bulk_s2g(void* dst, uint32_t src, uint32_t bytes) {
    asm volatile("cp.async.bulk.global.shared::cta.bulk_group [%0], [%1], %2;" ::"l"(dst), "r"(src), "r"(bytes) : "memory");
}
__device__ __forceinline__ void fence_async_all() { asm volatile("fence.proxy.async;" ::: "memory"); }
__device__ __forceinline__ void bar_sync(int id, int n) { asm volatile("bar.sync %0, %1;" ::"r"(id), "r"(n) : "memory"); }
__device__ __forceinline__ void bar_arrive(int id, int n) { asm volatile("bar.arrive %0, %1;" ::"r"(id), "r"(n) : "memory"); }
__device__ __forceinline__ uint4 ld_relaxed4(const void* p) {
    uint4 v;
    asm volatile("ld.relaxed.gpu.global.v4.u32 {%0,%1,%2,%3}, [%4];"
                 : "=r"(v.x), "=r"(v.y), "=r"(v.z), "=r"(v.w) : "l"(p) : "memory");
    return v;
}
__device__ __forceinline__ unsigned ld_relaxed1(const void* p) {
    unsigned v;
    asm volatile("ld.relaxed.gpu.global.u32 %0, [%1];" : "=r"(v) : "l"(p) : "memory");
    return v;
}
__device__ __forceinline__ unsigned atom_inc(unsigned* p) {
    unsigned v;
    asm volatile("atom.relaxed.gpu.global.add.u32 %0, [%1], 1;" : "=r"(v) : "l"(p) : "memory");
    return v;
}
__device__ __forceinline__ void st_relaxed4(void* p, uint4 v) {
    asm volatile("st.relaxed.gpu.global.v4.u32 [%0], {%1,%2,%3,%4};" ::"l"(p), "r"(v.x), "r"(v.y), "r"(v.z), "r"(v.w) : "memory");
}
__device__ __forceinline__ uint4 ld_b128(const void* p) {
    uint4 v;
    asm volatile("{\n.reg .b128 t;\nld.relaxed.gpu.global.b128 t, [%4];\nmov.b128 {%0,%1,%2,%3}, t;\n}"
                 : "=r"(v.x), "=r"(v.y), "=r"(v.z), "=r"(v.w) : "l"(p) : "memory");
    return v;
}
__device__ __forceinline__ void st_b128(void* p, uint4 v) {
    asm volatile("{\n.reg .b128 t;\nmov.b128 t, {%1,%2,%3,%4};\nst.relaxed.gpu.global.b128 [%0], t;\n}"
                 ::"l"(p), "r"(v.x), "r"(v.y), "r"(v.z), "r"(v.w) : "memory");
}
__device__ __forceinline__ uint2 ld_b64(const void* p) {
    uint2 v;
    asm volatile("{\n.reg .b64 a;\nld.relaxed.gpu.global.b64 a, [%2];\nmov.b64 {%0,%1}, a;\n}" : "=r"(v.x), "=r"(v.y) : "l"(p) : "memory");
    return v;
}
__device__ __forceinline__ void st_b64(void* p, uint32_t a, uint32_t b) {
    asm volatile("{\n.reg .b64 t;\nmov.b64 t, {%1,%2};\nst.relaxed.gpu.global.b64 [%0], t;\n}" ::"l"(p), "r"(a), "r"(b) : "memory");
}
__device__ __forceinline__ unsigned ld_acquire(const unsigned* p) {
    unsigned v;
    asm volatile("ld.acquire.gpu.global.u32 %0, [%1];" : "=r"(v) : "l"(p) : "memory");
    return v;
}
__device__ __forceinline__ void st_release(unsigned* p, unsigned v) {
    asm volatile("st.release.gpu.global.u32 [%0], %1;" ::"l"(p), "r"(v) : "memory");
}
__device__ __forceinline__ void ldsm4(uint32_t (&r)[4], uint32_t a) {
    asm volatile("ldmatrix.sync.aligned.m8n8.x4.shared.b16 {%0,%1,%2,%3}, [%4];"
                 : "=r"(r[0]), "=r"(r[1]), "=r"(r[2]), "=r"(r[3]) : "r"(a) : "memory");
}
__device__ __forceinline__ void ldsm4t(uint32_t (&r)[4], uint32_t a) {
    asm volatile("ldmatrix.sync.aligned.m8n8.x4.trans.shared.b16 {%0,%1,%2,%3}, [%4];"
                 : "=r"(r[0]), "=r"(r[1]), "=r"(r[2]), "=r"(r[3]) : "r"(a) : "memory");
}
__device__ __forceinline__ uint4 lds128(uint32_t a) {
    uint4 v;
    asm volatile("ld.shared.v4.u32 {%0, %1, %2, %3}, [%4];" : "=r"(v.x), "=r"(v.y), "=r"(v.z), "=r"(v.w) : "r"(a) : "memory");
    return v;
}
__device__ __forceinline__ uint32_t lds32(uint32_t a) {
    uint32_t v;
    asm volatile("ld.shared.u32 %0, [%1];" : "=r"(v) : "r"(a) : "memory");
    return v;
}
__device__ __forceinline__ void sts32(uint32_t a, uint32_t v) { asm volatile("st.shared.u32 [%0], %1;" ::"r"(a), "r"(v) : "memory"); }
__device__ __forceinline__ void mma16816(float (&d)[4], const uint32_t (&a)[4], uint32_t b0, uint32_t b1) {
    asm volatile("mma.sync.aligned.m16n8k16.row.col.f32.bf16.bf16.f32 {%0,%1,%2,%3}, {%4,%5,%6,%7}, {%8,%9}, {%0,%1,%2,%3};"
                 : "+f"(d[0]), "+f"(d[1]), "+f"(d[2]), "+f"(d[3])
                 : "r"(a[0]), "r"(a[1]), "r"(a[2]), "r"(a[3]), "r"(b0), "r"(b1));
}
__device__ __forceinline__ uint32_t prmt0(uint32_t a, uint32_t sel) {
    uint32_t d;
    asm volatile("prmt.b32 %0, %1, 0, %2;" : "=r"(d) : "r"(a), "r"(sel));
    return d;
}
__device__ __forceinline__ unsigned gt() {
    unsigned t;
    asm volatile("mov.u32 %0, %globaltimer_lo;" : "=r"(t));
    return t;
}
__device__ __forceinline__ unsigned clk32() {
    unsigned c;
    asm volatile("mov.u32 %0, %clock;" : "=r"(c));
    return c;
}
__device__ __forceinline__ int sreg_tid() {
    int v;
    asm volatile("mov.u32 %0, %%tid.x;" : "=r"(v));
    return v;
}
__device__ __forceinline__ int sreg_ctaid() {
    int v;
    asm volatile("mov.u32 %0, %%ctaid.x;" : "=r"(v));
    return v;
}
__device__ __forceinline__ float ex2(float x) {
    float y;
    asm("ex2.approx.ftz.f32 %0, %1;" : "=f"(y) : "f"(x));
    return y;
}
__device__ __forceinline__ float bf16r(float x) { return __bfloat162float(__float2bfloat16_rn(x)); }
__device__ __forceinline__ uint32_t packbf(float lo, float hi) {
    uint32_t r;
    asm("cvt.rn.bf16x2.f32 %0, %1, %2;" : "=r"(r) : "f"(hi), "f"(lo));
    return r;
}
__device__ __forceinline__ float bflo(uint32_t v) { return __uint_as_float(v << 16); }
__device__ __forceinline__ float bfhi(uint32_t v) { return __uint_as_float(v & 0xffff0000u); }
__device__ __forceinline__ uint32_t tagf(float v, uint32_t t8) { return (__float_as_uint(v) & 0xffffff00u) | t8; }
__device__ __forceinline__ float shx(float v, int m) { return __shfl_xor_sync(0xffffffffu, v, m); }

__device__ __forceinline__ uint64_t gdesc(uint32_t addr, uint32_t lbo, uint32_t sbo) {
    return (uint64_t)((addr & 0x3ffff) >> 4) | ((uint64_t)(lbo >> 4) << 16) | ((uint64_t)(sbo >> 4) << 32) | (1ull << 62);
}
__device__ __forceinline__ void wg_fence() { asm volatile("wgmma.fence.sync.aligned;" ::: "memory"); }
__device__ __forceinline__ void wg_commit() { asm volatile("wgmma.commit_group.sync.aligned;" ::: "memory"); }
__device__ __forceinline__ void wg_wait0() { asm volatile("wgmma.wait_group.sync.aligned 0;" ::: "memory"); }
template <int N> __device__ __forceinline__ void reg_fence(float (&r)[N]) {
#pragma unroll
    for (int i = 0; i < N; i++) asm volatile("" : "+f"(r[i])::"memory");
}
#define F8(a, o) "+f"(a[o]), "+f"(a[o + 1]), "+f"(a[o + 2]), "+f"(a[o + 3]), "+f"(a[o + 4]), "+f"(a[o + 5]), "+f"(a[o + 6]), "+f"(a[o + 7])
#define F32(a, o) F8(a, o), F8(a, o + 8), F8(a, o + 16), F8(a, o + 24)
__device__ __forceinline__ void wgmma_n64_ss(float (&d)[32], uint64_t da, uint64_t db, int scale_d) {
    asm volatile(
        "{\n.reg .pred p;\nsetp.ne.b32 p, %34, 0;\n"
        "wgmma.mma_async.sync.aligned.m64n64k16.f32.bf16.bf16 "
        "{%0,%1,%2,%3,%4,%5,%6,%7,%8,%9,%10,%11,%12,%13,%14,%15,%16,%17,%18,%19,%20,%21,%22,%23,%24,%25,%26,%27,%28,%29,%30,%31},"
        " %32, %33, p, 1, 1, 0, 0;\n}"
        : F32(d, 0) : "l"(da), "l"(db), "r"(scale_d));
}
__device__ __forceinline__ void wgmma_n32_ts(float (&d)[16], uint64_t da, uint64_t db) {
    asm volatile(
        "{\n.reg .pred p;\nsetp.ne.b32 p, 1, 0;\n"
        "wgmma.mma_async.sync.aligned.m64n32k16.f32.bf16.bf16 "
        "{%0,%1,%2,%3,%4,%5,%6,%7,%8,%9,%10,%11,%12,%13,%14,%15}, %16, %17, p, 1, 1, 1, 0;\n}"
        : F8(d, 0), F8(d, 8) : "l"(da), "l"(db));
}

struct Params {
    Scratch* scr;
    const uint32_t *ax, *bx;
    const char *k, *v, *wq;
    __nv_bfloat16* out;
};
struct Maps { CUtensorMap kv[2], qa, qb, wo[2], c, uk, uv; };

__device__ __forceinline__ void wait_flags(const unsigned* flags, unsigned tag, int lane) {
    for (int i = 0; !__all_sync(0xffffffffu, ld_acquire(flags + lane) == tag); i++) {
        if (i > SPIN_MAX) __trap();
        __nanosleep(BPOLL);
    }
}
__device__ __forceinline__ void load_slice(uint32_t dst, const CUtensorMap* map, int r, uint32_t bar) {
    mbar_expect(bar, 131072);
#pragma unroll
    for (int x = 0; x < 4; x++) tma2d(dst + x * 32768, map, r * 128 + (x & 1) * 64, (x >> 1) * 256, bar);
}
__device__ __forceinline__ void gemv_slice(uint32_t sb, int warp, int lane) {
    const int g = lane >> 2, tq = lane & 3;
    float d[4][4];
#pragma unroll
    for (int i = 0; i < 4; i++) d[i][0] = d[i][1] = d[i][2] = d[i][3] = 0.f;
    const uint32_t wb = sb + SB_STG + (warp >> 2) * 32768 + ((lane & 7) + 8 * (lane >> 4)) * 128 +
                        (((2 * (warp & 3) + ((lane >> 3) & 1)) ^ (lane & 7)) << 4);
    const uint32_t xb = sb + SB_X + ((g & 3) * 264 + tq) * 4;
#pragma unroll 1
    for (int k8 = 0; k8 < 4; k8++) {
        uint32_t a[8][4], b[8][2];
#pragma unroll
        for (int ks = 0; ks < 8; ks++) {
            ldsm4t(a[ks], wb + (k8 >> 1) * 65536 + (k8 & 1) * 16384 + ks * 2048);
            b[ks][0] = lds32(xb + k8 * 256 + ks * 32);
            b[ks][1] = lds32(xb + k8 * 256 + ks * 32 + 16);
        }
#pragma unroll
        for (int ks = 0; ks < 8; ks++) mma16816(d[ks & 3], a[ks], b[ks][0], b[ks][1]);
    }
    const float y0 = ((d[0][0] + d[1][0]) + (d[2][0] + d[3][0])) + ((d[0][1] + d[1][1]) + (d[2][1] + d[3][1]));
    const float y1 = ((d[0][2] + d[1][2]) + (d[2][2] + d[3][2])) + ((d[0][3] + d[1][3]) + (d[2][3] + d[3][3]));
    if (tq < 2) {
        sts32(sb + SB_QB + (tq * 128 + warp * 16 + g) * 4, __float_as_uint(y0));
        sts32(sb + SB_QB + (tq * 128 + warp * 16 + 8 + g) * 4, __float_as_uint(y1));
    }
}
__device__ __forceinline__ uint32_t wo_lane(uint32_t sb, int lane) {
    return sb + SB_STG + ((lane & 7) + 8 * (lane >> 4)) * 32 + ((((lane >> 3) & 1) ^ ((lane >> 2) & 1)) << 4);
}

__device__ __forceinline__ void main_bc(const Params& P, const Maps& M, uint8_t* sm TRARG) {
    const uint32_t sb = s2u(sm);
    const int tid = sreg_tid(), bx = sreg_ctaid(), lane = tid & 31, warp = tid >> 5, g = lane >> 2, tq = lane & 3;
    const int r = bx >> 2, isC = (bx >> 1) & 1;
    const uint32_t bar_w = sb + SB_BAR + 16, bar_x = sb + SB_BAR + 24, bar_h = sb + SB_BAR + 32;
    const unsigned tag = lds32(sb + SB_CNT + 4) + 1;
    Scratch* const S = P.scr;
    const float* yb = reinterpret_cast<const float*>(sm + SB_QB);
    uint2* const bfr = reinterpret_cast<uint2*>(sm + SB_QIMG) + ((warp & 3) * 32 + (g >> 1) * 8 + (warp >> 2) * 4 + tq) * 2 + (g & 1);
    float u0 = 0.f, u1 = 0.f;

    if (isC) {
        const uint32_t t8 = tag & 0xffu;
        if (CSLEEP) __nanosleep(CSLEEP);
        uint32_t wf[8][4];
#pragma unroll 1
        for (int pp = 0; pp < 8; pp++) {
            const int pair = warp * 8 + pp;
            const uint2* mlp = S->aml + pair * (CPG * 4);
            unsigned rdy;
            for (int it = 0;; it++) {
                rdy = __ballot_sync(0xffffffffu, (ld_b64(mlp + (lane & 7) * 4).y & 0xffu) == t8);
                if (pp == 7 ? rdy != 0 : rdy == 0xffffffffu) break;
                if (it > SPIN_MAX) __trap();
                __nanosleep(pp == 7 ? POLL_NS : POLL0_NS);
            }
            if (pp == 7) {
                mbar_wait(bar_h + (pair & 31) * 8, 0);
#pragma unroll
                for (int ks = 0; ks < 8; ks++) ldsm4t(wf[ks], wo_lane(sb, lane) + (pair & 31) * 4096 + ks * 512);
            }
            TR(3);
            const uint4* src = S->apart + pair * (CPG * 32) + lane;
            uint4 v[CPG];
            uint2 ml[CPG];
            unsigned need = (1u << CPG) - 1;
            for (int it = 0; need; it++) {
                const unsigned get = __popc(need & ~rdy) <= SPEC_K ? need : need & rdy;
                const unsigned fl0 = ld_b64(mlp + (lane & 7) * 4).y;
#pragma unroll
                for (int i = 0; i < CPG; i++)
                    if (get >> i & 1) { v[i] = ld_b128(src + i * 32); ml[i] = ld_b64(mlp + i * 4); }
                unsigned bad = 0;
#pragma unroll
                for (int i = 0; i < CPG; i++)
                    if ((((v[i].x ^ t8) | (ml[i].y ^ t8)) & 0xffu) != 0) bad |= 1u << i;
                need &= __reduce_or_sync(0xffffffffu, bad) | ~get;
                rdy = __ballot_sync(0xffffffffu, (fl0 & 0xffu) == t8);
                if (it > SPIN_MAX) __trap();
            }
            TR(2);
            float M4[CPG / 2], e[CPG];
#pragma unroll
            for (int i = 0; i < CPG / 2; i++) M4[i] = fmaxf(__uint_as_float(ml[2 * i].x), __uint_as_float(ml[2 * i + 1].x));
            const float MM = fmaxf(fmaxf(M4[0], M4[1]), fmaxf(M4[2], M4[3]));
#pragma unroll
            for (int i = 0; i < CPG; i++) e[i] = ex2((__uint_as_float(ml[i].x) - MM) * LOG2E);
            float ls[2], oa[4], ob[4];
#pragma unroll
            for (int i = 0; i < CPG; i++) ls[i & 1] = i < 2 ? e[i] * __uint_as_float(ml[i].y) : fmaf(e[i], __uint_as_float(ml[i].y), ls[i & 1]);
            float inv;
            asm("rcp.approx.ftz.f32 %0, %1;" : "=f"(inv) : "f"(ls[0] + ls[1]));
#pragma unroll
            for (int i = 0; i < CPG; i++) {
                float (&o)[4] = (i & 1) ? ob : oa;
                o[0] = i < 2 ? e[i] * __uint_as_float(v[i].x) : fmaf(e[i], __uint_as_float(v[i].x), o[0]);
                o[1] = i < 2 ? e[i] * __uint_as_float(v[i].y) : fmaf(e[i], __uint_as_float(v[i].y), o[1]);
                o[2] = i < 2 ? e[i] * __uint_as_float(v[i].z) : fmaf(e[i], __uint_as_float(v[i].z), o[2]);
                o[3] = i < 2 ? e[i] * __uint_as_float(v[i].w) : fmaf(e[i], __uint_as_float(v[i].w), o[3]);
            }
            const uint32_t b0 = packbf((oa[0] + ob[0]) * inv, (oa[1] + ob[1]) * inv), b1 = packbf((oa[2] + ob[2]) * inv, (oa[3] + ob[3]) * inv);
            if (pp == 7) {
                float d[4][4];
#pragma unroll
                for (int i = 0; i < 4; i++) d[i][0] = d[i][1] = d[i][2] = d[i][3] = 0.f;
#pragma unroll
                for (int ks = 0; ks < 8; ks++) mma16816(d[ks & 3], wf[ks], g == ks ? b0 : 0u, g == ks ? b1 : 0u);
                u0 = ((d[0][0] + d[0][1]) + (d[1][0] + d[1][1])) + ((d[2][0] + d[2][1]) + (d[3][0] + d[3][1]));
                u1 = ((d[0][2] + d[0][3]) + (d[1][2] + d[1][3])) + ((d[2][2] + d[2][3]) + (d[3][2] + d[3][3]));
            } else {
                bfr[pp * 256] = make_uint2(b0, b1);
                if (pp == 6) bar_arrive(4, 384);
            }
        }
    } else {
        float* xs = reinterpret_cast<float*>(sm + SB_X);
        const int crow0 = (r >> 4) * 8192 + (r & 15) * 64;
        {
            if (tid == 32) {
                if (BDELAY) __nanosleep(BDELAY);
                load_slice(sb + SB_STG, &M.qb, r, bar_w);
            }
            uint32_t* xh = reinterpret_cast<uint32_t*>(sm + SB_X) + tid;
            xh[0] = __ldg(P.bx + tid); xh[264] = 0; xh[528] = __ldg(P.bx + 256 + tid); xh[792] = 0;
            bar_sync(0, 256);
            mbar_wait(bar_w, 0);
            TR(0);
            gemv_slice(sb, warp, lane);
            bar_sync(0, 256);
            if (tid == 0) load_slice(sb + SB_STG, &M.uk, r, bar_w);
            uint32_t qb[8][2];
#pragma unroll
            for (int ks = 0; ks < 8; ks++) {
                const float2 a = *reinterpret_cast<const float2*>(yb + (g & 1) * 128 + ks * 16 + 2 * tq);
                const float2 b = *reinterpret_cast<const float2*>(yb + (g & 1) * 128 + ks * 16 + 8 + 2 * tq);
                qb[ks][0] = packbf(a.x, a.y);
                qb[ks][1] = packbf(b.x, b.y);
            }
            mbar_wait(bar_w, 1);
            const uint32_t wb = sb + SB_STG + (warp >> 2) * 65536 + ((warp & 3) * 64 + (lane & 15)) * 128;
#pragma unroll 1
            for (int mt = 0; mt < 4; mt++) {
                float d[4] = {0.f, 0.f, 0.f, 0.f};
#pragma unroll
                for (int ks = 0; ks < 8; ks++) {
                    uint32_t a[4];
                    ldsm4(a, wb + (ks >> 2) * 32768 + mt * 2048 + (((2 * (ks & 3) + (lane >> 4)) ^ (lane & 7)) << 4));
                    mma16816(d, a, qb[ks][0], qb[ks][1]);
                }
                if (tq == 0) {
                    const int c = warp * 64 + mt * 16 + g;
                    xs[c] = d[0]; xs[512 + c] = d[1]; xs[c + 8] = d[2]; xs[512 + c + 8] = d[3];
                }
            }
            bar_sync(0, 256);
            if (tid == 32) {
#pragma unroll 1
                for (int x = 0; x < 16; x++) {
                    if (!(x & 7)) mbar_expect(sb + SB_BAR + x, 65536);
                    tma2d_ef(sb + SB_STG + x * 8192, &M.c, (x & 7) * 64, crow0 + (x >> 3) * 1024, sb + SB_BAR + (x & 8));
                }
            }
            const int b = tid >> 7, lo = (tid >> 6) & 1, ch = tid & 63;
            float v[8];
#pragma unroll
            for (int i = 0; i < 8; i++) {
                const float x = xs[b * 512 + ch * 8 + i];
                v[i] = lo ? x - bf16r(x) : x;
            }
            const int row = 16 * (r >> 3) + (r & 7) + 8 * lo;
            S->qimg[b * 4096 + (ch >> 3) * 512 + row * 8 + ((ch & 7) ^ (r & 7))] =
                make_uint4(packbf(v[0], v[1]), packbf(v[2], v[3]), packbf(v[4], v[5]), packbf(v[6], v[7]));
            bar_sync(0, 256);
            if (warp == 0) {
                if (lane == 0) { __threadfence(); st_release(S->qflag + r, tag); }
                wait_flags(S->qflag, tag, lane);
                if (lane == 0) {
                    fence_async_all();
                    mbar_expect(bar_x, 65536);
                    bulk_g2s(sb + SB_QIMG, S->qimg + (r >> 4) * 4096, 65536, bar_x);
                }
            }
            mbar_wait(bar_x, 0);
        }
        TR(1);
        {
            const int wg = warp >> 2;
            float acc[4][16];
#pragma unroll
            for (int i = 0; i < 64; i++) acc[i >> 4][i & 15] = 0.f;
            const int head = (warp & 3) * 8 + g;
            const uint32_t pa = sb + SB_P + wg * 4096;
            float* al = reinterpret_cast<float*>(sm + SB_AL) + wg * 32;
            float m = -FLT_MAX, l = 0.f;
#pragma unroll 1
            for (int t = 0; t < 8; t++) {
                const uint32_t stg = sb + SB_STG + (t & 1) * 65536;
                mbar_wait(sb + SB_BAR + (t & 1) * 8, (t >> 1) & 1);
                float s[32];
                uint32_t qa = sb + SB_QIMG;
                asm volatile("" : "+r"(qa));
                wg_fence();
#pragma unroll
                for (int k = 0; k < 32; k++) {
                    const uint32_t off = (k >> 2) * 8192 + (k & 3) * 32;
                    wgmma_n64_ss(s, gdesc(qa + off, 16, 1024), gdesc(stg + off, 16, 1024), k > 0);
                }
                wg_commit();
                wg_wait0();
                reg_fence(s);
                float p[16], mx = m;
#pragma unroll
                for (int i = 0; i < 8; i++) {
                    p[2 * i] = bf16r(bf16r(s[4 * i] + s[4 * i + 2]) * SCALE);
                    p[2 * i + 1] = bf16r(bf16r(s[4 * i + 1] + s[4 * i + 3]) * SCALE);
                    mx = fmaxf(mx, fmaxf(p[2 * i], p[2 * i + 1]));
                }
                mx = fmaxf(mx, shx(mx, 1));
                mx = fmaxf(mx, shx(mx, 2));
                const float alpha = ex2((m - mx) * LOG2E);
                m = mx;
                float sum = 0.f;
#pragma unroll
                for (int i = 0; i < 8; i++) {
                    const float a = ex2((p[2 * i] - mx) * LOG2E), b = ex2((p[2 * i + 1] - mx) * LOG2E);
                    sum += a + b;
                    sts32(pa + head * 128 + ((i ^ g) << 4) + tq * 4, packbf(a, b));
                }
                l = fmaf(l, alpha, sum);
                if (tq == 0) al[head] = alpha;
                asm volatile("fence.proxy.async.shared::cta;" ::: "memory");
                bar_sync(1 + wg, 128);
#pragma unroll
                for (int j = 0; j < 4; j++) {
                    const float2 a = *reinterpret_cast<const float2*>(al + 8 * j + 2 * tq);
#pragma unroll
                    for (int i = 0; i < 4; i++) { acc[i][4 * j] *= a.x; acc[i][4 * j + 1] *= a.y; acc[i][4 * j + 2] *= a.x; acc[i][4 * j + 3] *= a.y; }
                }
#pragma unroll
                for (int i = 0; i < 4; i++) reg_fence(acc[i]);
                wg_fence();
#pragma unroll
                for (int kk = 0; kk < 4; kk++)
#pragma unroll
                    for (int i = 0; i < 4; i++)
                        wgmma_n32_ts(acc[i], gdesc(stg + (wg * 4 + i) * 8192 + kk * 2048, 8192, 1024), gdesc(pa + kk * 32, 16, 1024));
                wg_commit();
                wg_wait0();
#pragma unroll
                for (int i = 0; i < 4; i++) reg_fence(acc[i]);
                bar_sync(0, 256);
                if (tid == 0) {
                    if (t + 2 < 8) {
                        const uint32_t bar = sb + SB_BAR + (t & 1) * 8;
                        mbar_expect(bar, 65536);
#pragma unroll 1
                        for (int x = 0; x < 8; x++) tma2d_ef(stg + x * 8192, &M.c, x * 64, crow0 + (t + 2) * 1024, bar);
                    }
                    if (t == 7) load_slice(sb + SB_STG, &M.uv, r, bar_w);
                }
            }
            TR(2);
            float* dst = reinterpret_cast<float*>(sm + SB_QIMG + 2 * tq * PROW) + wg * 256 + (warp & 3) * 16 + g;
#pragma unroll
            for (int i = 0; i < 64; i++)
                dst[(((i >> 2) & 3) * 8 + (i & 1)) * (PROW / 4) + (i >> 4) * 64 + (i & 2) * 4] = acc[i >> 4][i & 15];
            l += shx(l, 1); l += shx(l, 2);
            if (wg == 0 && tq < 2) *reinterpret_cast<float4*>(sm + SB_QIMG + head * PROW + 2048 + tq * 16) = make_float4(m, l, 0.f, 0.f);
            asm volatile("fence.proxy.async.shared::cta;" ::: "memory");
            bar_sync(0, 256);
            if (warp == 0) {
                bulk_s2g(S->bpart + (lane * 32 + r) * (PROW / 16), sb + SB_QIMG + lane * PROW, PROW);
                asm volatile("cp.async.bulk.commit_group;" ::: "memory");
                asm volatile("cp.async.bulk.wait_group 0;" ::: "memory");
                fence_async_all();
                __threadfence();
                __syncwarp();
                if (lane == 0) st_release(S->bflag + r, tag);
                wait_flags(S->bflag, tag, lane);
                if (lane == 0) {
                    fence_async_all();
                    mbar_expect(bar_x, 32 * PROW);
                    bulk_g2s(sb + SB_QIMG, S->bpart + r * 32 * (PROW / 16), 32 * PROW, bar_x);
                }
            }
        }
        {
            const int b = tid >> 7, c4 = tid & 127;
            mbar_wait(bar_x, 1);
            TR(3);
            const float2 ml = *reinterpret_cast<const float2*>(sm + SB_QIMG + (b * 16 + (lane & 15)) * PROW + 2048);
            float MM = ml.x;
            MM = fmaxf(MM, shx(MM, 1)); MM = fmaxf(MM, shx(MM, 2)); MM = fmaxf(MM, shx(MM, 4)); MM = fmaxf(MM, shx(MM, 8));
            const float e = ex2((ml.x - MM) * LOG2E);
            float L = e * ml.y;
            L += shx(L, 1); L += shx(L, 2); L += shx(L, 4); L += shx(L, 8);
            const float wgt = e / L;
            float4 o = make_float4(0.f, 0.f, 0.f, 0.f);
#pragma unroll 4
            for (int i = 0; i < 16; i++) {
                const float w = __shfl_sync(0xffffffffu, wgt, i);
                const float4 v = *reinterpret_cast<const float4*>(sm + SB_QIMG + (b * 16 + i) * PROW + c4 * 16);
                o.x = fmaf(w, v.x, o.x); o.y = fmaf(w, v.y, o.y); o.z = fmaf(w, v.z, o.z); o.w = fmaf(w, v.w, o.w);
            }
            uint32_t* xh = reinterpret_cast<uint32_t*>(xs);
            const uint32_t h0 = packbf(o.x, o.y), h1 = packbf(o.z, o.w);
            *reinterpret_cast<uint2*>(xh + (2 * b) * 264 + c4 * 2) = make_uint2(h0, h1);
            *reinterpret_cast<uint2*>(xh + (2 * b + 1) * 264 + c4 * 2) =
                make_uint2(packbf(o.x - bflo(h0), o.y - bfhi(h0)), packbf(o.z - bflo(h1), o.w - bfhi(h1)));
            bar_sync(0, 256);
            mbar_wait(bar_w, 0);
            gemv_slice(sb, warp, lane);
            bar_sync(0, 256);
            if (tid < 64) {
                const float* y = yb + warp * 128 + 16 * g + 2 * tq;
                st_relaxed4(S->ctx + (warp * 32 + r) * 32 + lane, make_uint4(packbf(y[0], y[1]), tag, packbf(y[8], y[9]), tag));
            }
        }
        if (BPOLL) __nanosleep(4 * BPOLL);
#pragma unroll 1
        for (int pp = 0; pp < 8; pp++) {
            uint4 v;
            for (int it = 0;; it++) {
                v = ld_relaxed4(S->ctx + (warp * 8 + pp) * 32 + lane);
                if (__all_sync(0xffffffffu, v.y == tag && v.w == tag)) break;
                if (it > SPIN_MAX) __trap();
                __nanosleep(BPOLL);
            }
            bfr[pp * 256] = make_uint2(v.x, v.z);
        }
        TR(4);
        bar_arrive(4, 384);
    }
    float* red = reinterpret_cast<float*>(sm + SB_RED);
    red[warp * 64 + lane] = u0;
    red[warp * 64 + 32 + lane] = u1;
    TR(5);
    if (warp) {
        bar_arrive(5, 384);
    } else {
        bar_sync(5, 384);
        const int b = tid >> 4, c = tid & 15;
        const float4* q = reinterpret_cast<const float4*>(red) + b * 64 + c;
        const float4 x = q[0], y = q[16], z = q[32], w = q[48], p = reinterpret_cast<const float4*>(red + 512)[tid];
        const float s = (((x.x + x.y) + (x.z + x.w)) + ((y.x + y.y) + (y.z + y.w))) + (((z.x + z.y) + (z.z + z.w)) + ((w.x + w.y) + (w.z + w.w)));
        P.out[b * 1024 + (isC ? 0 : 512) + r * 16 + c] = __float2bfloat16_rn(s + ((p.x + p.y) + (p.z + p.w)));
        TR(6);
    }
    TROUT();
}

__global__ void __launch_bounds__(384, 1)
fused_decode_kernel(const Params P, const __grid_constant__ Maps M) {
    extern __shared__ __align__(1024) uint8_t sm[];
    const uint32_t sb = s2u(sm);
    const int tid = threadIdx.x, lane = tid & 31, bx = blockIdx.x;
    const int warp = __shfl_sync(0xffffffffu, tid >> 5, 0);
    const int g = lane >> 2, tq = lane & 3;
    Scratch* const S = P.scr;

    if (!(bx & 1)) {
        const int grp = (bx >> 1) & 7, crk = bx >> 4;
        const int rowbase = grp * (UPG * 64);
        auto issue = [&](int slot, unsigned tk) {
            const int row = rowbase + (int)((tk & ~255u) | ((tk + grp * ROT) & 255u)) * 64;
            const uint32_t full = sb + SA_FULL + slot * 16;
            sts32(sb + SA_META + slot * 4, tk >> 8);
            mbar_expect(full, 8192);
            tma2d_ef(sb + slot * 16384, &M.kv[0], 0, row, full);
            mbar_expect(full + 8, 8192);
            tma2d_ef(sb + slot * 16384 + 8192, &M.kv[1], 0, row, full + 8);
        };
        if (warp >= 8) {
            const int w = warp - 8;
            if (w >= NW) return;
            const bool one = elect();
            if (one) {
                if ((PFA & 1) && w < NI) prefetch_l2(P.k + (size_t)(rowbase + ((w * CPG + crk + grp * ROT) & 255) * 64) * 128, 8192);
                if ((PFA & 2) && w < NI) prefetch_l2(P.v + (size_t)(rowbase + ((w * CPG + crk + grp * ROT) & 255) * 64) * 128, 8192);
                mbar_init(sb + SA_FULL + w * 16, 1);
                mbar_init(sb + SA_FULL + w * 16 + 8, 1);
                mbar_init_fence();
                TR(3);
                if (w < NI) issue(w, w * CPG + crk);
                mbar_init(sb + SA_EMPTY + w * 8, 2);
                mbar_arrive(sb + SA_EMPTY + w * 8);
                if (w < NI) mbar_arrive(sb + SA_EMPTY + w * 8);
#pragma unroll
                for (int i = 1; i < SPW; i++) {
                    mbar_init(sb + SA_FULL + (w + i * NW) * 16, 1);
                    mbar_init(sb + SA_FULL + (w + i * NW) * 16 + 8, 1);
                    mbar_init(sb + SA_EMPTY + (w + i * NW) * 8, 2);
                    mbar_arrive(sb + SA_EMPTY + (w + i * NW) * 8);
                }
                sts32(sb + SA_LIM + w * 4, LIM);
                mbar_init_fence();
            }
            __syncwarp();
            bar_arrive(2, (NW + 1) * 32);
            bar_arrive(1, (2 * NW + 1) * 32);
            unsigned c = 0, tbase = 0;
            int slot = w < NI ? w + NW : w;
            uint32_t eph = 0;
#pragma unroll 1
            for (int n = w < NI ? 1 : 0;; n++) {
                unsigned tk = (n * NW + w) * CPG + crk;
                if (n == SPW) {
                    mbar_wait(sb + SA_EMPTY + w * 8, 1);
                    tbase = NSL * CPG - lds32(sb + SA_CNT + 32) * TICK_INC;
                }
                if (n >= SPW) {
                    const unsigned own = __shfl_sync(0xffffffffu, c, grp);
                    tk = own + tbase;
                    const int lag = (int)(__reduce_add_sync(0xffffffffu, c) - NG * own);
                    if (BAL && one) sts32(sb + SA_LIM + w * 4, lag > BAL * NG ? LIM + BALD : lag < -BAL * NG ? LIM - BALD2 : LIM);
                }
                mbar_wait(sb + SA_EMPTY + slot * 8, eph);
                if (tk >= UPG) {
                    if (one) { sts32(sb + SA_LIM + w * 4, 0); sts32(sb + SA_META + slot * 4, 8); mbar_arrive(sb + SA_FULL + slot * 16); }
                    return;
                }
                if (one) {
                    issue(slot, tk);
                    if (tk == UPG - FIRE_T) st_b64(S->fire + grp, gt(), lds32(sb + SA_CNT + 32) + 1);
                }
                TR(0);
                if (n >= SPW - 1) {
                    if (lane == grp) c = atom_inc(S->ctr + lane);
                    else if (BAL && lane < NG) c = ld_relaxed1(S->ctr + lane);
                }
                slot += NW;
                if (slot >= NSL) { slot -= NSL; eph ^= 1; }
                __syncwarp();
            }
        }
        if (warp == 0) {
            bool busy = lane < 2 * NI, first = true;
            uint32_t par = 0, lap = 0;
            int slot = NI;
            const unsigned c0 = clk32() + RAMP_T0;
            const uint32_t fb = sb + SA_FULL + (lane < 2 * NSL ? lane : 0) * 8, lw = sb + SA_LIM + ((lane >> 1) % NW) * 4;
            bar_sync(2, (NW + 1) * 32);
#pragma unroll 1
            for (int it = 0; it < SPIN_MAX; it++) {
                bool ok = true;
                if (busy) ok = mbar_test(fb, par);
                int lim = lds32(lw);
                if (first) lim = min(LIM0, 2 * NI + max((int)(clk32() - c0), 0) / RAMP_S);
                busy = busy && !ok && lim;
                const unsigned b = __ballot_sync(0xffffffffu, busy);
                if (!__any_sync(0xffffffffu, lim)) return;
                const bool mine = (lane >> 1) == slot;
                if (__any_sync(0xffffffffu, mine && (!lim || (__popc(b) <= lim - 2 && !(b >> (2 * slot) & 3))))) {
                    if (mine && lim) {
                        if (lane & 1) mbar_arrive(sb + SA_EMPTY + slot * 8);
                        busy = true; par = lap;
                    }
                    if (++slot == NSL) { slot = 0; lap ^= 1; first = false; }
                    it = 0;
                }
            }
            __trap();
        }
        if (warp != 1 && (warp < 4 || warp >= 4 + NW)) return;
        auto fetch_q = [&](int pl, unsigned tag) {
            uint4 v;
            for (int it = 0;; it++) {
                v = ld_relaxed4(S->qpub + (grp * 8 + pl) * 32 + lane);
                if (__all_sync(0xffffffffu, v.y == tag && v.w == tag)) break;
                if (it > SPIN_MAX) __trap();
                if (QPOLL) __nanosleep(QPOLL);
            }
            *reinterpret_cast<uint2*>(sm + SA_Q + pl * 256 + lane * 8) = make_uint2(v.x, v.z);
        };
        if (warp == 1) {
            const unsigned epoch = ld_relaxed1(S->epoch + bx * 8);
            if (lane == 0) { mbar_init(sb + SA_QBAR, 32); mbar_init_fence(); }
            if (lane < 9) sts32(sb + SA_CNT + lane * 4, lane < 8 ? 0u : epoch);
            bar_arrive(1, (2 * NW + 1) * 32);
            if (lane == 0) S->epoch[bx * 8] = epoch + 1;
            __nanosleep(3000);
#pragma unroll 1
            for (int pl = 1; pl < 8; pl++) fetch_q(pl, epoch + 1);
            mbar_arrive(sb + SA_QBAR);
            return;
        }
        const int cw = warp - 4;
        bar_sync(1, (2 * NW + 1) * 32);
        const unsigned tag = lds32(sb + SA_CNT + 32) + 1;
        if (QSLEEP) __nanosleep(QSLEEP);
        fetch_q(0, tag);
        __syncwarp();
        TR(0);

        const uint32_t t8 = tag & 0xffu;
        uint32_t koff[4], voff[4];
#pragma unroll
        for (int i = 0; i < 4; i++) {
            koff[i] = ((lane & 7) + 8 * ((lane >> 3) & 1)) * 128 + (((2 * i + (lane >> 4)) ^ (lane & 7)) << 4);
            voff[i] = ((lane & 7) + 8 * (lane >> 4)) * 128 + (((2 * i + ((lane >> 3) & 1)) ^ (lane & 7)) << 4);
        }
        uint32_t psel[4][2];
#pragma unroll
        for (int i = 0; i < 4; i++) {
            psel[i][0] = (g >> 1) != i ? 0x4444u : (g & 1) ? 0x1044u : 0x4410u;
            psel[i][1] = (g >> 1) != i ? 0x4444u : (g & 1) ? 0x3244u : 0x4432u;
        }
        uint32_t qf[4][2];
        auto load_q = [&](int pl) {
            const uint32_t q = sb + SA_Q + pl * 256 + ((g & 1) * 32 + tq) * 4;
#pragma unroll
            for (int ks = 0; ks < 4; ks++) { qf[ks][0] = lds32(q + ks * 32); qf[ks][1] = lds32(q + ks * 32 + 16); }
        };
        load_q(0);
        float acc[4][4], m = -FLT_MAX, l = 0.f;
#pragma unroll
        for (int i = 0; i < 4; i++) acc[i][0] = acc[i][1] = acc[i][2] = acc[i][3] = 0.f;
        int slot = cw, cur = 0;
        uint32_t ph = 0;
#pragma unroll 1
        for (;;) {
            mbar_wait(sb + SA_FULL + slot * 16, ph);
            const int pl = lds32(sb + SA_META + slot * 4);
            if (pl != cur) {
#pragma unroll 1
            for (; cur != pl; cur++) {
                float* s0 = reinterpret_cast<float*>(sm + SA_SLOT) + cur * (NW * 132);
                float* sw = s0 + cw * 132 + tq * 16 + (g >> 1) * 4 + (g & 1);
                sw[0] = (acc[0][0] + acc[1][0]) + (acc[2][0] + acc[3][0]);
                sw[2] = (acc[0][2] + acc[1][2]) + (acc[2][2] + acc[3][2]);
                sw[64] = (acc[0][1] + acc[1][1]) + (acc[2][1] + acc[3][1]);
                sw[66] = (acc[0][3] + acc[1][3]) + (acc[2][3] + acc[3][3]);
                if (lane == 0) *reinterpret_cast<float2*>(s0 + cw * 132 + 128) = make_float2(m, l);
                __syncwarp();
                int old = 0;
                if (lane == 0) asm volatile("atom.acq_rel.cta.shared.add.u32 %0, [%1], 1;" : "=r"(old) : "r"(sb + SA_CNT + cur * 4) : "memory");
                if (__shfl_sync(0xffffffffu, old, 0) == NW - 1) {
                    float2 ml[NW];
                    float4 v[NW];
#pragma unroll
                    for (int w = 0; w < NW; w++) {
                        ml[w] = *reinterpret_cast<const float2*>(s0 + w * 132 + 128);
                        v[w] = *reinterpret_cast<const float4*>(s0 + w * 132 + lane * 4);
                    }
                    float MM = ml[0].x;
#pragma unroll
                    for (int w = 1; w < NW; w++) MM = fmaxf(MM, ml[w].x);
                    float4 o = make_float4(0.f, 0.f, 0.f, 0.f);
                    float L = 0.f;
#pragma unroll
                    for (int w = 0; w < NW; w++) {
                        const float e = ex2((ml[w].x - MM) * LOG2E);
                        o.x = fmaf(e, v[w].x, o.x); o.y = fmaf(e, v[w].y, o.y); o.z = fmaf(e, v[w].z, o.z); o.w = fmaf(e, v[w].w, o.w);
                        L = fmaf(e, ml[w].y, L);
                    }
                    const int rec = (grp * 8 + cur) * CPG + crk;
                    st_b128(S->apart + rec * 32 + lane, make_uint4(tagf(o.x, t8), __float_as_uint(o.y), __float_as_uint(o.z), __float_as_uint(o.w)));
                    if (lane < 4) st_b64(S->aml + rec * 4 + lane, __float_as_uint(MM), tagf(L, t8));
                    if (PLACE && cur == 6) st_b128(S->apart + (rec + CPG) * 32 + lane, make_uint4(t8 ^ 0x80u, 0, 0, 0));
                    TR(2);
                }
#pragma unroll
                for (int i = 0; i < 4; i++) acc[i][0] = acc[i][1] = acc[i][2] = acc[i][3] = 0.f;
                m = -FLT_MAX; l = 0.f;
            }
                if (pl == 8) break;
                mbar_wait(sb + SA_QBAR, 0);
                load_q(pl);
            }
            float s4[4][4];
            const uint32_t kb = sb + slot * 16384;
#pragma unroll
            for (int j = 0; j < 4; j++) {
                s4[j][0] = s4[j][1] = s4[j][2] = s4[j][3] = 0.f;
                const bool on = (g >> 1) == j;
#pragma unroll
                for (int ks = 0; ks < 4; ks++) {
                    uint32_t a[4];
                    ldsm4(a, kb + j * 2048 + koff[ks]);
                    mma16816(s4[j], a, on ? qf[ks][0] : 0u, on ? qf[ks][1] : 0u);
                }
            }
            float d[4];
#pragma unroll
            for (int r = 0; r < 4; r++) d[r] = (s4[0][r] + s4[1][r]) + (s4[2][r] + s4[3][r]);
            float sa = (g & 1) ? d[1] : d[0], sc = (g & 1) ? d[3] : d[2];
            sa += shx(sa, 4); sc += shx(sc, 4);
            sa = bf16r(bf16r(sa) * SCALE); sc = bf16r(bf16r(sc) * SCALE);
            float mx = fmaxf(sa, sc);
            mx = fmaxf(mx, shx(mx, 8));
            mx = fmaxf(mx, shx(mx, 16));
            mx = fmaxf(mx, shx(mx, 1));
            mx = fmaxf(mx, shx(mx, 2));
            mx = fmaxf(mx, m);
            const float alpha = ex2((m - mx) * LOG2E);
            m = mx;
            const float pa = ex2((sa - mx) * LOG2E), pc = ex2((sc - mx) * LOG2E);
            const uint32_t pk = packbf(pa, pc);
            uint32_t pb[4][4][2];
#pragma unroll
            for (int j = 0; j < 4; j++) {
                const uint32_t pj = __shfl_sync(0xffffffffu, pk, 8 * tq + j);
#pragma unroll
                for (int i = 0; i < 4; i++) { pb[j][i][0] = prmt0(pj, psel[i][0]); pb[j][i][1] = prmt0(pj, psel[i][1]); }
            }
            float ps = pa + pc;
            ps += shx(ps, 8); ps += shx(ps, 16); ps += shx(ps, 1); ps += shx(ps, 2);
            l = fmaf(l, alpha, ps);
#pragma unroll
            for (int i = 0; i < 4; i++) { acc[i][0] *= alpha; acc[i][1] *= alpha; acc[i][2] *= alpha; acc[i][3] *= alpha; }
            mbar_wait(sb + SA_FULL + slot * 16 + 8, ph);
            TR(1);
            const uint32_t vb = kb + 8192;
#pragma unroll
            for (int i = 0; i < 4; i++)
#pragma unroll
                for (int j = 0; j < 4; j++) {
                    uint32_t a[4];
                    ldsm4t(a, vb + j * 2048 + voff[i]);
                    mma16816(acc[j], a, pb[j][i][0], pb[j][i][1]);
                }
            __syncwarp();
            if (lane == 0) mbar_arrive(sb + SA_EMPTY + slot * 8);
            slot += NW;
            if (slot >= NSL) { slot -= NSL; ph ^= 1; }
        }
        TROUT();
        return;
    }

    const int r = bx >> 2, isC = (bx >> 1) & 1;
    const uint32_t bar_h = sb + SB_BAR + 32;
    if (warp >= 8) {
        const int x = warp & 3;
        const uint32_t wlane = wo_lane(sb, lane);
        bar_sync(4, 384);
        asm volatile("prefetch.tensormap [%0];" ::"l"(&M.wo[isC]) : "memory");
        if (x == 0) {
            const unsigned tag = lds32(sb + SB_CNT + 4) + 1;
            uint2 f;
            for (int it = 0;; it++) {
                f = ld_b64(S->fire + (lane & 7));
                if (__all_sync(0xffffffffu, f.y == tag)) break;
                if (it > SPIN_MAX) __trap();
                __nanosleep(FPOLL);
            }
            const unsigned t0 = __shfl_sync(0xffffffffu, f.x, 0);
            const unsigned t1 = t0 + (__reduce_add_sync(0xffffffffu, (int)(f.x - t0)) >> 5) + FIRE_NS + isC * FIRE_C;
            TR(2);
            for (int it = 0; (int)(gt() - t1) < 0 && it < 4096; it++) {}
            if (elect()) {
                TR(0);
#pragma unroll 1
                for (int y = 0; y < 32; y++) {
                    for (int it = 0; (int)(gt() - t1) < (y - FIRE_B) * FIRE_DT && it < 4096; it++) {}
                    const int h = (y & 3) * 8 + (((y >> 2) - isC) & 7);
                    mbar_expect(bar_h + h * 8, 4096);
                    tma2d(sb + SB_STG + h * 4096, &M.wo[isC], r * 16, h * 128, bar_h + h * 8);
                }
            }
            __syncwarp();
        }
        float e[4][4];
#pragma unroll
        for (int i = 0; i < 4; i++) e[i][0] = e[i][1] = e[i][2] = e[i][3] = 0.f;
#pragma unroll 1
        for (int k = 0; k < 8 - isC; k++) {
            const uint32_t bp = sb + SB_QIMG + ((k * 4 + x) * 32 + (lane & 7)) * 16;
            const uint32_t wa = wlane + (x * 8 + k) * 4096;
            uint4 b[4];
#pragma unroll
            for (int j = 0; j < 4; j++) b[j] = lds128(bp + j * 128);
            mbar_wait(bar_h + (x * 8 + k) * 8, 0);
            TR(1);
            uint32_t a[8][4];
#pragma unroll
            for (int j = 0; j < 8; j++) ldsm4t(a[j], wa + j * 512);
#pragma unroll
            for (int j = 0; j < 8; j++)
                mma16816(e[j & 3], a[j], (j & 1) ? b[j >> 1].z : b[j >> 1].x, (j & 1) ? b[j >> 1].w : b[j >> 1].y);
        }
        if (tq < 2) {
            float* rx = reinterpret_cast<float*>(sm + SB_RED) + 512 + (tq * 16 + g) * 4 + x;
            rx[0] = tq ? (e[0][1] + e[1][1]) + (e[2][1] + e[3][1]) : (e[0][0] + e[1][0]) + (e[2][0] + e[3][0]);
            rx[32] = tq ? (e[0][3] + e[1][3]) + (e[2][3] + e[3][3]) : (e[0][2] + e[1][2]) + (e[2][2] + e[3][2]);
        }
        bar_arrive(5, 384);
        TROUT();
        return;
    }

    {
        const uint32_t bar_q = bar_h + 256 + warp * 8, box = sb + SB_QIMG + warp * 8192;
        if (elect()) {
            if (PFQ) prefetch_l2(P.wq + ((bx >> 1) * 8 + warp) * 8192, PFQ);
            mbar_init(bar_q, 1);
            mbar_init_fence();
            mbar_expect(bar_q, 8192 + (XBULK ? 256 : 0));
            tma2d(box, &M.qa, (bx >> 1) * 64, warp * 64, bar_q);
            if (XBULK) {
                bulk_g2s(sb + SB_P + 4096 + warp * 288, P.ax + warp * 32, 128, bar_q);
                bulk_g2s(sb + SB_P + 4096 + warp * 288 + 144, P.ax + 256 + warp * 32, 128, bar_q);
            }
        }
        const uint32_t* x = P.ax + (g & 1) * 256 + warp * 32 + tq;
        uint32_t b[8];
        if (!XBULK) {
#pragma unroll
            for (int i = 0; i < 8; i++) b[i] = __ldg(x + i * 4);
        }
        unsigned epoch = 0;
        if (warp < 2) epoch = ld_relaxed1(S->epoch + bx * 8);
        uint4* const qdst = S->qpub + ((lane >> 4) * 32 + r) * 32 + isC * 16 + (lane & 15);
        if (PLACE && warp == 0) st_relaxed4(qdst, make_uint4(0, 0, 0, 0));
        if (tid == 32) {
#pragma unroll
            for (int i = 0; i < 36; i++) mbar_init(sb + SB_BAR + i * 8, 1);
            mbar_init_fence();
            sts32(sb + SB_CNT + 4, epoch);
        }
        __syncwarp();
        mbar_wait(bar_q, 0);
        TR(0);
        if (XBULK) {
#pragma unroll
            for (int i = 0; i < 8; i++) b[i] = lds32(sb + SB_P + 4096 + warp * 288 + (g & 1) * 144 + tq * 4 + i * 16);
        }
        float d[4][4];
        uint32_t a[4][4][4];
#pragma unroll
        for (int i = 0; i < 4; i++) {
            d[i][0] = d[i][1] = d[i][2] = d[i][3] = 0.f;
#pragma unroll
            for (int ks = 0; ks < 4; ks++)
                ldsm4t(a[i][ks], box + ks * 2048 + ((lane & 7) + 8 * (lane >> 4)) * 128 + (((2 * i + ((lane >> 3) & 1)) ^ (lane & 7)) << 4));
        }
#pragma unroll
        for (int ks = 0; ks < 4; ks++)
#pragma unroll
            for (int i = 0; i < 4; i++) mma16816(d[i], a[i][ks], b[2 * ks], b[2 * ks + 1]);
        float* qred = reinterpret_cast<float*>(sm + SB_P);
#pragma unroll
        for (int c = 0; c < 4; c++)
            qred[warp * 128 + (c & 1) * 64 + tq * 16 + (c >> 1) * 8 + g] = tq == 0 ? d[0][c] : tq == 1 ? d[1][c] : tq == 2 ? d[2][c] : d[3][c];
        bar_sync(0, 256);
        if (warp == 0) {
            float4 v[8];
#pragma unroll
            for (int w = 0; w < 8; w++) v[w] = *reinterpret_cast<const float4*>(qred + w * 128 + lane * 4);
#pragma unroll
            for (int o = 4; o; o >>= 1)
#pragma unroll
                for (int w = 0; w < o; w++) { v[w].x += v[w + o].x; v[w].y += v[w + o].y; v[w].z += v[w + o].z; v[w].w += v[w + o].w; }
            st_relaxed4(qdst, make_uint4(packbf(v[0].x, v[0].y), epoch + 1, packbf(v[0].z, v[0].w), epoch + 1));
            if (lane == 0) S->epoch[bx * 8] = epoch + 1;
        }
        TR(1);
    }
    main_bc(P, M, sm TRPASS);
}

typedef CUresult (*EncodeFn)(CUtensorMap*, CUtensorMapDataType, cuuint32_t, void*, const cuuint64_t*, const cuuint64_t*,
                             const cuuint32_t*, const cuuint32_t*, CUtensorMapInterleave, CUtensorMapSwizzle,
                             CUtensorMapL2promotion, CUtensorMapFloatOOBfill);

void make_map(EncodeFn enc, CUtensorMap* m, const void* base, uint64_t cols, uint64_t rows, uint32_t bc, uint32_t br,
              CUtensorMapL2promotion promo, CUtensorMapSwizzle sw = CU_TENSOR_MAP_SWIZZLE_128B) {
    cuuint64_t dims[2] = {cols, rows};
    cuuint64_t strides[1] = {cols * 2};
    cuuint32_t box[2] = {bc, br};
    cuuint32_t es[2] = {1, 1};
    enc(m, CU_TENSOR_MAP_DATA_TYPE_BFLOAT16, 2, const_cast<void*>(base), dims, strides, box, es,
        CU_TENSOR_MAP_INTERLEAVE_NONE, sw, promo, CU_TENSOR_MAP_FLOAT_OOB_FILL_NONE);
}

}

extern "C" void kernel_launch(void* const* d_in, const int* in_sizes, int n_in, void* d_out, int out_size) {
    (void)in_sizes; (void)n_in; (void)out_size;
    static EncodeFn enc = nullptr;
    static void* scr = nullptr;
    if (!enc) {
        void* fn = nullptr;
        cudaDriverEntryPointQueryResult qr;
        cudaGetDriverEntryPoint("cuTensorMapEncodeTiled", &fn, cudaEnableDefault, &qr);
        enc = (EncodeFn)fn;
        cudaGetSymbolAddress(&scr, g_scr);
        cudaFuncSetAttribute(fused_decode_kernel, cudaFuncAttributeMaxDynamicSharedMemorySize, SMEM_BYTES);
    }
    Maps m;
    make_map(enc, &m.kv[0], d_in[1], 64, 1048576, 64, 64, CU_TENSOR_MAP_L2_PROMOTION_NONE);
    make_map(enc, &m.kv[1], d_in[2], 64, 1048576, 64, 64, CU_TENSOR_MAP_L2_PROMOTION_NONE);
    make_map(enc, &m.qa, d_in[3], 4096, 512, 64, 64, QPROMO);
    make_map(enc, &m.qb, d_in[7], 4096, 512, 64, 256, CU_TENSOR_MAP_L2_PROMOTION_L2_256B);
    make_map(enc, &m.wo[0], d_in[10], 512, 4096, 16, 128, WPROMO, CU_TENSOR_MAP_SWIZZLE_32B);
    make_map(enc, &m.wo[1], d_in[4], 512, 4096, 16, 128, WPROMO, CU_TENSOR_MAP_SWIZZLE_32B);
    make_map(enc, &m.c, d_in[6], 512, 16384, 64, 64, CU_TENSOR_MAP_L2_PROMOTION_NONE);
    make_map(enc, &m.uk, d_in[8], 4096, 512, 64, 256, CU_TENSOR_MAP_L2_PROMOTION_L2_256B);
    make_map(enc, &m.uv, d_in[9], 4096, 512, 64, 256, CU_TENSOR_MAP_L2_PROMOTION_L2_256B);
    Params p;
    p.scr = (Scratch*)scr;
    p.ax = (const uint32_t*)d_in[0];
    p.bx = (const uint32_t*)d_in[5];
    p.out = (__nv_bfloat16*)d_out;
    p.k = (const char*)d_in[1];
    p.v = (const char*)d_in[2];
    p.wq = (const char*)d_in[3];
    fused_decode_kernel<<<128, 384, SMEM_BYTES, cudaStreamPerThread>>>(p, m);
}
```

```cpp
#include <cuda_runtime.h>
#include <cuda_bf16.h>
#include <cuda.h>
#include <stdint.h>
#include <float.h>

#define NW 4
#define LIM 12
#define ROT 32
#define BDELAY 1000
#define POLL_NS 300
#define FIRE_T 60
#define FIRE_NS 3200
#define FIRE_DT 78
#define FIRE_B 0
#define FIRE_C 0
#define SPEC_K 3

#define BAL 4
#define BALD 1
#define BALD2 1
#define DIRECT7 1
#define PLACE 1
#define POLL0_NS 700
#define NI SKEW
#define LIM0 10
#define RAMP_S 256
#define RAMP_T0 300
#define PFA 3
#define PFQ 4096
#define BPOLL 1000
#define PADW 1088
#define FPOLL 300
#define QPOLL 0
#define SKEW 2
#define PF_DT 135
#define PF_T0 0
#define PF_N 32
#define REC_I 12
#define EARLY_C 4
#define EARLY_B 0
#define NSA 12
#define NSB 12
#define FIRE_DTA 78
#define FIRE_DTB 0
#define EXP 0
#define XBULK 1
#define QSLEEP 1500
#define LATET 1
#define CSLEEP 8000
#define WPROMO CU_TENSOR_MAP_L2_PROMOTION_L2_128B
#define QPROMO CU_TENSOR_MAP_L2_PROMOTION_NONE

namespace {

constexpr int NG = 8, CPG = 8;
constexpr int UPG = 2048;
constexpr int NSL = 12, SPW = NSL / NW;
constexpr unsigned TICK_INC = UPG - NSL * CPG + NW * CPG;
static_assert(NSL % NW == 0 && NW <= 4, "slot rotation");
constexpr int SPIN_MAX = 1 << 22;
constexpr float LOG2E = 1.4426950408889634f;
constexpr float SCALE = 0.08838834764831845f;
constexpr uint64_t EVICT_FIRST = 0x12F0000000000000ull;

constexpr int SA_SLOT = NSL * 16384;
constexpr int SA_Q    = SA_SLOT + 8 * NW * 132 * 4;
constexpr int SA_FULL = SA_Q + 2048;
constexpr int SA_EMPTY = SA_FULL + NSL * 16;
constexpr int SA_GOV  = SA_EMPTY + NSL * 8;
constexpr int SA_QBAR = SA_GOV + NSL * 8;
constexpr int SA_META = SA_QBAR + 8;
constexpr int SA_LIM  = SA_META + NSL * 4;
constexpr int SA_CNT  = SA_LIM + 16;
constexpr int SA_END  = SA_CNT + 64;
constexpr int PROW    = 2080;
constexpr int SB_STG  = 0;
constexpr int SB_QIMG = 131072;
constexpr int SB_P    = SB_QIMG + 32 * PROW;
constexpr int SB_AL   = SB_P + 8192;
constexpr int SB_X    = SB_AL + 256;
static_assert(SB_P % 1024 == 0, "swizzle atom");
constexpr int SB_QB   = SB_X + 4352;
constexpr int NT      = 40;
constexpr int SC_FR   = NT * 4096;
constexpr int SC_RED  = SB_QB + 1024;
constexpr int SB_BAR  = SC_RED + 2560;
constexpr int SB_CNT  = SB_BAR + (12 + NT) * 8;
static_assert(SC_FR + 16384 <= SB_P && 2 * (32 - NSA) <= NT && 2 * (32 - NSB) <= NT && NSA <= 16 && NSB <= 16, "projection slots");
constexpr int SB_END  = SB_CNT + 64;
constexpr int SMEM_BYTES = (SA_END > SB_END ? SA_END : SB_END);
static_assert(SMEM_BYTES <= 232448, "shared memory");

struct Scratch {
    uint4    bpart[32 * 32 * (PROW / 16)];
    uint4    apart[64 * CPG * 32];
    uint4    qimg[2 * 4096];
    uint4    qpub[64 * 32];
    uint4    frag[2][64 * 32];
    uint2    snd[32 * 32];
    uint2    aml[64 * CPG * 4];
    unsigned epoch[128 * 8];
    unsigned ctr[PADW];
    uint2    fire[PADW / 2];
    unsigned qflag[PADW], bflag[PADW];
};
__device__ __align__(1024) Scratch g_scr;

#define TRARG
#define TRPASS
#define TR(k)
#define TROUT()

__device__ __forceinline__ uint32_t s2u(const void* p) { return (uint32_t)__cvta_generic_to_shared(p); }
__device__ __forceinline__ bool elect() {
    uint32_t ok;
    asm volatile("{\n.reg .pred p;\nelect.sync _|p, 0xffffffff;\nselp.u32 %0,1,0,p;\n}" : "=r"(ok));
    return ok;
}
__device__ __forceinline__ void mbar_init(uint32_t b, int c) {
    asm volatile("mbarrier.init.shared::cta.b64 [%0], %1;" ::"r"(b), "r"(c) : "memory");
}
__device__ __forceinline__ void mbar_init_fence() { asm volatile("fence.mbarrier_init.release.cluster;" ::: "memory"); }
__device__ __forceinline__ void mbar_expect(uint32_t b, uint32_t bytes) {
    asm volatile("mbarrier.arrive.expect_tx.shared::cta.b64 _, [%0], %1;" ::"r"(b), "r"(bytes) : "memory");
}
__device__ __forceinline__ void mbar_arrive(uint32_t b) {
    asm volatile("mbarrier.arrive.shared::cta.b64 _, [%0];" ::"r"(b) : "memory");
}
__device__ __forceinline__ bool mbar_test(uint32_t b, uint32_t ph) {
    uint32_t ok;
    asm volatile("{\n.reg .pred p;\nmbarrier.test_wait.parity.shared::cta.b64 p, [%1], %2;\nselp.u32 %0,1,0,p;\n}"
                 : "=r"(ok) : "r"(b), "r"(ph) : "memory");
    return ok;
}
__device__ __forceinline__ void mbar_wait(uint32_t b, uint32_t ph) {
    asm volatile("{\n.reg .pred p;\n.reg .u32 n;\nmov.u32 n, 0;\n"
                 "W: mbarrier.try_wait.parity.shared::cta.b64 p, [%0], %1;\n@p bra.uni D;\n"
                 "add.u32 n, n, 1;\nsetp.lt.u32 p, n, %2;\n@p bra.uni W;\ntrap;\nD:\n}"
                 ::"r"(b), "r"(ph), "n"(SPIN_MAX) : "memory");
}
__device__ __forceinline__ void tma2d(uint32_t dst, const CUtensorMap* map, int c0, int c1, uint32_t bar) {
    asm volatile("cp.async.bulk.tensor.2d.shared::cluster.global.mbarrier::complete_tx::bytes [%0], [%1, {%3, %4}], [%2];"
                 ::"r"(dst), "l"(map), "r"(bar), "r"(c0), "r"(c1) : "memory");
}
__device__ __forceinline__ void tma2d_ef(uint32_t dst, const CUtensorMap* map, int c0, int c1, uint32_t bar) {
    asm volatile("cp.async.bulk.tensor.2d.shared::cluster.global.mbarrier::complete_tx::bytes.L2::cache_hint [%0], [%1, {%3, %4}], [%2], %5;"
                 ::"r"(dst), "l"(map), "r"(bar), "r"(c0), "r"(c1), "l"(EVICT_FIRST) : "memory");
}
__device__ __forceinline__ void bulk_g2s(uint32_t dst, const void* src, uint32_t bytes, uint32_t bar) {
    asm volatile("cp.async.bulk.shared::cluster.global.mbarrier::complete_tx::bytes [%0], [%1], %2, [%3];"
                 ::"r"(dst), "l"(src), "r"(bytes), "r"(bar) : "memory");
}
__device__ __forceinline__ void prefetch_l2(const void* src, uint32_t bytes) {
    asm volatile("cp.async.bulk.prefetch.L2.global.L2::cache_hint [%0], %1, %2;" ::"l"(src), "r"(bytes), "l"(EVICT_FIRST) : "memory");
}
__device__ __forceinline__ void bulk_s2g(void* dst, uint32_t src, uint32_t bytes) {
    asm volatile("cp.async.bulk.global.shared::cta.bulk_group [%0], [%1], %2;" ::"l"(dst), "r"(src), "r"(bytes) : "memory");
}
__device__ __forceinline__ void fence_async_all() { asm volatile("fence.proxy.async;" ::: "memory"); }
__device__ __forceinline__ void bar_sync(int id, int n) { asm volatile("bar.sync %0, %1;" ::"r"(id), "r"(n) : "memory"); }
__device__ __forceinline__ void bar_arrive(int id, int n) { asm volatile("bar.arrive %0, %1;" ::"r"(id), "r"(n) : "memory"); }
__device__ __forceinline__ uint4 ld_relaxed4(const void* p) {
    uint4 v;
    asm volatile("ld.relaxed.gpu.global.v4.u32 {%0,%1,%2,%3}, [%4];"
                 : "=r"(v.x), "=r"(v.y), "=r"(v.z), "=r"(v.w) : "l"(p) : "memory");
    return v;
}
__device__ __forceinline__ unsigned ld_relaxed1(const void* p) {
    unsigned v;
    asm volatile("ld.relaxed.gpu.global.u32 %0, [%1];" : "=r"(v) : "l"(p) : "memory");
    return v;
}
__device__ __forceinline__ unsigned atom_inc(unsigned* p) {
    unsigned v;
    asm volatile("atom.relaxed.gpu.global.add.u32 %0, [%1], 1;" : "=r"(v) : "l"(p) : "memory");
    return v;
}
__device__ __forceinline__ void st_relaxed4(void* p, uint4 v) {
    asm volatile("st.relaxed.gpu.global.v4.u32 [%0], {%1,%2,%3,%4};" ::"l"(p), "r"(v.x), "r"(v.y), "r"(v.z), "r"(v.w) : "memory");
}
__device__ __forceinline__ uint4 ld_b128(const void* p) {
    uint4 v;
    asm volatile("{\n.reg .b128 t;\nld.relaxed.gpu.global.b128 t, [%4];\nmov.b128 {%0,%1,%2,%3}, t;\n}"
                 : "=r"(v.x), "=r"(v.y), "=r"(v.z), "=r"(v.w) : "l"(p) : "memory");
    return v;
}
__device__ __forceinline__ void st_b128(void* p, uint4 v) {
    asm volatile("{\n.reg .b128 t;\nmov.b128 t, {%1,%2,%3,%4};\nst.relaxed.gpu.global.b128 [%0], t;\n}"
                 ::"l"(p), "r"(v.x), "r"(v.y), "r"(v.z), "r"(v.w) : "memory");
}
__device__ __forceinline__ uint2 ld_b64(const void* p) {
    uint2 v;
    asm volatile("{\n.reg .b64 a;\nld.relaxed.gpu.global.b64 a, [%2];\nmov.b64 {%0,%1}, a;\n}" : "=r"(v.x), "=r"(v.y) : "l"(p) : "memory");
    return v;
}
__device__ __forceinline__ void st_b64(void* p, uint32_t a, uint32_t b) {
    asm volatile("{\n.reg .b64 t;\nmov.b64 t, {%1,%2};\nst.relaxed.gpu.global.b64 [%0], t;\n}" ::"l"(p), "r"(a), "r"(b) : "memory");
}
__device__ __forceinline__ unsigned ld_acquire(const unsigned* p) {
    unsigned v;
    asm volatile("ld.acquire.gpu.global.u32 %0, [%1];" : "=r"(v) : "l"(p) : "memory");
    return v;
}
__device__ __forceinline__ void st_release(unsigned* p, unsigned v) {
    asm volatile("st.release.gpu.global.u32 [%0], %1;" ::"l"(p), "r"(v) : "memory");
}
__device__ __forceinline__ void ldsm4(uint32_t (&r)[4], uint32_t a) {
    asm volatile("ldmatrix.sync.aligned.m8n8.x4.shared.b16 {%0,%1,%2,%3}, [%4];"
                 : "=r"(r[0]), "=r"(r[1]), "=r"(r[2]), "=r"(r[3]) : "r"(a) : "memory");
}
__device__ __forceinline__ void ldsm4t(uint32_t (&r)[4], uint32_t a) {
    asm volatile("ldmatrix.sync.aligned.m8n8.x4.trans.shared.b16 {%0,%1,%2,%3}, [%4];"
                 : "=r"(r[0]), "=r"(r[1]), "=r"(r[2]), "=r"(r[3]) : "r"(a) : "memory");
}
__device__ __forceinline__ uint4 lds128(uint32_t a) {
    uint4 v;
    asm volatile("ld.shared.v4.u32 {%0, %1, %2, %3}, [%4];" : "=r"(v.x), "=r"(v.y), "=r"(v.z), "=r"(v.w) : "r"(a) : "memory");
    return v;
}
__device__ __forceinline__ uint32_t lds32(uint32_t a) {
    uint32_t v;
    asm volatile("ld.shared.u32 %0, [%1];" : "=r"(v) : "r"(a) : "memory");
    return v;
}
__device__ __forceinline__ void sts32(uint32_t a, uint32_t v) { asm volatile("st.shared.u32 [%0], %1;" ::"r"(a), "r"(v) : "memory"); }
__device__ __forceinline__ void mma16816(float (&d)[4], const uint32_t (&a)[4], uint32_t b0, uint32_t b1) {
    asm volatile("mma.sync.aligned.m16n8k16.row.col.f32.bf16.bf16.f32 {%0,%1,%2,%3}, {%4,%5,%6,%7}, {%8,%9}, {%0,%1,%2,%3};"
                 : "+f"(d[0]), "+f"(d[1]), "+f"(d[2]), "+f"(d[3])
                 : "r"(a[0]), "r"(a[1]), "r"(a[2]), "r"(a[3]), "r"(b0), "r"(b1));
}
__device__ __forceinline__ uint32_t prmt0(uint32_t a, uint32_t sel) {
    uint32_t d;
    asm volatile("prmt.b32 %0, %1, 0, %2;" : "=r"(d) : "r"(a), "r"(sel));
    return d;
}
__device__ __forceinline__ unsigned gt() {
    unsigned t;
    asm volatile("mov.u32 %0, %globaltimer_lo;" : "=r"(t));
    return t;
}
__device__ __forceinline__ unsigned clk32() {
    unsigned c;
    asm volatile("mov.u32 %0, %clock;" : "=r"(c));
    return c;
}
__device__ __forceinline__ float ex2(float x) {
    float y;
    asm("ex2.approx.ftz.f32 %0, %1;" : "=f"(y) : "f"(x));
    return y;
}
__device__ __forceinline__ float bf16r(float x) { return __bfloat162float(__float2bfloat16_rn(x)); }
__device__ __forceinline__ uint32_t packbf(float lo, float hi) {
    uint32_t r;
    asm("cvt.rn.bf16x2.f32 %0, %1, %2;" : "=r"(r) : "f"(hi), "f"(lo));
    return r;
}
__device__ __forceinline__ float bflo(uint32_t v) { return __uint_as_float(v << 16); }
__device__ __forceinline__ float bfhi(uint32_t v) { return __uint_as_float(v & 0xffff0000u); }
__device__ __forceinline__ uint32_t tagf(float v, uint32_t t8) { return (__float_as_uint(v) & 0xffffff00u) | t8; }
__device__ __forceinline__ float shx(float v, int m) { return __shfl_xor_sync(0xffffffffu, v, m); }

__device__ __forceinline__ uint64_t gdesc(uint32_t addr, uint32_t lbo, uint32_t sbo) {
    return (uint64_t)((addr & 0x3ffff) >> 4) | ((uint64_t)(lbo >> 4) << 16) | ((uint64_t)(sbo >> 4) << 32) | (1ull << 62);
}
__device__ __forceinline__ void wg_fence() { asm volatile("wgmma.fence.sync.aligned;" ::: "memory"); }
__device__ __forceinline__ void wg_commit() { asm volatile("wgmma.commit_group.sync.aligned;" ::: "memory"); }
__device__ __forceinline__ void wg_wait0() { asm volatile("wgmma.wait_group.sync.aligned 0;" ::: "memory"); }
template <int N> __device__ __forceinline__ void reg_fence(float (&r)[N]) {
#pragma unroll
    for (int i = 0; i < N; i++) asm volatile("" : "+f"(r[i])::"memory");
}
#define F8(a, o) "+f"(a[o]), "+f"(a[o + 1]), "+f"(a[o + 2]), "+f"(a[o + 3]), "+f"(a[o + 4]), "+f"(a[o + 5]), "+f"(a[o + 6]), "+f"(a[o + 7])
#define F32(a, o) F8(a, o), F8(a, o + 8), F8(a, o + 16), F8(a, o + 24)
__device__ __forceinline__ void wgmma_n64_ss(float (&d)[32], uint64_t da, uint64_t db, int scale_d) {
    asm volatile(
        "{\n.reg .pred p;\nsetp.ne.b32 p, %34, 0;\n"
        "wgmma.mma_async.sync.aligned.m64n64k16.f32.bf16.bf16 "
        "{%0,%1,%2,%3,%4,%5,%6,%7,%8,%9,%10,%11,%12,%13,%14,%15,%16,%17,%18,%19,%20,%21,%22,%23,%24,%25,%26,%27,%28,%29,%30,%31},"
        " %32, %33, p, 1, 1, 0, 0;\n}"
        : F32(d, 0) : "l"(da), "l"(db), "r"(scale_d));
}
__device__ __forceinline__ void wgmma_n32_ts(float (&d)[16], uint64_t da, uint64_t db) {
    asm volatile(
        "{\n.reg .pred p;\nsetp.ne.b32 p, 1, 0;\n"
        "wgmma.mma_async.sync.aligned.m64n32k16.f32.bf16.bf16 "
        "{%0,%1,%2,%3,%4,%5,%6,%7,%8,%9,%10,%11,%12,%13,%14,%15}, %16, %17, p, 1, 1, 1, 0;\n}"
        : F8(d, 0), F8(d, 8) : "l"(da), "l"(db));
}

struct Params {
    Scratch* scr;
    const uint32_t *ax, *bx;
    const char *k, *wq;
    __nv_bfloat16* out;
};
struct Maps { CUtensorMap kv[2], qa, qb, wo[2], c, uk, uv; };

__device__ __forceinline__ void wait_flags(const unsigned* flags, unsigned tag, int lane) {
    for (int i = 0; !__all_sync(0xffffffffu, ld_acquire(flags + lane) == tag); i++) {
        if (i > SPIN_MAX) __trap();
        __nanosleep(BPOLL);
    }
}
__device__ __forceinline__ void load_slice(uint32_t dst, const CUtensorMap* map, int r, uint32_t bar) {
    mbar_expect(bar, 131072);
#pragma unroll
    for (int x = 0; x < 4; x++) tma2d(dst + x * 32768, map, r * 128 + (x & 1) * 64, (x >> 1) * 256, bar);
}
__device__ __forceinline__ void gemv_slice(uint32_t sb, int warp, int lane) {
    const int g = lane >> 2, tq = lane & 3;
    float d[4][4];
#pragma unroll
    for (int i = 0; i < 4; i++) d[i][0] = d[i][1] = d[i][2] = d[i][3] = 0.f;
    const uint32_t wb = sb + SB_STG + (warp >> 2) * 32768 + ((lane & 7) + 8 * (lane >> 4)) * 128 +
                        (((2 * (warp & 3) + ((lane >> 3) & 1)) ^ (lane & 7)) << 4);
    const uint32_t xb = sb + SB_X + ((g & 3) * 264 + tq) * 4;
#pragma unroll 1
    for (int k8 = 0; k8 < 4; k8++) {
        uint32_t a[8][4], b[8][2];
#pragma unroll
        for (int ks = 0; ks < 8; ks++) {
            ldsm4t(a[ks], wb + (k8 >> 1) * 65536 + (k8 & 1) * 16384 + ks * 2048);
            b[ks][0] = lds32(xb + k8 * 256 + ks * 32);
            b[ks][1] = lds32(xb + k8 * 256 + ks * 32 + 16);
        }
#pragma unroll
        for (int ks = 0; ks < 8; ks++) mma16816(d[ks & 3], a[ks], b[ks][0], b[ks][1]);
    }
    const float y0 = ((d[0][0] + d[1][0]) + (d[2][0] + d[3][0])) + ((d[0][1] + d[1][1]) + (d[2][1] + d[3][1]));
    const float y1 = ((d[0][2] + d[1][2]) + (d[2][2] + d[3][2])) + ((d[0][3] + d[1][3]) + (d[2][3] + d[3][3]));
    if (tq < 2) {
        sts32(sb + SB_QB + (tq * 128 + warp * 16 + g) * 4, __float_as_uint(y0));
        sts32(sb + SB_QB + (tq * 128 + warp * 16 + 8 + g) * 4, __float_as_uint(y1));
    }
}
__device__ __forceinline__ uint32_t wo_lane(uint32_t sb, int lane) {
    return sb + ((lane & 7) + 8 * (lane >> 4)) * 64 + ((((lane >> 3) & 1) ^ ((lane >> 1) & 3)) << 4);
}

__device__ __forceinline__ void latent_branch(const Params& P, const Maps& M, uint8_t* sm TRARG) {
    const uint32_t sb = s2u(sm);
    const int tid = threadIdx.x, lane = tid & 31, warp = tid >> 5, g = lane >> 2, tq = lane & 3, r = blockIdx.x >> 2;
    const uint32_t bar_w = sb + SB_BAR + 16, bar_x = sb + SB_BAR + 24;
    const unsigned tag = lds32(sb + SB_CNT + 4) + 1;
    Scratch* const S = P.scr;
    const float* yb = reinterpret_cast<const float*>(sm + SB_QB);
    {
        float* xs = reinterpret_cast<float*>(sm + SB_X);
        const int crow0 = (r >> 4) * 8192 + (r & 15) * 64;
        {
            if (tid == 32) {
                if (BDELAY) __nanosleep(BDELAY);
                load_slice(sb + SB_STG, &M.qb, r, bar_w);
            }
            uint32_t* xh = reinterpret_cast<uint32_t*>(sm + SB_X) + tid;
            xh[0] = __ldg(P.bx + tid); xh[264] = 0; xh[528] = __ldg(P.bx + 256 + tid); xh[792] = 0;
            bar_sync(0, 256);
            mbar_wait(bar_w, 0);
            TR(0);
            gemv_slice(sb, warp, lane);
            bar_sync(0, 256);
            if (tid == 0) load_slice(sb + SB_STG, &M.uk, r, bar_w);
            uint32_t qb[8][2];
#pragma unroll
            for (int ks = 0; ks < 8; ks++) {
                const float2 a = *reinterpret_cast<const float2*>(yb + (g & 1) * 128 + ks * 16 + 2 * tq);
                const float2 b = *reinterpret_cast<const float2*>(yb + (g & 1) * 128 + ks * 16 + 8 + 2 * tq);
                qb[ks][0] = packbf(a.x, a.y);
                qb[ks][1] = packbf(b.x, b.y);
            }
            mbar_wait(bar_w, 1);
            const uint32_t wb = sb + SB_STG + (warp >> 2) * 65536 + ((warp & 3) * 64 + (lane & 15)) * 128;
#pragma unroll 1
            for (int mt = 0; mt < 4; mt++) {
                float d[4] = {0.f, 0.f, 0.f, 0.f};
#pragma unroll
                for (int ks = 0; ks < 8; ks++) {
                    uint32_t a[4];
                    ldsm4(a, wb + (ks >> 2) * 32768 + mt * 2048 + (((2 * (ks & 3) + (lane >> 4)) ^ (lane & 7)) << 4));
                    mma16816(d, a, qb[ks][0], qb[ks][1]);
                }
                if (tq == 0) {
                    const int c = warp * 64 + mt * 16 + g;
                    xs[c] = d[0]; xs[512 + c] = d[1]; xs[c + 8] = d[2]; xs[512 + c + 8] = d[3];
                }
            }
            bar_sync(0, 256);
            if (tid == 32) {
#pragma unroll 1
                for (int x = 0; x < 16; x++) {
                    if (!(x & 7)) mbar_expect(sb + SB_BAR + x, 65536);
                    tma2d_ef(sb + SB_STG + x * 8192, &M.c, (x & 7) * 64, crow0 + (x >> 3) * 1024, sb + SB_BAR + (x & 8));
                }
            }
            const int b = tid >> 7, lo = (tid >> 6) & 1, ch = tid & 63;
            float v[8];
#pragma unroll
            for (int i = 0; i < 8; i++) {
                const float x = xs[b * 512 + ch * 8 + i];
                v[i] = lo ? x - bf16r(x) : x;
            }
            const int row = 16 * (r >> 3) + (r & 7) + 8 * lo;
            S->qimg[b * 4096 + (ch >> 3) * 512 + row * 8 + ((ch & 7) ^ (r & 7))] =
                make_uint4(packbf(v[0], v[1]), packbf(v[2], v[3]), packbf(v[4], v[5]), packbf(v[6], v[7]));
            bar_sync(0, 256);
            if (warp == 0) {
                if (lane == 0) { __threadfence(); st_release(S->qflag + r, tag); }
                wait_flags(S->qflag, tag, lane);
                if (lane == 0) {
                    fence_async_all();
                    mbar_expect(bar_x, 65536);
                    bulk_g2s(sb + SB_QIMG, S->qimg + (r >> 4) * 4096, 65536, bar_x);
                }
            }
            mbar_wait(bar_x, 0);
        }
        TR(1);
        {
            const int wg = warp >> 2;
            float acc[4][16];
#pragma unroll
            for (int i = 0; i < 64; i++) acc[i >> 4][i & 15] = 0.f;
            const int head = (warp & 3) * 8 + g;
            const uint32_t pa = sb + SB_P + wg * 4096;
            float* al = reinterpret_cast<float*>(sm + SB_AL) + wg * 32;
            float m = -FLT_MAX, l = 0.f;
#pragma unroll 1
            for (int t = 0; t < 8; t++) {
                const uint32_t stg = sb + SB_STG + (t & 1) * 65536;
                mbar_wait(sb + SB_BAR + (t & 1) * 8, (t >> 1) & 1);
                float s[32];
                uint32_t qa = sb + SB_QIMG;
                asm volatile("" : "+r"(qa));
                wg_fence();
#pragma unroll
                for (int k = 0; k < 32; k++) {
                    const uint32_t off = (k >> 2) * 8192 + (k & 3) * 32;
                    wgmma_n64_ss(s, gdesc(qa + off, 16, 1024), gdesc(stg + off, 16, 1024), k > 0);
                }
                wg_commit();
                wg_wait0();
                reg_fence(s);
                float p[16], mx = m;
#pragma unroll
                for (int i = 0; i < 8; i++) {
                    p[2 * i] = bf16r(bf16r(s[4 * i] + s[4 * i + 2]) * SCALE);
                    p[2 * i + 1] = bf16r(bf16r(s[4 * i + 1] + s[4 * i + 3]) * SCALE);
                    mx = fmaxf(mx, fmaxf(p[2 * i], p[2 * i + 1]));
                }
                mx = fmaxf(mx, shx(mx, 1));
                mx = fmaxf(mx, shx(mx, 2));
                const float alpha = ex2((m - mx) * LOG2E);
                m = mx;
                float sum = 0.f;
#pragma unroll
                for (int i = 0; i < 8; i++) {
                    const float a = ex2((p[2 * i] - mx) * LOG2E), b = ex2((p[2 * i + 1] - mx) * LOG2E);
                    sum += a + b;
                    sts32(pa + head * 128 + ((i ^ g) << 4) + tq * 4, packbf(a, b));
                }
                l = fmaf(l, alpha, sum);
                if (tq == 0) al[head] = alpha;
                asm volatile("fence.proxy.async.shared::cta;" ::: "memory");
                bar_sync(1 + wg, 128);
#pragma unroll
                for (int j = 0; j < 4; j++) {
                    const float2 a = *reinterpret_cast<const float2*>(al + 8 * j + 2 * tq);
#pragma unroll
                    for (int i = 0; i < 4; i++) { acc[i][4 * j] *= a.x; acc[i][4 * j + 1] *= a.y; acc[i][4 * j + 2] *= a.x; acc[i][4 * j + 3] *= a.y; }
                }
#pragma unroll
                for (int i = 0; i < 4; i++) reg_fence(acc[i]);
                wg_fence();
#pragma unroll
                for (int kk = 0; kk < 4; kk++)
#pragma unroll
                    for (int i = 0; i < 4; i++)
                        wgmma_n32_ts(acc[i], gdesc(stg + (wg * 4 + i) * 8192 + kk * 2048, 8192, 1024), gdesc(pa + kk * 32, 16, 1024));
                wg_commit();
                wg_wait0();
#pragma unroll
                for (int i = 0; i < 4; i++) reg_fence(acc[i]);
                bar_sync(0, 256);
                if (tid == 0) {
                    if (t + 2 < 8) {
                        const uint32_t bar = sb + SB_BAR + (t & 1) * 8;
                        mbar_expect(bar, 65536);
#pragma unroll 1
                        for (int x = 0; x < 8; x++) tma2d_ef(stg + x * 8192, &M.c, x * 64, crow0 + (t + 2) * 1024, bar);
                    }
                    if (t == 7) load_slice(sb + SB_STG, &M.uv, r, bar_w);
                }
            }
            TR(2);
            float* dst = reinterpret_cast<float*>(sm + SB_QIMG + 2 * tq * PROW) + wg * 256 + (warp & 3) * 16 + g;
#pragma unroll
            for (int i = 0; i < 64; i++)
                dst[(((i >> 2) & 3) * 8 + (i & 1)) * (PROW / 4) + (i >> 4) * 64 + (i & 2) * 4] = acc[i >> 4][i & 15];
            l += shx(l, 1); l += shx(l, 2);
            if (wg == 0 && tq < 2) *reinterpret_cast<float4*>(sm + SB_QIMG + head * PROW + 2048 + tq * 16) = make_float4(m, l, 0.f, 0.f);
            asm volatile("fence.proxy.async.shared::cta;" ::: "memory");
            bar_sync(0, 256);
            if (warp == 0) {
                bulk_s2g(S->bpart + (lane * 32 + r) * (PROW / 16), sb + SB_QIMG + lane * PROW, PROW);
                asm volatile("cp.async.bulk.commit_group;" ::: "memory");
                asm volatile("cp.async.bulk.wait_group 0;" ::: "memory");
                fence_async_all();
                __threadfence();
                __syncwarp();
                if (lane == 0) st_release(S->bflag + r, tag);
                wait_flags(S->bflag, tag, lane);
                if (lane == 0) {
                    fence_async_all();
                    mbar_expect(bar_x, 32 * PROW);
                    bulk_g2s(sb + SB_QIMG, S->bpart + r * 32 * (PROW / 16), 32 * PROW, bar_x);
                }
            }
        }
        {
            const int b = tid >> 7, c4 = tid & 127;
            mbar_wait(bar_x, 1);
            TR(3);
            const float2 ml = *reinterpret_cast<const float2*>(sm + SB_QIMG + (b * 16 + (lane & 15)) * PROW + 2048);
            float MM = ml.x;
            MM = fmaxf(MM, shx(MM, 1)); MM = fmaxf(MM, shx(MM, 2)); MM = fmaxf(MM, shx(MM, 4)); MM = fmaxf(MM, shx(MM, 8));
            const float e = ex2((ml.x - MM) * LOG2E);
            float L = e * ml.y;
            L += shx(L, 1); L += shx(L, 2); L += shx(L, 4); L += shx(L, 8);
            const float wgt = e / L;
            float4 o = make_float4(0.f, 0.f, 0.f, 0.f);
#pragma unroll 4
            for (int i = 0; i < 16; i++) {
                const float w = __shfl_sync(0xffffffffu, wgt, i);
                const float4 v = *reinterpret_cast<const float4*>(sm + SB_QIMG + (b * 16 + i) * PROW + c4 * 16);
                o.x = fmaf(w, v.x, o.x); o.y = fmaf(w, v.y, o.y); o.z = fmaf(w, v.z, o.z); o.w = fmaf(w, v.w, o.w);
            }
            uint32_t* xh = reinterpret_cast<uint32_t*>(xs);
            const uint32_t h0 = packbf(o.x, o.y), h1 = packbf(o.z, o.w);
            *reinterpret_cast<uint2*>(xh + (2 * b) * 264 + c4 * 2) = make_uint2(h0, h1);
            *reinterpret_cast<uint2*>(xh + (2 * b + 1) * 264 + c4 * 2) =
                make_uint2(packbf(o.x - bflo(h0), o.y - bfhi(h0)), packbf(o.z - bflo(h1), o.w - bfhi(h1)));
            bar_sync(0, 256);
            mbar_wait(bar_w, 0);
            gemv_slice(sb, warp, lane);
            bar_sync(0, 256);
            if (tid < 64) {
                const float* y = yb + warp * 128 + 16 * g + 2 * tq;
                st_relaxed4(S->frag[0] + (warp * 32 + r) * 32 + lane, make_uint4(packbf(y[0], y[1]), tag, packbf(y[8], y[9]), tag));
            }
        }
        TR(4);
    }
}

__global__ void __launch_bounds__(384, 1)
fused_decode_kernel(const Params P, const __grid_constant__ Maps M) {
    extern __shared__ __align__(1024) uint8_t sm[];
    const uint32_t sb = s2u(sm);
    const int tid = threadIdx.x, lane = tid & 31, bx = blockIdx.x;
    const int warp = __shfl_sync(0xffffffffu, tid >> 5, 0);
    const int g = lane >> 2, tq = lane & 3;
    Scratch* const S = P.scr;

    if (!(bx & 1)) {
        const int grp = (bx >> 1) & 7, crk = bx >> 4;
        const int rowbase = grp * (UPG * 64);
        auto issue = [&](int slot, unsigned tk, int v) {
            const int row = rowbase + (int)((tk & ~255u) | ((tk + grp * ROT) & 255u)) * 64;
            const uint32_t full = sb + SA_FULL + slot * 16 + v * 8;
            mbar_expect(full, 8192);
            tma2d_ef(sb + slot * 16384 + v * 8192, &M.kv[v], 0, row, full);
        };
        if (warp >= 8) {
            const int w = warp - 8;
            if (w >= NW) return;
            const bool one = elect();
            if (one) {
                if (PFA && w < NI) prefetch_l2(P.k + (size_t)(rowbase + ((w * CPG + crk + grp * ROT) & 255) * 64) * 128, 8192);
                mbar_init(sb + SA_FULL + w * 16, 1);
                mbar_init_fence();
                TR(3);
                sts32(sb + SA_META + w * 4, 0);
                if (w < NI) issue(w, w * CPG + crk, 0);
#pragma unroll
                for (int i = 0; i < SPW; i++) {
                    if (i) mbar_init(sb + SA_FULL + (w + i * NW) * 16, 1);
                    mbar_init(sb + SA_FULL + (w + i * NW) * 16 + 8, 1);
                    mbar_init(sb + SA_GOV + (w + i * NW) * 8, 1);
                    mbar_init(sb + SA_EMPTY + (w + i * NW) * 8, 2);
                    mbar_arrive(sb + SA_EMPTY + (w + i * NW) * 8);
                }
                if (w < NI) mbar_arrive(sb + SA_EMPTY + w * 8);
                sts32(sb + SA_LIM + w * 4, LIM);
                mbar_init_fence();
            }
            __syncwarp();
            bar_arrive(2, (NW + 1) * 32);
            bar_arrive(1, (2 * NW + 1) * 32);
            unsigned c = 0, tbase = 0;
            int slot = w;
            uint32_t eph = 0;
#pragma unroll 1
            for (int n = 0;; n++) {
                unsigned tk = (n * NW + w) * CPG + crk;
                if (n == SPW) {
                    mbar_wait(sb + SA_EMPTY + w * 8, 1);
                    tbase = NSL * CPG - lds32(sb + SA_CNT + 32) * TICK_INC;
                }
                if (n >= SPW) {
                    const unsigned own = __shfl_sync(0xffffffffu, c, grp);
                    tk = own + tbase;
                    const int lag = (int)(__reduce_add_sync(0xffffffffu, c) - NG * own);
                    if (BAL && one) sts32(sb + SA_LIM + w * 4, lag > BAL * NG ? LIM + BALD : lag < -BAL * NG ? LIM - BALD2 : LIM);
                }
                mbar_wait(sb + SA_EMPTY + slot * 8, eph);
                if (tk >= UPG) {
                    if (one) { sts32(sb + SA_LIM + w * 4, 0); sts32(sb + SA_META + slot * 4, 8); mbar_arrive(sb + SA_FULL + slot * 16); }
                    return;
                }
                if (one && (n || w >= NI)) {
                    sts32(sb + SA_META + slot * 4, tk >> 8);
                    issue(slot, tk, 0);
                    if (tk == UPG - FIRE_T) { st_b64(S->fire + grp, gt(), lds32(sb + SA_CNT + 32) + 1); TR(4); }
                }
                if (n >= SPW - 1) {
                    if (lane == grp) c = atom_inc(S->ctr + lane);
                    else if (BAL && lane < NG) c = ld_relaxed1(S->ctr + lane);
                }
                mbar_wait(sb + SA_GOV + slot * 8, eph);
                if (one) issue(slot, tk, 1);
                TR(0);
                slot += NW;
                if (slot >= NSL) { slot -= NSL; eph ^= 1; }
                __syncwarp();
            }
        }
        if (warp == 0) {
            static_assert(NI == SKEW, "the first step grants V of unit 0");
            bool busy = lane < 2 * NI && !(lane & 1);
            uint32_t par = busy ? 0 : 1;
            int slot = NI;
            bool first = true;
            const unsigned c0 = clk32() + RAMP_T0;
            const int own = lane >= 2 * NSL ? -1 : ((lane >> 1) + (lane & 1) * SKEW) % NSL;
            const uint32_t fb = sb + SA_FULL + lane * 8, lw = sb + SA_LIM + ((lane >> 1) % NW) * 4;
            const uint32_t go = sb + ((lane & 1) ? SA_GOV : SA_EMPTY) + (lane >> 1) * 8;
            bar_sync(2, (NW + 1) * 32);
#pragma unroll 1
            for (int it = 0; it < SPIN_MAX; it++) {
                bool ok = true;
                if (busy) ok = mbar_test(fb, par);
                int lim = lds32(lw);
                if (first) lim = min(LIM0, NI + max((int)(clk32() - c0), 0) / RAMP_S);
                busy = busy && !ok && lim;
                const int n = __popc(__ballot_sync(0xffffffffu, busy));
                if (!__any_sync(0xffffffffu, lim)) return;
                const bool mine = own == slot && lim;
                if (!__any_sync(0xffffffffu, mine && (busy || n > lim - 2))) {
                    if (mine) { mbar_arrive(go); busy = true; par ^= 1; }
                    if (++slot == NSL) { slot = 0; first = false; }
                    it = 0;
                }
            }
            __trap();
        }
        if (warp != 1 && (warp < 4 || warp >= 4 + NW)) return;
        auto fetch_q = [&](int pl, unsigned tag) {
            uint4 v;
            for (int it = 0;; it++) {
                v = ld_relaxed4(S->qpub + (grp * 8 + pl) * 32 + lane);
                if (__all_sync(0xffffffffu, v.y == tag && v.w == tag)) break;
                if (it > SPIN_MAX) __trap();
                if (QPOLL) __nanosleep(QPOLL);
            }
            *reinterpret_cast<uint2*>(sm + SA_Q + pl * 256 + lane * 8) = make_uint2(v.x, v.z);
        };
        if (warp == 1) {
            const unsigned epoch = ld_relaxed1(S->epoch + bx * 8);
            if (lane == 0) { mbar_init(sb + SA_QBAR, 32); mbar_init_fence(); }
            if (lane < 9) sts32(sb + SA_CNT + lane * 4, lane < 8 ? 0u : epoch);
            bar_arrive(1, (2 * NW + 1) * 32);
            if (lane == 0) S->epoch[bx * 8] = epoch + 1;
            __nanosleep(3000);
#pragma unroll 1
            for (int pl = 1; pl < 8; pl++) fetch_q(pl, epoch + 1);
            mbar_arrive(sb + SA_QBAR);
            return;
        }
        const int cw = warp - 4;
        bar_sync(1, (2 * NW + 1) * 32);
        const unsigned tag = lds32(sb + SA_CNT + 32) + 1;
        if (QSLEEP) __nanosleep(QSLEEP);
        fetch_q(0, tag);
        __syncwarp();
        TR(0);

        const uint32_t t8 = tag & 0xffu;
        uint32_t koff[4], voff[4];
#pragma unroll
        for (int i = 0; i < 4; i++) {
            koff[i] = ((lane & 7) + 8 * ((lane >> 3) & 1)) * 128 + (((2 * i + (lane >> 4)) ^ (lane & 7)) << 4);
            voff[i] = ((lane & 7) + 8 * (lane >> 4)) * 128 + (((2 * i + ((lane >> 3) & 1)) ^ (lane & 7)) << 4);
        }
        uint32_t psel[4][2];
#pragma unroll
        for (int i = 0; i < 4; i++) {
            psel[i][0] = (g >> 1) != i ? 0x4444u : (g & 1) ? 0x1044u : 0x4410u;
            psel[i][1] = (g >> 1) != i ? 0x4444u : (g & 1) ? 0x3244u : 0x4432u;
        }
        uint32_t qf[4][2];
        auto load_q = [&](int pl) {
            const uint32_t q = sb + SA_Q + pl * 256 + ((g & 1) * 32 + tq) * 4;
#pragma unroll
            for (int ks = 0; ks < 4; ks++) { qf[ks][0] = lds32(q + ks * 32); qf[ks][1] = lds32(q + ks * 32 + 16); }
        };
        load_q(0);
        float acc[4][4], m = -FLT_MAX, l = 0.f, ls = 0.f;
#pragma unroll
        for (int i = 0; i < 4; i++) acc[i][0] = acc[i][1] = acc[i][2] = acc[i][3] = 0.f;
        int slot = cw, cur = 0;
        uint32_t ph = 0;
#pragma unroll 1
        for (;;) {
            mbar_wait(sb + SA_FULL + slot * 16, ph);
            const int pl = lds32(sb + SA_META + slot * 4);
            if (pl != cur) {
#pragma unroll 1
            for (; cur != pl; cur++) {
                float* s0 = reinterpret_cast<float*>(sm + SA_SLOT) + cur * (NW * 132);
                float* sw = s0 + cw * 132 + tq * 16 + (g >> 1) * 4 + (g & 1);
                sw[0] = (acc[0][0] + acc[1][0]) + (acc[2][0] + acc[3][0]);
                sw[2] = (acc[0][2] + acc[1][2]) + (acc[2][2] + acc[3][2]);
                sw[64] = (acc[0][1] + acc[1][1]) + (acc[2][1] + acc[3][1]);
                sw[66] = (acc[0][3] + acc[1][3]) + (acc[2][3] + acc[3][3]);
                if (lane == 0) *reinterpret_cast<float2*>(s0 + cw * 132 + 128) = make_float2(m, ls);
                __syncwarp();
                int old = 0;
                if (lane == 0) asm volatile("atom.acq_rel.cta.shared.inc.u32 %0, [%1], 255;" : "=r"(old) : "r"(sb + SA_CNT + cur * 4) : "memory");
                if (__shfl_sync(0xffffffffu, old, 0) == NW - 1) {
                    float2 ml[NW];
                    float4 v[NW];
#pragma unroll
                    for (int w = 0; w < NW; w++) {
                        ml[w] = *reinterpret_cast<const float2*>(s0 + w * 132 + 128);
                        v[w] = *reinterpret_cast<const float4*>(s0 + w * 132 + lane * 4);
                    }
                    float MM = ml[0].x;
#pragma unroll
                    for (int w = 1; w < NW; w++) MM = fmaxf(MM, ml[w].x);
                    float4 o = make_float4(0.f, 0.f, 0.f, 0.f);
                    float L = 0.f;
#pragma unroll
                    for (int w = 0; w < NW; w++) {
                        const float e = ex2((ml[w].x - MM) * LOG2E);
                        o.x = fmaf(e, v[w].x, o.x); o.y = fmaf(e, v[w].y, o.y); o.z = fmaf(e, v[w].z, o.z); o.w = fmaf(e, v[w].w, o.w);
                        L = fmaf(e, ml[w].y, L);
                    }
                    const int rec = (grp * 8 + cur) * CPG + crk;
                    st_b128(S->apart + rec * 32 + lane, make_uint4(tagf(o.x, t8), __float_as_uint(o.y), __float_as_uint(o.z), __float_as_uint(o.w)));
                    if (lane < 4) st_b64(S->aml + rec * 4 + lane, __float_as_uint(MM), tagf(L, t8));
                    if (PLACE && cur == 6) {
                        st_b128(S->apart + (rec + CPG) * 32 + lane, make_uint4(t8 ^ 0x80u, 0, 0, 0));
                        if (lane < 4) st_b64(S->aml + (rec + CPG) * 4 + lane, 0, t8 ^ 0x80u);
                    }
                    TR(2);
                }
#pragma unroll
                for (int i = 0; i < 4; i++) acc[i][0] = acc[i][1] = acc[i][2] = acc[i][3] = 0.f;
                m = -FLT_MAX; l = ls = 0.f;
            }
                if (pl == 8) break;
                mbar_wait(sb + SA_QBAR, 0);
                load_q(pl);
            }
            float s4[4][4];
            const uint32_t kb = sb + slot * 16384;
#pragma unroll
            for (int j = 0; j < 4; j++) {
                s4[j][0] = s4[j][1] = s4[j][2] = s4[j][3] = 0.f;
                const bool on = (g >> 1) == j;
#pragma unroll
                for (int ks = 0; ks < 4; ks++) {
                    uint32_t a[4];
                    ldsm4(a, kb + j * 2048 + koff[ks]);
                    mma16816(s4[j], a, on ? qf[ks][0] : 0u, on ? qf[ks][1] : 0u);
                }
            }
            float d[4];
#pragma unroll
            for (int r = 0; r < 4; r++) d[r] = (s4[0][r] + s4[1][r]) + (s4[2][r] + s4[3][r]);
            float sa = (g & 1) ? d[1] : d[0], sc = (g & 1) ? d[3] : d[2];
            sa += shx(sa, 4); sc += shx(sc, 4);
            uint32_t sp = packbf(sa, sc);
            sp = packbf(bflo(sp) * SCALE, bfhi(sp) * SCALE);
            sa = bflo(sp); sc = bfhi(sp);
            int mi = __float_as_int(fmaxf(fmaxf(sa, sc), m));
            mi ^= (mi >> 31) & 0x7fffffff;
            mi = __reduce_max_sync(0xffffffffu, mi);
            const float mx = __int_as_float(mi ^ ((mi >> 31) & 0x7fffffff));
            const float alpha = ex2((m - mx) * LOG2E);
            m = mx;
            const float pa = ex2((sa - mx) * LOG2E), pc = ex2((sc - mx) * LOG2E);
            const uint32_t pk = packbf(pa, pc);
            uint32_t pb[4][4][2];
#pragma unroll
            for (int j = 0; j < 4; j++) {
                const uint32_t pj = __shfl_sync(0xffffffffu, pk, 8 * tq + j);
#pragma unroll
                for (int i = 0; i < 4; i++) { pb[j][i][0] = prmt0(pj, psel[i][0]); pb[j][i][1] = prmt0(pj, psel[i][1]); }
            }
            l = fmaf(l, alpha, pa + pc);
            ls = l + shx(l, 8);
#pragma unroll
            for (int i = 0; i < 4; i++) { acc[i][0] *= alpha; acc[i][1] *= alpha; acc[i][2] *= alpha; acc[i][3] *= alpha; }
            mbar_wait(sb + SA_FULL + slot * 16 + 8, ph);
            TR(1);
            const uint32_t vb = kb + 8192;
#pragma unroll
            for (int i = 0; i < 4; i++)
#pragma unroll
                for (int j = 0; j < 4; j++) {
                    uint32_t a[4];
                    ldsm4t(a, vb + j * 2048 + voff[i]);
                    mma16816(acc[j], a, pb[j][i][0], pb[j][i][1]);
                }
            ls += shx(ls, 16); ls += shx(ls, 1); ls += shx(ls, 2);
            __syncwarp();
            if (lane == 0) mbar_arrive(sb + SA_EMPTY + slot * 8);
            slot += NW;
            if (slot >= NSL) { slot -= NSL; ph ^= 1; }
        }
        TROUT();
        return;
    }

    const int r = bx >> 2, isC = (bx >> 1) & 1;
    const uint32_t bar_h = sb + SB_BAR + 32;
    if (warp < 8) {
    {
        const uint32_t bar_q = bar_h + (NT + warp) * 8, box = sb + SB_QIMG + warp * 8192;
        if (elect()) {
            if (PFQ) prefetch_l2(P.wq + ((bx >> 1) * 8 + warp) * 8192, PFQ);
            mbar_init(bar_q, 1);
            mbar_init_fence();
            mbar_expect(bar_q, 8192 + (XBULK ? 256 : 0));
            tma2d(box, &M.qa, (bx >> 1) * 64, warp * 64, bar_q);
            if (XBULK) {
                bulk_g2s(sb + SB_P + 4096 + warp * 288, P.ax + warp * 32, 128, bar_q);
                bulk_g2s(sb + SB_P + 4096 + warp * 288 + 144, P.ax + 256 + warp * 32, 128, bar_q);
            }
        }
        const uint32_t* x = P.ax + (g & 1) * 256 + warp * 32 + tq;
        uint32_t b[8];
        if (!XBULK) {
#pragma unroll
            for (int i = 0; i < 8; i++) b[i] = __ldg(x + i * 4);
        }
        unsigned epoch = 0;
        if (warp < 2) epoch = ld_relaxed1(S->epoch + bx * 8);
        uint4* const qdst = S->qpub + ((lane >> 4) * 32 + r) * 32 + isC * 16 + (lane & 15);
        if (PLACE && warp == 0) st_relaxed4(qdst, make_uint4(0, 0, 0, 0));
        if (tid == 32) {
#pragma unroll
            for (int i = 0; i < 4 + NT; i++) mbar_init(sb + SB_BAR + i * 8, 1);
            mbar_init_fence();
            sts32(sb + SB_CNT + 4, epoch);
        }
        __syncwarp();
        mbar_wait(bar_q, 0);
        TR(0);
        if (XBULK) {
#pragma unroll
            for (int i = 0; i < 8; i++) b[i] = lds32(sb + SB_P + 4096 + warp * 288 + (g & 1) * 144 + tq * 4 + i * 16);
        }
        float d[4][4];
        uint32_t a[4][4][4];
#pragma unroll
        for (int i = 0; i < 4; i++) {
            d[i][0] = d[i][1] = d[i][2] = d[i][3] = 0.f;
#pragma unroll
            for (int ks = 0; ks < 4; ks++)
                ldsm4t(a[i][ks], box + ks * 2048 + ((lane & 7) + 8 * (lane >> 4)) * 128 + (((2 * i + ((lane >> 3) & 1)) ^ (lane & 7)) << 4));
        }
#pragma unroll
        for (int ks = 0; ks < 4; ks++)
#pragma unroll
            for (int i = 0; i < 4; i++) mma16816(d[i], a[i][ks], b[2 * ks], b[2 * ks + 1]);
        float* qred = reinterpret_cast<float*>(sm + SB_P);
#pragma unroll
        for (int c = 0; c < 4; c++)
            qred[warp * 128 + (c & 1) * 64 + tq * 16 + (c >> 1) * 8 + g] = tq == 0 ? d[0][c] : tq == 1 ? d[1][c] : tq == 2 ? d[2][c] : d[3][c];
        bar_sync(0, 256);
        if (warp == 0) {
            float4 v[8];
#pragma unroll
            for (int w = 0; w < 8; w++) v[w] = *reinterpret_cast<const float4*>(qred + w * 128 + lane * 4);
#pragma unroll
            for (int o = 4; o; o >>= 1)
#pragma unroll
                for (int w = 0; w < o; w++) { v[w].x += v[w + o].x; v[w].y += v[w + o].y; v[w].z += v[w + o].z; v[w].w += v[w + o].w; }
            st_relaxed4(qdst, make_uint4(packbf(v[0].x, v[0].y), epoch + 1, packbf(v[0].z, v[0].w), epoch + 1));
            if (lane == 0) S->epoch[bx * 8] = epoch + 1;
        }
        TR(1);
    }
    if (!isC) latent_branch(P, M, sm TRPASS);
    bar_arrive(6, 288);
    }

    const int isA = r & 1, nsnd = isA ? NSA : NSB, isCA = isC & isA;
    const int y0 = isC ? nsnd : 0, y1 = isC ? 32 - 4 * isA : nsnd;
    float* const red = reinterpret_cast<float*>(sm + SC_RED);
    const uint32_t wlane = wo_lane(sb, lane);
    if (warp < 8) {
        const unsigned tag = lds32(sb + SB_CNT + 4) + 1;
        const uint32_t t8 = tag & 0xffu;
        uint32_t wf[2][8][4];
        if (isC) __nanosleep(CSLEEP);
#pragma unroll 1
        for (int step = 0;; step++) {
            if (isCA) {
                const int pair = warp * 8 + (step ? 7 : (r >> 1) % 7);
                const uint2* mlp = S->aml + pair * (CPG * 4);
                unsigned rdy = 0xffffffffu;
                if (!step) {
                    for (int it = 0; !__all_sync(0xffffffffu, (ld_b64(mlp + (lane & 7) * 4).y & 0xffu) == t8); it++) {
                        if (it > SPIN_MAX) __trap();
                        __nanosleep(POLL0_NS);
                    }
                } else {
                    mbar_wait(bar_h + (NT - 8 + (warp & 3) * 2) * 8, 0);
                    mbar_wait(bar_h + (NT - 7 + (warp & 3) * 2) * 8, 0);
                }
#pragma unroll
                for (int ks = 0; ks < 8; ks++) {
                    ldsm4t(wf[0][ks], wlane + (NT - 8) * 4096 + (warp & 3) * 8192 + ks * 1024);
                    ldsm4t(wf[1][ks], (wlane ^ 32) + (NT - 8) * 4096 + (warp & 3) * 8192 + ks * 1024);
                }
                if (step) mbar_wait(sb + SB_BAR, 0);
                TR(3);
            const uint4* src = S->apart + pair * (CPG * 32) + lane;
            uint4 v[CPG];
            uint2 ml[CPG];
            unsigned need = (1u << CPG) - 1;
            for (int it = 0; need; it++) {
                const unsigned get = __popc(need & ~rdy) <= SPEC_K ? need : need & rdy;
                const unsigned fl0 = ld_b64(mlp + (lane & 7) * 4).y;
#pragma unroll
                for (int i = 0; i < CPG; i++)
                    if (get >> i & 1) { v[i] = ld_b128(src + i * 32); ml[i] = ld_b64(mlp + i * 4); }
                unsigned bad = 0;
#pragma unroll
                for (int i = 0; i < CPG; i++)
                    if ((((v[i].x ^ t8) | (ml[i].y ^ t8)) & 0xffu) != 0) bad |= 1u << i;
                need &= __reduce_or_sync(0xffffffffu, bad) | ~get;
                rdy = __ballot_sync(0xffffffffu, (fl0 & 0xffu) == t8);
                if (it > SPIN_MAX) __trap();
            }
            TR(2);
            float M4[CPG / 2], e[CPG];
#pragma unroll
            for (int i = 0; i < CPG / 2; i++) M4[i] = fmaxf(__uint_as_float(ml[2 * i].x), __uint_as_float(ml[2 * i + 1].x));
            const float MM = fmaxf(fmaxf(M4[0], M4[1]), fmaxf(M4[2], M4[3]));
#pragma unroll
            for (int i = 0; i < CPG; i++) e[i] = ex2((__uint_as_float(ml[i].x) - MM) * LOG2E);
            float ls[2], oa[4], ob[4];
#pragma unroll
            for (int i = 0; i < CPG; i++) ls[i & 1] = i < 2 ? e[i] * __uint_as_float(ml[i].y) : fmaf(e[i], __uint_as_float(ml[i].y), ls[i & 1]);
            float inv;
            asm("rcp.approx.ftz.f32 %0, %1;" : "=f"(inv) : "f"(ls[0] + ls[1]));
#pragma unroll
            for (int i = 0; i < CPG; i++) {
                float (&o)[4] = (i & 1) ? ob : oa;
                o[0] = i < 2 ? e[i] * __uint_as_float(v[i].x) : fmaf(e[i], __uint_as_float(v[i].x), o[0]);
                o[1] = i < 2 ? e[i] * __uint_as_float(v[i].y) : fmaf(e[i], __uint_as_float(v[i].y), o[1]);
                o[2] = i < 2 ? e[i] * __uint_as_float(v[i].z) : fmaf(e[i], __uint_as_float(v[i].z), o[2]);
                o[3] = i < 2 ? e[i] * __uint_as_float(v[i].w) : fmaf(e[i], __uint_as_float(v[i].w), o[3]);
            }
            const uint32_t b0 = packbf((oa[0] + ob[0]) * inv, (oa[1] + ob[1]) * inv), b1 = packbf((oa[2] + ob[2]) * inv, (oa[3] + ob[3]) * inv);
                float d[4][4];
#pragma unroll
                for (int i = 0; i < 4; i++) d[i][0] = d[i][1] = d[i][2] = d[i][3] = 0.f;
#pragma unroll
                for (int ks = 0; ks < 8; ks++) {
                    mma16816(d[ks & 1], wf[0][ks], g == ks ? b0 : 0u, g == ks ? b1 : 0u);
                    mma16816(d[2 + (ks & 1)], wf[1][ks], g == ks ? b0 : 0u, g == ks ? b1 : 0u);
                }
                const float x0 = (d[0][0] + d[0][1]) + (d[1][0] + d[1][1]), x1 = (d[0][2] + d[0][3]) + (d[1][2] + d[1][3]);
                const float x2 = (d[2][0] + d[2][1]) + (d[3][0] + d[3][1]), x3 = (d[2][2] + d[2][3]) + (d[3][2] + d[3][3]);
                const float z0 = ((tq & 2) ? x2 : x0) + shx((tq & 2) ? x0 : x2, 2), z1 = ((tq & 2) ? x3 : x1) + shx((tq & 2) ? x1 : x3, 2);
                red[(4 + (warp & 3)) * 80 + (warp >> 2) * 40 + tq * 8 + g] = ((tq & 1) ? z1 : z0) + shx((tq & 1) ? z0 : z1, 1);
                if (step) {
                    bar_arrive(5, 384);
                    TR(5);
                    TROUT();
                    return;
                }
                st_relaxed4(S->frag[1] + pair * 32 + lane, make_uint4(b0, tag, b1, tag));
            }
            uint2* const bfr = reinterpret_cast<uint2*>(sm + SC_FR) + ((warp & 3) * 32 + (g >> 1) * 8 + (warp >> 2) * 4 + tq) * 2 + (g & 1);
            const int p0 = (y0 + 3 - (warp & 3)) >> 2, p1 = (y1 + 3 - (warp & 3)) >> 2;
            const uint4* fsrc = S->frag[0] + isA * 2048 + warp * 256 + lane;
            for (int it = 0;; it++) {
                const uint4 v = ld_relaxed4(fsrc + (p1 - 1) * 32);
                if (__all_sync(0xffffffffu, v.y == tag && v.w == tag)) {
                    uint4 u[4];
                    bool ok = true;
#pragma unroll
                    for (int k = 0; k < 4; k++) u[k] = ld_relaxed4(fsrc + min(p0 + k, p1 - 1) * 32);
#pragma unroll
                    for (int k = 0; k < 4; k++) { ok = ok && u[k].y == tag && u[k].w == tag; bfr[min(p0 + k, p1 - 1) * 256] = make_uint2(u[k].x, u[k].z); }
                    bfr[(p1 - 1) * 256] = make_uint2(v.x, v.z);
                    if (__all_sync(0xffffffffu, ok)) break;
                }
                if (it > SPIN_MAX) __trap();
                __nanosleep(POLL0_NS);
            }
            if (!isCA && warp < 4) break;
            bar_arrive(4, 352);
            if (!isCA) { TROUT(); return; }
        }
    }
    if (warp == 11) {
        bar_sync(6, 288);
        const CUtensorMap* map = &M.wo[isA];
        const unsigned tag = lds32(sb + SB_CNT + 4) + 1;
        const uint32_t t8 = tag & 0xffu;
        uint2* const snd = S->snd + r * 32 + lane;
        auto request = [&](int t, int slot) {
            mbar_expect(bar_h + slot * 8, 4096);
            tma2d(sb + slot * 4096, map, (r >> 1) * 32, (((t >> 1) & 3) * 8 + (t >> 3)) * 128 + (t & 1) * 64, bar_h + slot * 8);
        };
        asm volatile("prefetch.tensormap [%0];" ::"l"(map) : "memory");
        if (!isC) st_b64(snd, t8 ^ 0x80u, 0);
        if (isCA && elect()) for (int t = 0; t < 8; t++) request(56 + t, NT - 8 + t);
        __syncwarp();
        uint2 f;
        mbar_wait(sb + SB_BAR + 8, isC ? 0 : 1);
        for (int it = 0;; it++) {
            f = ld_b64(S->fire + (lane & 7));
            if (__all_sync(0xffffffffu, f.y == tag)) break;
            if (it > SPIN_MAX) __trap();
            __nanosleep(FPOLL);
        }
        const unsigned t0 = __shfl_sync(0xffffffffu, f.x, 0);
        unsigned t1 = t0 + (__reduce_add_sync(0xffffffffu, (int)(f.x - t0)) >> 5) + FIRE_NS + isC * FIRE_C;
        TR(2);
        if (elect()) {
#pragma unroll 1
            for (int i = 0; i < 2 * (y1 - y0); i += 2) {
                for (int it = 0; (int)(gt() - t1) < 0 && it < 4096; it++) {}
                request(2 * y0 + i, i);
                request(2 * y0 + i + 1, i + 1);
                if (isCA && i == 2 * REC_I) mbar_arrive(sb + SB_BAR);
                t1 += 2 * (i < 2 * nsnd ? FIRE_DT : isA ? FIRE_DTA : FIRE_DTB);
            }
            TR(3);
        }
        __syncwarp();
        uint2 o = make_uint2(0, 0);
        if (isC) {
            for (int it = 0;; it++) {
                o = ld_b64(snd);
                if (__all_sync(0xffffffffu, (o.x & 0xffu) == t8)) break;
                if (it > SPIN_MAX) __trap();
            }
        }
        TR(4);
        uint32_t* const dst = reinterpret_cast<uint32_t*>(P.out) + (lane >> 4) * 512 + (isA ? 0 : 256) + (r >> 1) * 16 + (lane & 15);
        const float2* q = reinterpret_cast<const float2*>(red) + (lane >> 4) * 20 + (lane & 15);
        bar_sync(5, isCA ? 384 : 256);
        const float2 p0 = q[0], p1 = q[40], p2 = q[80], p4 = q[160], p5 = q[200], p6 = q[240], p7 = q[280];
        const float sx = ((p0.x + p1.x) + (p2.x + __uint_as_float(o.x))) + ((p4.x + p5.x) + (p6.x + p7.x));
        const float sy = ((p0.y + p1.y) + (p2.y + __uint_as_float(o.y))) + ((p4.y + p5.y) + (p6.y + p7.y));
        if (isC) *dst = packbf(sx, sy);
        else st_b64(snd, tagf(sx, t8), __float_as_uint(sy));
        TR(6);
        TROUT();
        return;
    }
    {
        bar_sync(4, 352);
        if (isC && tid == 256) mbar_arrive(sb + SB_BAR + 8);
        const int nw = isCA ? 3 : 7;
        float e[4][4];
#pragma unroll
        for (int i = 0; i < 4; i++) e[i][0] = e[i][1] = e[i][2] = e[i][3] = 0.f;
#pragma unroll 1
        for (int i = warp < 8 ? warp + 3 : warp - 8; i < y1 - y0; i += nw) {
            const uint32_t bp = sb + SC_FR + ((y0 + i) * 32 + (lane & 7)) * 16;
            uint4 b[4];
#pragma unroll
            for (int j = 0; j < 4; j++) b[j] = lds128(bp + j * 128);
            uint32_t a[16][4];
            mbar_wait(bar_h + i * 16, 0);
#pragma unroll
            for (int j = 0; j < 8; j++) ldsm4t(a[j], (wlane ^ ((j & 1) * 32)) + i * 8192 + (j >> 1) * 1024);
            mbar_wait(bar_h + i * 16 + 8, 0);
#pragma unroll
            for (int j = 8; j < 16; j++) ldsm4t(a[j], (wlane ^ ((j & 1) * 32)) + i * 8192 + (j >> 1) * 1024);
#pragma unroll
            for (int j = 0; j < 16; j++)
                mma16816(e[(j & 1) * 2 + ((j >> 1) & 1)], a[j], (j & 2) ? b[j >> 2].z : b[j >> 2].x, (j & 2) ? b[j >> 2].w : b[j >> 2].y);
        }
        float* rx = red + (warp < 8 ? warp + 4 : warp - 8) * 80 + (tq & 1) * 40 + (tq >> 1) * 16 + g;
        float s4[4];
#pragma unroll
        for (int c = 0; c < 4; c++) s4[c] = (tq & 2) ? e[2][c] + e[3][c] : e[0][c] + e[1][c];
        rx[0] = (tq & 1) ? s4[1] : s4[0];
        rx[8] = (tq & 1) ? s4[3] : s4[2];
        bar_arrive(5, isCA ? 384 : 256);
        TROUT();
    }
}

typedef CUresult (*EncodeFn)(CUtensorMap*, CUtensorMapDataType, cuuint32_t, void*, const cuuint64_t*, const cuuint64_t*,
                             const cuuint32_t*, const cuuint32_t*, CUtensorMapInterleave, CUtensorMapSwizzle,
                             CUtensorMapL2promotion, CUtensorMapFloatOOBfill);

void make_map(EncodeFn enc, CUtensorMap* m, const void* base, uint64_t cols, uint64_t rows, uint32_t bc, uint32_t br,
              CUtensorMapL2promotion promo, CUtensorMapSwizzle sw = CU_TENSOR_MAP_SWIZZLE_128B) {
    cuuint64_t dims[2] = {cols, rows};
    cuuint64_t strides[1] = {cols * 2};
    cuuint32_t box[2] = {bc, br};
    cuuint32_t es[2] = {1, 1};
    enc(m, CU_TENSOR_MAP_DATA_TYPE_BFLOAT16, 2, const_cast<void*>(base), dims, strides, box, es,
        CU_TENSOR_MAP_INTERLEAVE_NONE, sw, promo, CU_TENSOR_MAP_FLOAT_OOB_FILL_NONE);
}

}

extern "C" void kernel_launch(void* const* d_in, const int* in_sizes, int n_in, void* d_out, int out_size) {
    (void)in_sizes; (void)n_in; (void)out_size;
    static EncodeFn enc = nullptr;
    static void* scr = nullptr;
    if (!enc) {
        void* fn = nullptr;
        cudaDriverEntryPointQueryResult qr;
        cudaGetDriverEntryPoint("cuTensorMapEncodeTiled", &fn, cudaEnableDefault, &qr);
        enc = (EncodeFn)fn;
        cudaGetSymbolAddress(&scr, g_scr);
        cudaFuncSetAttribute(fused_decode_kernel, cudaFuncAttributeMaxDynamicSharedMemorySize, SMEM_BYTES);
    }
    Maps m;
    make_map(enc, &m.kv[0], d_in[1], 64, 1048576, 64, 64, CU_TENSOR_MAP_L2_PROMOTION_NONE);
    make_map(enc, &m.kv[1], d_in[2], 64, 1048576, 64, 64, CU_TENSOR_MAP_L2_PROMOTION_NONE);
    make_map(enc, &m.qa, d_in[3], 4096, 512, 64, 64, QPROMO);
    make_map(enc, &m.qb, d_in[7], 4096, 512, 64, 256, CU_TENSOR_MAP_L2_PROMOTION_L2_256B);
    make_map(enc, &m.wo[0], d_in[10], 512, 4096, 32, 64, WPROMO, CU_TENSOR_MAP_SWIZZLE_64B);
    make_map(enc, &m.wo[1], d_in[4], 512, 4096, 32, 64, WPROMO, CU_TENSOR_MAP_SWIZZLE_64B);
    make_map(enc, &m.c, d_in[6], 512, 16384, 64, 64, CU_TENSOR_MAP_L2_PROMOTION_NONE);
    make_map(enc, &m.uk, d_in[8], 4096, 512, 64, 256, CU_TENSOR_MAP_L2_PROMOTION_L2_256B);
    make_map(enc, &m.uv, d_in[9], 4096, 512, 64, 256, CU_TENSOR_MAP_L2_PROMOTION_L2_256B);
    Params p;
    p.scr = (Scratch*)scr;
    p.ax = (const uint32_t*)d_in[0];
    p.bx = (const uint32_t*)d_in[5];
    p.out = (__nv_bfloat16*)d_out;
    p.k = (const char*)d_in[1];
    p.wq = (const char*)d_in[3];
    fused_decode_kernel<<<128, 384, SMEM_BYTES, cudaStreamPerThread>>>(p, m);
}
```

```cpp
#include <cuda_runtime.h>
#include <cuda_bf16.h>
#include <cuda.h>
#include <stdint.h>
#include <float.h>

#define LIM 12
#define LIM0 10
#define RAMP_S 256
#define RAMP_T0 300
#define BAL 4
#define SKEW 2
#define ROT 32
#define FIRE_T 60
#define FIRE_NS 3300
#define FIRE_W 2050
#define NLA 3
#define NLB 7
#define NSA 13
#define NSB 13
#define REC_NS 1900
#define JMAP 1
#define WPROMO CU_TENSOR_MAP_L2_PROMOTION_L2_128B
#define PLACE 1
#define BDELAY 1000
#define QSLEEP 1500
#define BPOLL 1000
#define CPOLL 700
#define FPOLL 300

namespace {

constexpr int NG = 8, CPG = 8, NW = 4;
constexpr int UPG = 2048;
constexpr int NSL = 12, SPW = NSL / NW;
constexpr unsigned TICK_INC = UPG - NSL * CPG + NW * CPG;
constexpr int SPIN_MAX = 1 << 22;
constexpr float LOG2E = 1.4426950408889634f;
constexpr float SCALE = 0.08838834764831845f;
constexpr uint64_t EVICT_FIRST = 0x12F0000000000000ull;

constexpr int SA_SLOT = NSL * 16384;
constexpr int SA_Q    = SA_SLOT + 8 * NW * 132 * 4;
constexpr int SA_FULL = SA_Q + 2048;
constexpr int SA_EMPTY = SA_FULL + NSL * 16;
constexpr int SA_GOV  = SA_EMPTY + NSL * 8;
constexpr int SA_QBAR = SA_GOV + NSL * 8;
constexpr int SA_META = SA_QBAR + 8;
constexpr int SA_LIM  = SA_META + NSL * 4;
constexpr int SA_CNT  = SA_LIM + 16;
constexpr int SA_END  = SA_CNT + 64;
constexpr int PROW    = 2080;
constexpr int SB_STG  = 0;
constexpr int SB_QIMG = 131072;
constexpr int SB_P    = SB_QIMG + 32 * PROW;
constexpr int SB_AL   = SB_P + 8192;
constexpr int SB_X    = SB_AL + 256;
static_assert(SB_P % 1024 == 0, "swizzle atom");
constexpr int SB_QB   = SB_X + 4352;
constexpr int NT      = 40;
constexpr int SC_FR   = NT * 4096;
constexpr int SC_RED  = SB_QB + 1024;
constexpr int SB_BAR  = SC_RED + 2560;
constexpr int SB_CNT  = SB_BAR + (12 + NT) * 8;
static_assert(SC_FR + 16384 <= SB_P && 2 * (32 - NSA) <= NT && 2 * (32 - NSB) <= NT && NSA <= 16 && NSB <= 16, "projection slots");
constexpr int SB_END  = SB_CNT + 64;
constexpr int SMEM_BYTES = (SA_END > SB_END ? SA_END : SB_END);
static_assert(SMEM_BYTES <= 232448, "shared memory");

struct Scratch {
    uint4    bpart[32 * 32 * (PROW / 16)];
    uint4    apart[64 * CPG * 32];
    uint4    qimg[2 * 4096];
    uint4    qpub[64 * 32];
    uint4    frag[2][64 * 32];
    uint2    snd[32 * 32];
    uint2    aml[64 * CPG * 4];
    unsigned epoch[128 * 8];
    unsigned ctr[1088];
    uint2    fire[544];
    unsigned qflag[1088], bflag[1088];
};
__device__ __align__(1024) Scratch g_scr;

#define TRARG
#define TRPASS
#define TR(k)
#define TROUT()

__device__ __forceinline__ uint32_t s2u(const void* p) { return (uint32_t)__cvta_generic_to_shared(p); }
__device__ __forceinline__ bool elect() {
    uint32_t ok;
    asm volatile("{\n.reg .pred p;\nelect.sync _|p, 0xffffffff;\nselp.u32 %0,1,0,p;\n}" : "=r"(ok));
    return ok;
}
__device__ __forceinline__ void mbar_init(uint32_t b, int c) {
    asm volatile("mbarrier.init.shared::cta.b64 [%0], %1;" ::"r"(b), "r"(c) : "memory");
}
__device__ __forceinline__ void mbar_init_fence() { asm volatile("fence.mbarrier_init.release.cluster;" ::: "memory"); }
__device__ __forceinline__ void mbar_expect(uint32_t b, uint32_t bytes) {
    asm volatile("mbarrier.arrive.expect_tx.shared::cta.b64 _, [%0], %1;" ::"r"(b), "r"(bytes) : "memory");
}
__device__ __forceinline__ void mbar_arrive(uint32_t b) {
    asm volatile("mbarrier.arrive.shared::cta.b64 _, [%0];" ::"r"(b) : "memory");
}
__device__ __forceinline__ bool mbar_test(uint32_t b, uint32_t ph) {
    uint32_t ok;
    asm volatile("{\n.reg .pred p;\nmbarrier.test_wait.parity.shared::cta.b64 p, [%1], %2;\nselp.u32 %0,1,0,p;\n}"
                 : "=r"(ok) : "r"(b), "r"(ph) : "memory");
    return ok;
}
__device__ __forceinline__ void mbar_wait(uint32_t b, uint32_t ph) {
    asm volatile("{\n.reg .pred p;\n.reg .u32 n;\nmov.u32 n, 0;\n"
                 "W: mbarrier.try_wait.parity.shared::cta.b64 p, [%0], %1;\n@p bra.uni D;\n"
                 "add.u32 n, n, 1;\nsetp.lt.u32 p, n, %2;\n@p bra.uni W;\ntrap;\nD:\n}"
                 ::"r"(b), "r"(ph), "n"(SPIN_MAX) : "memory");
}
__device__ __forceinline__ void tma2d(uint32_t dst, const CUtensorMap* map, int c0, int c1, uint32_t bar) {
    asm volatile("cp.async.bulk.tensor.2d.shared::cluster.global.mbarrier::complete_tx::bytes [%0], [%1, {%3, %4}], [%2];"
                 ::"r"(dst), "l"(map), "r"(bar), "r"(c0), "r"(c1) : "memory");
}
__device__ __forceinline__ void tma2d_ef(uint32_t dst, const CUtensorMap* map, int c0, int c1, uint32_t bar) {
    asm volatile("cp.async.bulk.tensor.2d.shared::cluster.global.mbarrier::complete_tx::bytes.L2::cache_hint [%0], [%1, {%3, %4}], [%2], %5;"
                 ::"r"(dst), "l"(map), "r"(bar), "r"(c0), "r"(c1), "l"(EVICT_FIRST) : "memory");
}
__device__ __forceinline__ void bulk_g2s(uint32_t dst, const void* src, uint32_t bytes, uint32_t bar) {
    asm volatile("cp.async.bulk.shared::cluster.global.mbarrier::complete_tx::bytes [%0], [%1], %2, [%3];"
                 ::"r"(dst), "l"(src), "r"(bytes), "r"(bar) : "memory");
}
__device__ __forceinline__ void bulk_s2g(void* dst, uint32_t src, uint32_t bytes) {
    asm volatile("cp.async.bulk.global.shared::cta.bulk_group [%0], [%1], %2;" ::"l"(dst), "r"(src), "r"(bytes) : "memory");
}
__device__ __forceinline__ void fence_async_all() { asm volatile("fence.proxy.async;" ::: "memory"); }
__device__ __forceinline__ void bar_sync(int id, int n) { asm volatile("bar.sync %0, %1;" ::"r"(id), "r"(n) : "memory"); }
__device__ __forceinline__ void bar_arrive(int id, int n) { asm volatile("bar.arrive %0, %1;" ::"r"(id), "r"(n) : "memory"); }
__device__ __forceinline__ unsigned ld_relaxed1(const void* p) {
    unsigned v;
    asm volatile("ld.relaxed.gpu.global.u32 %0, [%1];" : "=r"(v) : "l"(p) : "memory");
    return v;
}
__device__ __forceinline__ unsigned atom_inc(unsigned* p) {
    unsigned v;
    asm volatile("atom.relaxed.gpu.global.add.u32 %0, [%1], 1;" : "=r"(v) : "l"(p) : "memory");
    return v;
}
__device__ __forceinline__ uint4 ld_b128(const void* p) {
    uint4 v;
    asm volatile("{\n.reg .b128 t;\nld.relaxed.gpu.global.b128 t, [%4];\nmov.b128 {%0,%1,%2,%3}, t;\n}"
                 : "=r"(v.x), "=r"(v.y), "=r"(v.z), "=r"(v.w) : "l"(p) : "memory");
    return v;
}
__device__ __forceinline__ void st_b128(void* p, uint4 v) {
    asm volatile("{\n.reg .b128 t;\nmov.b128 t, {%1,%2,%3,%4};\nst.relaxed.gpu.global.b128 [%0], t;\n}"
                 ::"l"(p), "r"(v.x), "r"(v.y), "r"(v.z), "r"(v.w) : "memory");
}
__device__ __forceinline__ uint2 ld_b64(const void* p) {
    uint2 v;
    asm volatile("{\n.reg .b64 a;\nld.relaxed.gpu.global.b64 a, [%2];\nmov.b64 {%0,%1}, a;\n}" : "=r"(v.x), "=r"(v.y) : "l"(p) : "memory");
    return v;
}
__device__ __forceinline__ void st_b64(void* p, uint32_t a, uint32_t b) {
    asm volatile("{\n.reg .b64 t;\nmov.b64 t, {%1,%2};\nst.relaxed.gpu.global.b64 [%0], t;\n}" ::"l"(p), "r"(a), "r"(b) : "memory");
}
__device__ __forceinline__ unsigned ld_acquire(const unsigned* p) {
    unsigned v;
    asm volatile("ld.acquire.gpu.global.u32 %0, [%1];" : "=r"(v) : "l"(p) : "memory");
    return v;
}
__device__ __forceinline__ void st_release(unsigned* p, unsigned v) {
    asm volatile("st.release.gpu.global.u32 [%0], %1;" ::"l"(p), "r"(v) : "memory");
}
__device__ __forceinline__ void ldsm4(uint32_t (&r)[4], uint32_t a) {
    asm volatile("ldmatrix.sync.aligned.m8n8.x4.shared.b16 {%0,%1,%2,%3}, [%4];"
                 : "=r"(r[0]), "=r"(r[1]), "=r"(r[2]), "=r"(r[3]) : "r"(a) : "memory");
}
__device__ __forceinline__ void ldsm4t(uint32_t (&r)[4], uint32_t a) {
    asm volatile("ldmatrix.sync.aligned.m8n8.x4.trans.shared.b16 {%0,%1,%2,%3}, [%4];"
                 : "=r"(r[0]), "=r"(r[1]), "=r"(r[2]), "=r"(r[3]) : "r"(a) : "memory");
}
__device__ __forceinline__ uint4 lds128(uint32_t a) {
    uint4 v;
    asm volatile("ld.shared.v4.u32 {%0, %1, %2, %3}, [%4];" : "=r"(v.x), "=r"(v.y), "=r"(v.z), "=r"(v.w) : "r"(a) : "memory");
    return v;
}
__device__ __forceinline__ uint32_t lds32(uint32_t a) {
    uint32_t v;
    asm volatile("ld.shared.u32 %0, [%1];" : "=r"(v) : "r"(a) : "memory");
    return v;
}
__device__ __forceinline__ void sts32(uint32_t a, uint32_t v) { asm volatile("st.shared.u32 [%0], %1;" ::"r"(a), "r"(v) : "memory"); }
__device__ __forceinline__ void mma16816(float (&d)[4], const uint32_t (&a)[4], uint32_t b0, uint32_t b1) {
    asm volatile("mma.sync.aligned.m16n8k16.row.col.f32.bf16.bf16.f32 {%0,%1,%2,%3}, {%4,%5,%6,%7}, {%8,%9}, {%0,%1,%2,%3};"
                 : "+f"(d[0]), "+f"(d[1]), "+f"(d[2]), "+f"(d[3])
                 : "r"(a[0]), "r"(a[1]), "r"(a[2]), "r"(a[3]), "r"(b0), "r"(b1));
}
__device__ __forceinline__ uint32_t prmt0(uint32_t a, uint32_t sel) {
    uint32_t d;
    asm volatile("prmt.b32 %0, %1, 0, %2;" : "=r"(d) : "r"(a), "r"(sel));
    return d;
}
__device__ __forceinline__ unsigned gt() {
    unsigned t;
    asm volatile("mov.u32 %0, %globaltimer_lo;" : "=r"(t));
    return t;
}
__device__ __forceinline__ unsigned clk32() {
    unsigned c;
    asm volatile("mov.u32 %0, %clock;" : "=r"(c));
    return c;
}
__device__ __forceinline__ float ex2(float x) {
    float y;
    asm("ex2.approx.ftz.f32 %0, %1;" : "=f"(y) : "f"(x));
    return y;
}
__device__ __forceinline__ float bf16r(float x) { return __bfloat162float(__float2bfloat16_rn(x)); }
__device__ __forceinline__ uint32_t packbf(float lo, float hi) {
    uint32_t r;
    asm("cvt.rn.bf16x2.f32 %0, %1, %2;" : "=r"(r) : "f"(hi), "f"(lo));
    return r;
}
__device__ __forceinline__ float bflo(uint32_t v) { return __uint_as_float(v << 16); }
__device__ __forceinline__ float bfhi(uint32_t v) { return __uint_as_float(v & 0xffff0000u); }
__device__ __forceinline__ uint32_t tagf(float v, uint32_t t8) { return (__float_as_uint(v) & 0xffffff00u) | t8; }
__device__ __forceinline__ float shx(float v, int m) { return __shfl_xor_sync(0xffffffffu, v, m); }

__device__ __forceinline__ float warp_max(float v) {
    int i = __float_as_int(v);
    i = __reduce_max_sync(0xffffffffu, i ^ ((i >> 31) & 0x7fffffff));
    return __int_as_float(i ^ ((i >> 31) & 0x7fffffff));
}

__device__ __forceinline__ uint64_t gdesc(uint32_t addr, uint32_t lbo, uint32_t sbo) {
    return (uint64_t)((addr & 0x3ffff) >> 4) | ((uint64_t)(lbo >> 4) << 16) | ((uint64_t)(sbo >> 4) << 32) | (1ull << 62);
}
__device__ __forceinline__ void wg_fence() { asm volatile("wgmma.fence.sync.aligned;" ::: "memory"); }
__device__ __forceinline__ void wg_commit() { asm volatile("wgmma.commit_group.sync.aligned;" ::: "memory"); }
__device__ __forceinline__ void wg_wait0() { asm volatile("wgmma.wait_group.sync.aligned 0;" ::: "memory"); }
template <int N> __device__ __forceinline__ void reg_fence(float (&r)[N]) {
#pragma unroll
    for (int i = 0; i < N; i++) asm volatile("" : "+f"(r[i])::"memory");
}
#define F8(a, o) "+f"(a[o]), "+f"(a[o + 1]), "+f"(a[o + 2]), "+f"(a[o + 3]), "+f"(a[o + 4]), "+f"(a[o + 5]), "+f"(a[o + 6]), "+f"(a[o + 7])
#define F32(a, o) F8(a, o), F8(a, o + 8), F8(a, o + 16), F8(a, o + 24)
__device__ __forceinline__ void wgmma_n64_ss(float (&d)[32], uint64_t da, uint64_t db, int scale_d) {
    asm volatile(
        "{\n.reg .pred p;\nsetp.ne.b32 p, %34, 0;\n"
        "wgmma.mma_async.sync.aligned.m64n64k16.f32.bf16.bf16 "
        "{%0,%1,%2,%3,%4,%5,%6,%7,%8,%9,%10,%11,%12,%13,%14,%15,%16,%17,%18,%19,%20,%21,%22,%23,%24,%25,%26,%27,%28,%29,%30,%31},"
        " %32, %33, p, 1, 1, 0, 0;\n}"
        : F32(d, 0) : "l"(da), "l"(db), "r"(scale_d));
}
__device__ __forceinline__ void wgmma_n32_ts(float (&d)[16], uint64_t da, uint64_t db) {
    asm volatile(
        "{\n.reg .pred p;\nsetp.ne.b32 p, 1, 0;\n"
        "wgmma.mma_async.sync.aligned.m64n32k16.f32.bf16.bf16 "
        "{%0,%1,%2,%3,%4,%5,%6,%7,%8,%9,%10,%11,%12,%13,%14,%15}, %16, %17, p, 1, 1, 1, 0;\n}"
        : F8(d, 0), F8(d, 8) : "l"(da), "l"(db));
}

struct Params {
    Scratch* scr;
    const uint32_t *ax, *bx;
    const char* wq;
    __nv_bfloat16* out;
};
struct Maps { CUtensorMap kv[2], qa, qb, wo[2], c, uk, uv; };

__device__ __forceinline__ void wait_flags(const unsigned* flags, unsigned tag, int lane) {
    for (int i = 0; !__all_sync(0xffffffffu, ld_acquire(flags + lane) == tag); i++) {
        if (i > SPIN_MAX) __trap();
        __nanosleep(BPOLL);
    }
}
__device__ __forceinline__ void load_slice(uint32_t dst, const CUtensorMap* map, int r, uint32_t bar) {
    mbar_expect(bar, 131072);
#pragma unroll
    for (int x = 0; x < 4; x++) tma2d(dst + x * 32768, map, r * 128 + (x & 1) * 64, (x >> 1) * 256, bar);
}
__device__ __forceinline__ void gemv_slice(uint32_t sb, int warp, int lane) {
    const int g = lane >> 2, tq = lane & 3;
    float d[4][4];
#pragma unroll
    for (int i = 0; i < 4; i++) d[i][0] = d[i][1] = d[i][2] = d[i][3] = 0.f;
    const uint32_t wb = sb + SB_STG + (warp >> 2) * 32768 + ((lane & 7) + 8 * (lane >> 4)) * 128 +
                        (((2 * (warp & 3) + ((lane >> 3) & 1)) ^ (lane & 7)) << 4);
    const uint32_t xb = sb + SB_X + ((g & 3) * 264 + tq) * 4;
#pragma unroll 1
    for (int k8 = 0; k8 < 4; k8++) {
        uint32_t a[8][4], b[8][2];
#pragma unroll
        for (int ks = 0; ks < 8; ks++) {
            ldsm4t(a[ks], wb + (k8 >> 1) * 65536 + (k8 & 1) * 16384 + ks * 2048);
            b[ks][0] = lds32(xb + k8 * 256 + ks * 32);
            b[ks][1] = lds32(xb + k8 * 256 + ks * 32 + 16);
        }
#pragma unroll
        for (int ks = 0; ks < 8; ks++) mma16816(d[ks & 3], a[ks], b[ks][0], b[ks][1]);
    }
    const float y0 = ((d[0][0] + d[1][0]) + (d[2][0] + d[3][0])) + ((d[0][1] + d[1][1]) + (d[2][1] + d[3][1]));
    const float y1 = ((d[0][2] + d[1][2]) + (d[2][2] + d[3][2])) + ((d[0][3] + d[1][3]) + (d[2][3] + d[3][3]));
    if (tq < 2) {
        sts32(sb + SB_QB + (tq * 128 + warp * 16 + g) * 4, __float_as_uint(y0));
        sts32(sb + SB_QB + (tq * 128 + warp * 16 + 8 + g) * 4, __float_as_uint(y1));
    }
}
__device__ __forceinline__ uint32_t wo_lane(uint32_t sb, int lane) {
    return sb + ((lane & 7) + 8 * (lane >> 4)) * 64 + ((((lane >> 3) & 1) ^ ((lane >> 1) & 3)) << 4);
}

__device__ __forceinline__ void latent_branch(const Params& P, const Maps& M, uint8_t* sm TRARG) {
    const uint32_t sb = s2u(sm);
    const int tid = threadIdx.x, lane = tid & 31, warp = tid >> 5, g = lane >> 2, tq = lane & 3, r = blockIdx.x >> 2;
    const uint32_t bar_w = sb + SB_BAR + 16, bar_x = sb + SB_BAR + 24;
    const unsigned tag = lds32(sb + SB_CNT) + 1;
    Scratch* const S = P.scr;
    const float* yb = reinterpret_cast<const float*>(sm + SB_QB);
    {
        float* xs = reinterpret_cast<float*>(sm + SB_X);
        const int crow0 = (r >> 4) * 8192 + (r & 15) * 64;
        {
            if (tid == 32) {
                __nanosleep(BDELAY);
                load_slice(sb + SB_STG, &M.qb, r, bar_w);
            }
            uint32_t* xh = reinterpret_cast<uint32_t*>(sm + SB_X) + tid;
            xh[0] = __ldg(P.bx + tid); xh[264] = 0; xh[528] = __ldg(P.bx + 256 + tid); xh[792] = 0;
            bar_sync(0, 256);
            mbar_wait(bar_w, 0);
            TR(0);
            gemv_slice(sb, warp, lane);
            bar_sync(0, 256);
            if (tid == 0) load_slice(sb + SB_STG, &M.uk, r, bar_w);
            uint32_t qb[8][2];
#pragma unroll
            for (int ks = 0; ks < 8; ks++) {
                const float2 a = *reinterpret_cast<const float2*>(yb + (g & 1) * 128 + ks * 16 + 2 * tq);
                const float2 b = *reinterpret_cast<const float2*>(yb + (g & 1) * 128 + ks * 16 + 8 + 2 * tq);
                qb[ks][0] = packbf(a.x, a.y);
                qb[ks][1] = packbf(b.x, b.y);
            }
            mbar_wait(bar_w, 1);
            const uint32_t wb = sb + SB_STG + (warp >> 2) * 65536 + ((warp & 3) * 64 + (lane & 15)) * 128;
#pragma unroll 1
            for (int mt = 0; mt < 4; mt++) {
                float d[4] = {0.f, 0.f, 0.f, 0.f};
#pragma unroll
                for (int ks = 0; ks < 8; ks++) {
                    uint32_t a[4];
                    ldsm4(a, wb + (ks >> 2) * 32768 + mt * 2048 + (((2 * (ks & 3) + (lane >> 4)) ^ (lane & 7)) << 4));
                    mma16816(d, a, qb[ks][0], qb[ks][1]);
                }
                if (tq == 0) {
                    const int c = warp * 64 + mt * 16 + g;
                    xs[c] = d[0]; xs[512 + c] = d[1]; xs[c + 8] = d[2]; xs[512 + c + 8] = d[3];
                }
            }
            bar_sync(0, 256);
            if (tid == 32) {
#pragma unroll 1
                for (int x = 0; x < 16; x++) {
                    if (!(x & 7)) mbar_expect(sb + SB_BAR + x, 65536);
                    tma2d_ef(sb + SB_STG + x * 8192, &M.c, (x & 7) * 64, crow0 + (x >> 3) * 1024, sb + SB_BAR + (x & 8));
                }
            }
            const int b = tid >> 7, lo = (tid >> 6) & 1, ch = tid & 63;
            float v[8];
#pragma unroll
            for (int i = 0; i < 8; i++) {
                const float x = xs[b * 512 + ch * 8 + i];
                v[i] = lo ? x - bf16r(x) : x;
            }
            const int row = 16 * (r >> 3) + (r & 7) + 8 * lo;
            S->qimg[b * 4096 + (ch >> 3) * 512 + row * 8 + ((ch & 7) ^ (r & 7))] =
                make_uint4(packbf(v[0], v[1]), packbf(v[2], v[3]), packbf(v[4], v[5]), packbf(v[6], v[7]));
            bar_sync(0, 256);
            if (warp == 0) {
                if (lane == 0) { __threadfence(); st_release(S->qflag + r, tag); }
                wait_flags(S->qflag, tag, lane);
                if (lane == 0) {
                    fence_async_all();
                    mbar_expect(bar_x, 65536);
                    bulk_g2s(sb + SB_QIMG, S->qimg + (r >> 4) * 4096, 65536, bar_x);
                }
            }
            mbar_wait(bar_x, 0);
        }
        TR(1);
        {
            const int wg = warp >> 2;
            float acc[4][16];
#pragma unroll
            for (int i = 0; i < 64; i++) acc[i >> 4][i & 15] = 0.f;
            const int head = (warp & 3) * 8 + g;
            const uint32_t pa = sb + SB_P + wg * 4096;
            float* al = reinterpret_cast<float*>(sm + SB_AL) + wg * 32;
            float m = -FLT_MAX, l = 0.f;
#pragma unroll 1
            for (int t = 0; t < 8; t++) {
                const uint32_t stg = sb + SB_STG + (t & 1) * 65536;
                mbar_wait(sb + SB_BAR + (t & 1) * 8, (t >> 1) & 1);
                float s[32];
                uint32_t qa = sb + SB_QIMG;
                asm volatile("" : "+r"(qa));
                wg_fence();
#pragma unroll
                for (int k = 0; k < 32; k++) {
                    const uint32_t off = (k >> 2) * 8192 + (k & 3) * 32;
                    wgmma_n64_ss(s, gdesc(qa + off, 16, 1024), gdesc(stg + off, 16, 1024), k > 0);
                }
                wg_commit();
                wg_wait0();
                reg_fence(s);
                float p[16], mx = m;
#pragma unroll
                for (int i = 0; i < 8; i++) {
                    p[2 * i] = bf16r(bf16r(s[4 * i] + s[4 * i + 2]) * SCALE);
                    p[2 * i + 1] = bf16r(bf16r(s[4 * i + 1] + s[4 * i + 3]) * SCALE);
                    mx = fmaxf(mx, fmaxf(p[2 * i], p[2 * i + 1]));
                }
                mx = fmaxf(mx, shx(mx, 1));
                mx = fmaxf(mx, shx(mx, 2));
                const float alpha = ex2((m - mx) * LOG2E);
                m = mx;
                float sum = 0.f;
#pragma unroll
                for (int i = 0; i < 8; i++) {
                    const float a = ex2((p[2 * i] - mx) * LOG2E), b = ex2((p[2 * i + 1] - mx) * LOG2E);
                    sum += a + b;
                    sts32(pa + head * 128 + ((i ^ g) << 4) + tq * 4, packbf(a, b));
                }
                l = fmaf(l, alpha, sum);
                if (tq == 0) al[head] = alpha;
                asm volatile("fence.proxy.async.shared::cta;" ::: "memory");
                bar_sync(1 + wg, 128);
#pragma unroll
                for (int j = 0; j < 4; j++) {
                    const float2 a = *reinterpret_cast<const float2*>(al + 8 * j + 2 * tq);
#pragma unroll
                    for (int i = 0; i < 4; i++) { acc[i][4 * j] *= a.x; acc[i][4 * j + 1] *= a.y; acc[i][4 * j + 2] *= a.x; acc[i][4 * j + 3] *= a.y; }
                }
#pragma unroll
                for (int i = 0; i < 4; i++) reg_fence(acc[i]);
                wg_fence();
#pragma unroll
                for (int kk = 0; kk < 4; kk++)
#pragma unroll
                    for (int i = 0; i < 4; i++)
                        wgmma_n32_ts(acc[i], gdesc(stg + (wg * 4 + i) * 8192 + kk * 2048, 8192, 1024), gdesc(pa + kk * 32, 16, 1024));
                wg_commit();
                wg_wait0();
#pragma unroll
                for (int i = 0; i < 4; i++) reg_fence(acc[i]);
                bar_sync(0, 256);
                if (tid == 0) {
                    if (t + 2 < 8) {
                        const uint32_t bar = sb + SB_BAR + (t & 1) * 8;
                        mbar_expect(bar, 65536);
#pragma unroll 1
                        for (int x = 0; x < 8; x++) tma2d_ef(stg + x * 8192, &M.c, x * 64, crow0 + (t + 2) * 1024, bar);
                    }
                    if (t == 7) load_slice(sb + SB_STG, &M.uv, r, bar_w);
                }
            }
            TR(2);
            float* dst = reinterpret_cast<float*>(sm + SB_QIMG + 2 * tq * PROW) + wg * 256 + (warp & 3) * 16 + g;
#pragma unroll
            for (int i = 0; i < 64; i++)
                dst[(((i >> 2) & 3) * 8 + (i & 1)) * (PROW / 4) + (i >> 4) * 64 + (i & 2) * 4] = acc[i >> 4][i & 15];
            l += shx(l, 1); l += shx(l, 2);
            if (wg == 0 && tq < 2) *reinterpret_cast<float4*>(sm + SB_QIMG + head * PROW + 2048 + tq * 16) = make_float4(m, l, 0.f, 0.f);
            asm volatile("fence.proxy.async.shared::cta;" ::: "memory");
            bar_sync(0, 256);
            if (warp == 0) {
                bulk_s2g(S->bpart + (lane * 32 + r) * (PROW / 16), sb + SB_QIMG + lane * PROW, PROW);
                asm volatile("cp.async.bulk.commit_group;" ::: "memory");
                asm volatile("cp.async.bulk.wait_group 0;" ::: "memory");
                fence_async_all();
                __threadfence();
                __syncwarp();
                if (lane == 0) st_release(S->bflag + r, tag);
                wait_flags(S->bflag, tag, lane);
                if (lane == 0) {
                    fence_async_all();
                    mbar_expect(bar_x, 32 * PROW);
                    bulk_g2s(sb + SB_QIMG, S->bpart + r * 32 * (PROW / 16), 32 * PROW, bar_x);
                }
            }
        }
        {
            const int b = tid >> 7, c4 = tid & 127;
            mbar_wait(bar_x, 1);
            TR(3);
            const float2 ml = *reinterpret_cast<const float2*>(sm + SB_QIMG + (b * 16 + (lane & 15)) * PROW + 2048);
            float MM = ml.x;
            MM = fmaxf(MM, shx(MM, 1)); MM = fmaxf(MM, shx(MM, 2)); MM = fmaxf(MM, shx(MM, 4)); MM = fmaxf(MM, shx(MM, 8));
            const float e = ex2((ml.x - MM) * LOG2E);
            float L = e * ml.y;
            L += shx(L, 1); L += shx(L, 2); L += shx(L, 4); L += shx(L, 8);
            const float wgt = e / L;
            float4 o = make_float4(0.f, 0.f, 0.f, 0.f);
#pragma unroll 4
            for (int i = 0; i < 16; i++) {
                const float w = __shfl_sync(0xffffffffu, wgt, i);
                const float4 v = *reinterpret_cast<const float4*>(sm + SB_QIMG + (b * 16 + i) * PROW + c4 * 16);
                o.x = fmaf(w, v.x, o.x); o.y = fmaf(w, v.y, o.y); o.z = fmaf(w, v.z, o.z); o.w = fmaf(w, v.w, o.w);
            }
            uint32_t* xh = reinterpret_cast<uint32_t*>(xs);
            const uint32_t h0 = packbf(o.x, o.y), h1 = packbf(o.z, o.w);
            *reinterpret_cast<uint2*>(xh + (2 * b) * 264 + c4 * 2) = make_uint2(h0, h1);
            *reinterpret_cast<uint2*>(xh + (2 * b + 1) * 264 + c4 * 2) =
                make_uint2(packbf(o.x - bflo(h0), o.y - bfhi(h0)), packbf(o.z - bflo(h1), o.w - bfhi(h1)));
            bar_sync(0, 256);
            mbar_wait(bar_w, 0);
            gemv_slice(sb, warp, lane);
            bar_sync(0, 256);
            if (tid < 64) {
                const float* y = yb + warp * 128 + 16 * g + 2 * tq;
                st_b128(S->frag[0] + (warp * 32 + r) * 32 + lane, make_uint4(packbf(y[0], y[1]), tag, packbf(y[8], y[9]), tag));
            }
        }
        TR(4);
    }
}

__global__ void __launch_bounds__(384, 1)
fused_decode_kernel(const Params P, const __grid_constant__ Maps M) {
    extern __shared__ __align__(1024) uint8_t sm[];
    const uint32_t sb = s2u(sm);
    const int tid = threadIdx.x, lane = tid & 31, bx = blockIdx.x;
    asm volatile("{\n.reg .pred p;\nsetp.lt.u32 p, %1, 256;\n@p prefetch.global.L2 [%0];\n}"
                 ::"l"(P.wq + (unsigned)(bx * 32768 + tid * 128)), "r"(tid) : "memory");
    const int warp = __shfl_sync(0xffffffffu, tid >> 5, 0);
    const int g = lane >> 2, tq = lane & 3;
    Scratch* const S = P.scr;

    if (!(bx & 1)) {
        const int grp = (bx >> 1) & 7, crk = bx >> 4;
        const int rowbase = grp * (UPG * 64);
        auto issue = [&](int slot, unsigned tk, int v) {
            const int row = rowbase + (int)((tk & ~255u) | ((tk + grp * ROT) & 255u)) * 64;
            const uint32_t full = sb + SA_FULL + slot * 16 + v * 8;
            mbar_expect(full, 8192);
            tma2d_ef(sb + slot * 16384 + v * 8192, &M.kv[v], 0, row, full);
        };
        if (warp >= 8) {
            const int w = warp - 8;
            const bool one = elect();
            if (one) {
                mbar_init(sb + SA_FULL + w * 16, 1);
                mbar_init_fence();
                TR(3);
                sts32(sb + SA_META + w * 4, 0);
                if (w < SKEW) issue(w, w * CPG + crk, 0);
#pragma unroll
                for (int i = 0; i < SPW; i++) {
                    if (i) mbar_init(sb + SA_FULL + (w + i * NW) * 16, 1);
                    mbar_init(sb + SA_FULL + (w + i * NW) * 16 + 8, 1);
                    mbar_init(sb + SA_GOV + (w + i * NW) * 8, 1);
                    mbar_init(sb + SA_EMPTY + (w + i * NW) * 8, 2);
                    mbar_arrive(sb + SA_EMPTY + (w + i * NW) * 8);
                }
                if (w < SKEW) mbar_arrive(sb + SA_EMPTY + w * 8);
                sts32(sb + SA_LIM + w * 4, LIM);
                mbar_init_fence();
            }
            __syncwarp();
            bar_arrive(2, (NW + 1) * 32);
            bar_arrive(1, (2 * NW + 1) * 32);
            unsigned c = 0, tbase = 0;
            int slot = w;
            uint32_t eph = 0;
#pragma unroll 1
            for (int n = 0;; n++) {
                unsigned tk = (n * NW + w) * CPG + crk;
                if (n == SPW) {
                    mbar_wait(sb + SA_EMPTY + w * 8, 1);
                    tbase = NSL * CPG - lds32(sb + SA_CNT + 32) * TICK_INC;
                }
                if (n >= SPW) {
                    const unsigned own = __shfl_sync(0xffffffffu, c, grp);
                    tk = own + tbase;
                    const int lag = (int)(__reduce_add_sync(0xffffffffu, c) - NG * own);
                    if (one) sts32(sb + SA_LIM + w * 4, lag > BAL * NG ? LIM + 1 : lag < -BAL * NG ? LIM - 1 : LIM);
                }
                mbar_wait(sb + SA_EMPTY + slot * 8, eph);
                if (tk >= UPG) {
                    if (one) { sts32(sb + SA_LIM + w * 4, 0); sts32(sb + SA_META + slot * 4, 8); mbar_arrive(sb + SA_FULL + slot * 16); }
                    return;
                }
                if (one && (n || w >= SKEW)) {
                    sts32(sb + SA_META + slot * 4, tk >> 8);
                    issue(slot, tk, 0);
                    if (tk == 300) TR(6);
                    if (tk == UPG - FIRE_T) { st_b64(S->fire + grp, gt(), lds32(sb + SA_CNT + 32) + 1); TR(4); }
                }
                if (n >= SPW - 1) {
                    if (lane == grp) c = atom_inc(S->ctr + lane);
                    else if (lane < NG) c = ld_relaxed1(S->ctr + lane);
                }
                mbar_wait(sb + SA_GOV + slot * 8, eph);
                if (one) issue(slot, tk, 1);
                TR(0);
                slot += NW;
                if (slot >= NSL) { slot -= NSL; eph ^= 1; }
                __syncwarp();
            }
        }
        if (warp == 0) {
            bool busy = lane < 2 * SKEW && !(lane & 1);
            uint32_t par = busy ? 0 : 1;
            int slot = SKEW;
            bool first = true;
            const unsigned c0 = clk32() + RAMP_T0;
            const int own = lane >= 2 * NSL ? -1 : ((lane >> 1) + (lane & 1) * SKEW) % NSL;
            const uint32_t fb = sb + SA_FULL + lane * 8, lw = sb + SA_LIM + ((lane >> 1) % NW) * 4;
            const uint32_t go = sb + ((lane & 1) ? SA_GOV : SA_EMPTY) + (lane >> 1) * 8;
            bar_sync(2, (NW + 1) * 32);
#pragma unroll 1
            for (int it = 0; it < SPIN_MAX; it++) {
                bool ok = true;
                if (busy) ok = mbar_test(fb, par);
                int lim = lds32(lw);
                if (first) lim = min(LIM0, SKEW + max((int)(clk32() - c0), 0) / RAMP_S);
                busy = busy && !ok && lim;
                const int n = __popc(__ballot_sync(0xffffffffu, busy));
                if (!__any_sync(0xffffffffu, lim)) return;
                const bool mine = own == slot && lim;
                if (!__any_sync(0xffffffffu, mine && (busy || n > lim - 2))) {
                    if (mine) { mbar_arrive(go); busy = true; par ^= 1; }
                    if (++slot == NSL) { slot = 0; first = false; }
                    it = 0;
                }
            }
            __trap();
        }
        if (warp == 2 || warp == 3) return;
        auto fetch_q = [&](int pl, unsigned tag) {
            uint4 v;
            for (int it = 0;; it++) {
                v = ld_b128(S->qpub + (grp * 8 + pl) * 32 + lane);
                if (__all_sync(0xffffffffu, v.y == tag)) break;
                if (it > SPIN_MAX) __trap();
            }
            *reinterpret_cast<uint2*>(sm + SA_Q + pl * 256 + lane * 8) = make_uint2(v.x, v.z);
        };
        if (warp == 1) {
            const unsigned epoch = ld_relaxed1(S->epoch + bx * 8);
            if (lane == 0) { mbar_init(sb + SA_QBAR, 32); mbar_init_fence(); }
            if (lane < 9) sts32(sb + SA_CNT + lane * 4, lane < 8 ? 0u : epoch);
            bar_arrive(1, (2 * NW + 1) * 32);
            if (lane == 0) S->epoch[bx * 8] = epoch + 1;
            __nanosleep(3000);
#pragma unroll 1
            for (int pl = 1; pl < 8; pl++) fetch_q(pl, epoch + 1);
            mbar_arrive(sb + SA_QBAR);
            return;
        }
        const int cw = warp - 4;
        bar_sync(1, (2 * NW + 1) * 32);
        const unsigned tag = lds32(sb + SA_CNT + 32) + 1;
        __nanosleep(QSLEEP);
        fetch_q(0, tag);
        __syncwarp();
        TR(0);

        const uint32_t t8 = tag & 0xffu;
        uint32_t koff[4], voff[4];
#pragma unroll
        for (int i = 0; i < 4; i++) {
            koff[i] = ((lane & 7) + 8 * ((lane >> 3) & 1)) * 128 + (((2 * i + (lane >> 4)) ^ (lane & 7)) << 4);
            voff[i] = ((lane & 7) + 8 * (lane >> 4)) * 128 + (((2 * i + ((lane >> 3) & 1)) ^ (lane & 7)) << 4);
        }
        uint32_t psel[4][2];
#pragma unroll
        for (int i = 0; i < 4; i++) {
            psel[i][0] = (g >> 1) != i ? 0x4444u : (g & 1) ? 0x1044u : 0x4410u;
            psel[i][1] = (g >> 1) != i ? 0x4444u : (g & 1) ? 0x3244u : 0x4432u;
        }
        uint32_t qf[4][2];
        auto load_q = [&](int pl) {
            const uint32_t q = sb + SA_Q + pl * 256 + ((g & 1) * 32 + tq) * 4;
#pragma unroll
            for (int ks = 0; ks < 4; ks++) { qf[ks][0] = lds32(q + ks * 32); qf[ks][1] = lds32(q + ks * 32 + 16); }
        };
        load_q(0);
        float acc[4][4], m = -FLT_MAX, l = 0.f, ls = 0.f;
#pragma unroll
        for (int i = 0; i < 4; i++) acc[i][0] = acc[i][1] = acc[i][2] = acc[i][3] = 0.f;
        int slot = cw, cur = 0;
        uint32_t ph = 0;
#pragma unroll 1
        for (;;) {
            mbar_wait(sb + SA_FULL + slot * 16, ph);
            const int pl = lds32(sb + SA_META + slot * 4);
            if (pl != cur) {
#pragma unroll 1
            for (; cur != pl; cur++) {
                float* s0 = reinterpret_cast<float*>(sm + SA_SLOT) + cur * (NW * 132);
                float* sw = s0 + cw * 132 + tq * 16 + (g >> 1) * 4 + (g & 1);
                sw[0] = (acc[0][0] + acc[1][0]) + (acc[2][0] + acc[3][0]);
                sw[2] = (acc[0][2] + acc[1][2]) + (acc[2][2] + acc[3][2]);
                sw[64] = (acc[0][1] + acc[1][1]) + (acc[2][1] + acc[3][1]);
                sw[66] = (acc[0][3] + acc[1][3]) + (acc[2][3] + acc[3][3]);
                if (lane == 0) *reinterpret_cast<float2*>(s0 + cw * 132 + 128) = make_float2(m, ls);
                __syncwarp();
                int old = 0;
                if (lane == 0) asm volatile("atom.acq_rel.cta.shared.inc.u32 %0, [%1], 255;" : "=r"(old) : "r"(sb + SA_CNT + cur * 4) : "memory");
                if (__shfl_sync(0xffffffffu, old, 0) == NW - 1) {
                    float2 ml[NW];
                    float4 v[NW];
#pragma unroll
                    for (int w = 0; w < NW; w++) {
                        ml[w] = *reinterpret_cast<const float2*>(s0 + w * 132 + 128);
                        v[w] = *reinterpret_cast<const float4*>(s0 + w * 132 + lane * 4);
                    }
                    float MM = ml[0].x;
#pragma unroll
                    for (int w = 1; w < NW; w++) MM = fmaxf(MM, ml[w].x);
                    float4 o = make_float4(0.f, 0.f, 0.f, 0.f);
                    float L = 0.f;
#pragma unroll
                    for (int w = 0; w < NW; w++) {
                        const float e = ex2((ml[w].x - MM) * LOG2E);
                        o.x = fmaf(e, v[w].x, o.x); o.y = fmaf(e, v[w].y, o.y); o.z = fmaf(e, v[w].z, o.z); o.w = fmaf(e, v[w].w, o.w);
                        L = fmaf(e, ml[w].y, L);
                    }
                    const int rec = (grp * 8 + cur) * CPG + crk;
                    st_b128(S->apart + rec * 32 + lane, make_uint4(tagf(o.x, t8), __float_as_uint(o.y), __float_as_uint(o.z), __float_as_uint(o.w)));
                    if (lane < 4) st_b64(S->aml + rec * 4 + lane, __float_as_uint(MM), tagf(L, t8));
                    if (PLACE && cur == 6) {
                        st_b128(S->apart + (rec + CPG) * 32 + lane, make_uint4(t8 ^ 0x80u, 0, 0, 0));
                        if (lane < 4) st_b64(S->aml + (rec + CPG) * 4 + lane, 0, t8 ^ 0x80u);
                    }
                    TR(2);
                }
#pragma unroll
                for (int i = 0; i < 4; i++) acc[i][0] = acc[i][1] = acc[i][2] = acc[i][3] = 0.f;
                m = -FLT_MAX; l = ls = 0.f;
            }
                if (pl == 8) break;
                mbar_wait(sb + SA_QBAR, 0);
                load_q(pl);
            }
            float s4[4][4];
            const uint32_t kb = sb + slot * 16384;
#pragma unroll
            for (int j = 0; j < 4; j++) {
                s4[j][0] = s4[j][1] = s4[j][2] = s4[j][3] = 0.f;
                const bool on = (g >> 1) == j;
#pragma unroll
                for (int ks = 0; ks < 4; ks++) {
                    uint32_t a[4];
                    ldsm4(a, kb + j * 2048 + koff[ks]);
                    mma16816(s4[j], a, on ? qf[ks][0] : 0u, on ? qf[ks][1] : 0u);
                }
            }
            float d[4];
#pragma unroll
            for (int r = 0; r < 4; r++) d[r] = (s4[0][r] + s4[1][r]) + (s4[2][r] + s4[3][r]);
            float sa = (g & 1) ? d[1] : d[0], sc = (g & 1) ? d[3] : d[2];
            sa += shx(sa, 4); sc += shx(sc, 4);
            uint32_t sp = packbf(sa, sc);
            sp = packbf(bflo(sp) * SCALE, bfhi(sp) * SCALE);
            sa = bflo(sp); sc = bfhi(sp);
            const float mx = warp_max(fmaxf(fmaxf(sa, sc), m));
            const float alpha = ex2((m - mx) * LOG2E);
            m = mx;
            const float pa = ex2((sa - mx) * LOG2E), pc = ex2((sc - mx) * LOG2E);
            const uint32_t pk = packbf(pa, pc);
            uint32_t pb[4][4][2];
#pragma unroll
            for (int j = 0; j < 4; j++) {
                const uint32_t pj = __shfl_sync(0xffffffffu, pk, 8 * tq + j);
#pragma unroll
                for (int i = 0; i < 4; i++) { pb[j][i][0] = prmt0(pj, psel[i][0]); pb[j][i][1] = prmt0(pj, psel[i][1]); }
            }
            l = fmaf(l, alpha, pa + pc);
            ls = l + shx(l, 8);
#pragma unroll
            for (int i = 0; i < 4; i++) { acc[i][0] *= alpha; acc[i][1] *= alpha; acc[i][2] *= alpha; acc[i][3] *= alpha; }
            mbar_wait(sb + SA_FULL + slot * 16 + 8, ph);
            TR(1);
            const uint32_t vb = kb + 8192;
#pragma unroll
            for (int i = 0; i < 4; i++)
#pragma unroll
                for (int j = 0; j < 4; j++) {
                    uint32_t a[4];
                    ldsm4t(a, vb + j * 2048 + voff[i]);
                    mma16816(acc[j], a, pb[j][i][0], pb[j][i][1]);
                }
            ls += shx(ls, 16); ls += shx(ls, 1); ls += shx(ls, 2);
            __syncwarp();
            if (lane == 0) mbar_arrive(sb + SA_EMPTY + slot * 8);
            slot += NW;
            if (slot >= NSL) { slot -= NSL; ph ^= 1; }
        }
        TROUT();
        return;
    }

    const int r = bx >> 2, isC = (bx >> 1) & 1;
    const uint32_t bar_h = sb + SB_BAR + 32;
    if (warp < 8) {
    {
        const uint32_t bar_q = bar_h + (NT + warp) * 8, box = sb + SB_QIMG + warp * 8192;
        if (elect()) {
            mbar_init(bar_q, 1);
            mbar_init_fence();
            mbar_expect(bar_q, 8192 + 256);
            tma2d(box, &M.qa, (bx >> 1) * 64, warp * 64, bar_q);
            bulk_g2s(sb + SB_P + 4096 + warp * 288, P.ax + warp * 32, 128, bar_q);
            bulk_g2s(sb + SB_P + 4096 + warp * 288 + 144, P.ax + 256 + warp * 32, 128, bar_q);
        }
        unsigned epoch = 0;
        if (warp < 2) epoch = ld_relaxed1(S->epoch + bx * 8);
        uint4* const qdst = S->qpub + ((lane >> 4) * 32 + r) * 32 + isC * 16 + (lane & 15);
        if (PLACE && warp == 0) st_b128(qdst, make_uint4(0, 0, 0, 0));
        if (tid == 32) {
#pragma unroll
            for (int i = 0; i < 4 + NT; i++) mbar_init(sb + SB_BAR + i * 8, 1);
            mbar_init_fence();
            sts32(sb + SB_CNT, epoch);
        }
        __syncwarp();
        mbar_wait(bar_q, 0);
        TR(0);
        uint32_t b[8];
#pragma unroll
        for (int i = 0; i < 8; i++) b[i] = lds32(sb + SB_P + 4096 + warp * 288 + (g & 1) * 144 + tq * 4 + i * 16);
        float d[4][4];
        uint32_t a[4][4][4];
#pragma unroll
        for (int i = 0; i < 4; i++) {
            d[i][0] = d[i][1] = d[i][2] = d[i][3] = 0.f;
#pragma unroll
            for (int ks = 0; ks < 4; ks++)
                ldsm4t(a[i][ks], box + ks * 2048 + ((lane & 7) + 8 * (lane >> 4)) * 128 + (((2 * i + ((lane >> 3) & 1)) ^ (lane & 7)) << 4));
        }
#pragma unroll
        for (int ks = 0; ks < 4; ks++)
#pragma unroll
            for (int i = 0; i < 4; i++) mma16816(d[i], a[i][ks], b[2 * ks], b[2 * ks + 1]);
        float* qred = reinterpret_cast<float*>(sm + SB_P);
#pragma unroll
        for (int c = 0; c < 4; c++)
            qred[warp * 128 + (c & 1) * 64 + tq * 16 + (c >> 1) * 8 + g] = tq == 0 ? d[0][c] : tq == 1 ? d[1][c] : tq == 2 ? d[2][c] : d[3][c];
        bar_sync(0, 256);
        if (warp == 0) {
            float4 v[8];
#pragma unroll
            for (int w = 0; w < 8; w++) v[w] = *reinterpret_cast<const float4*>(qred + w * 128 + lane * 4);
#pragma unroll
            for (int o = 4; o; o >>= 1)
#pragma unroll
                for (int w = 0; w < o; w++) { v[w].x += v[w + o].x; v[w].y += v[w + o].y; v[w].z += v[w + o].z; v[w].w += v[w + o].w; }
            st_b128(qdst, make_uint4(packbf(v[0].x, v[0].y), epoch + 1, packbf(v[0].z, v[0].w), epoch + 1));
            if (lane == 0) S->epoch[bx * 8] = epoch + 1;
        }
        TR(1);
    }
    if (!isC) latent_branch(P, M, sm TRPASS);
    }

    const int isA = (r >> JMAP) & 1, cb = ((r >> (JMAP + 1)) << JMAP) + (r & ((1 << JMAP) - 1)), nsnd = isA ? NSA : NSB, isCA = isC & isA;
    const int y0 = isC ? nsnd : 0, y1 = isC ? 32 - 4 * isA : nsnd;
    const int nreq = isC ? 32 - nsnd : nsnd;
    float* const red = reinterpret_cast<float*>(sm + SC_RED);
    const uint32_t wlane = wo_lane(sb, lane);
    if (warp < 8) {
        const unsigned tag = lds32(sb + SB_CNT) + 1;
        const uint32_t t8 = tag & 0xffu;
        if (isC) __nanosleep(8000);
#pragma unroll 1
        for (int step = 0;; step++) {
            if (isCA) {
                const int pair = warp * 8 + (step ? 7 : cb % 7);
                const uint2* mlp = S->aml + pair * (CPG * 4) + (lane & 7) * 4;
                const uint4* src = S->apart + pair * (CPG * 32) + lane;
                asm volatile("" : "+l"(mlp), "+l"(src));
                if (!step) {
                    for (int it = 0; !__all_sync(0xffffffffu, (ld_b64(mlp).y & 0xffu) == t8); it++) {
                        if (it > SPIN_MAX) __trap();
                        __nanosleep(CPOLL);
                    }
                } else {
                    mbar_wait(bar_h + (warp & 3) * 16, 0);
                    mbar_wait(bar_h + (warp & 3) * 16 + 8, 0);
                }
                uint32_t wf[2][8][4];
#pragma unroll
                for (int ks = 0; ks < 8; ks++) {
                    ldsm4t(wf[0][ks], wlane + (warp & 3) * 8192 + ks * 1024);
                    ldsm4t(wf[1][ks], (wlane ^ 32) + (warp & 3) * 8192 + ks * 1024);
                }
                if (step) mbar_wait(sb + SB_BAR, 0);
                TR(3);
                uint4 v[CPG];
                uint2 ml = ld_b64(mlp);
#pragma unroll
                for (int i = 0; i < CPG; i++) v[i] = ld_b128(src + i * 32);
                for (int it = 0;; it++) {
                    unsigned x = ml.y ^ t8;
#pragma unroll
                    for (int i = 0; i < CPG; i++) x |= v[i].x ^ t8;
                    if (!__any_sync(0xffffffffu, x & 0xffu)) break;
                    if (it > SPIN_MAX) __trap();
                    ml = ld_b64(mlp);
#pragma unroll
                    for (int i = 0; i < CPG; i++)
                        if ((v[i].x & 0xffu) != t8) v[i] = ld_b128(src + i * 32);
                }
                TR(2);
                const float e = ex2((__uint_as_float(ml.x) - warp_max(__uint_as_float(ml.x))) * LOG2E);
                float L = e * __uint_as_float(ml.y), oa[4], ob[4];
                L += shx(L, 1);
#pragma unroll
                for (int i = 0; i < CPG; i++) {
                    const float w = __shfl_sync(0xffffffffu, e, i);
                    float (&o)[4] = (i & 1) ? ob : oa;
                    o[0] = i < 2 ? w * __uint_as_float(v[i].x) : fmaf(w, __uint_as_float(v[i].x), o[0]);
                    o[1] = i < 2 ? w * __uint_as_float(v[i].y) : fmaf(w, __uint_as_float(v[i].y), o[1]);
                    o[2] = i < 2 ? w * __uint_as_float(v[i].z) : fmaf(w, __uint_as_float(v[i].z), o[2]);
                    o[3] = i < 2 ? w * __uint_as_float(v[i].w) : fmaf(w, __uint_as_float(v[i].w), o[3]);
                }
                L += shx(L, 2);
                L += shx(L, 4);
                float inv;
                asm("rcp.approx.ftz.f32 %0, %1;" : "=f"(inv) : "f"(L));
                const uint32_t b0 = packbf((oa[0] + ob[0]) * inv, (oa[1] + ob[1]) * inv), b1 = packbf((oa[2] + ob[2]) * inv, (oa[3] + ob[3]) * inv);
                float d[4][4];
#pragma unroll
                for (int i = 0; i < 4; i++) d[i][0] = d[i][1] = d[i][2] = d[i][3] = 0.f;
#pragma unroll
                for (int ks = 0; ks < 8; ks++) {
                    mma16816(d[ks & 1], wf[0][ks], g == ks ? b0 : 0u, g == ks ? b1 : 0u);
                    mma16816(d[2 + (ks & 1)], wf[1][ks], g == ks ? b0 : 0u, g == ks ? b1 : 0u);
                }
                const float x0 = (d[0][0] + d[0][1]) + (d[1][0] + d[1][1]), x1 = (d[0][2] + d[0][3]) + (d[1][2] + d[1][3]);
                const float x2 = (d[2][0] + d[2][1]) + (d[3][0] + d[3][1]), x3 = (d[2][2] + d[2][3]) + (d[3][2] + d[3][3]);
                const float z0 = ((tq & 2) ? x2 : x0) + shx((tq & 2) ? x0 : x2, 2), z1 = ((tq & 2) ? x3 : x1) + shx((tq & 2) ? x1 : x3, 2);
                red[(4 + (warp & 3)) * 80 + (warp >> 2) * 40 + tq * 8 + g] = ((tq & 1) ? z1 : z0) + shx((tq & 1) ? z0 : z1, 1);
                if (step) {
                    bar_arrive(5, 384);
                    TR(5);
                    TROUT();
                    return;
                }
                st_b128(S->frag[1] + pair * 32 + lane, make_uint4(b0, tag, b1, 0));
            }
            uint2* const bfr = reinterpret_cast<uint2*>(sm + SC_FR) + ((warp & 3) * 32 + (g >> 1) * 8 + (warp >> 2) * 4 + tq) * 2 + (g & 1);
            const int p0 = (y0 + 3 - (warp & 3)) >> 2, p1 = (y1 + 3 - (warp & 3)) >> 2;
            const uint4* fsrc = S->frag[0] + isA * 2048 + warp * 256 + lane;
            for (int it = 0;; it++) {
                const uint4 v = ld_b128(fsrc + (p1 - 1) * 32);
                if (__all_sync(0xffffffffu, v.y == tag)) {
                    uint4 u[4];
                    bool ok = true;
#pragma unroll
                    for (int k = 0; k < 4; k++) u[k] = ld_b128(fsrc + min(p0 + k, p1 - 1) * 32);
#pragma unroll
                    for (int k = 0; k < 4; k++) { ok = ok && u[k].y == tag; bfr[min(p0 + k, p1 - 1) * 256] = make_uint2(u[k].x, u[k].z); }
                    bfr[(p1 - 1) * 256] = make_uint2(v.x, v.z);
                    if (__all_sync(0xffffffffu, ok)) break;
                }
                if (it > SPIN_MAX) __trap();
                __nanosleep(CPOLL);
            }
            if (!isCA && warp < 4) break;
            bar_arrive(4, 384);
            if (!isCA) { TROUT(); return; }
        }
    }
    bar_sync(4, 384);
    if (warp == 11) {
        const CUtensorMap* map = &M.wo[isA];
        const unsigned tag = lds32(sb + SB_CNT) + 1;
        const uint32_t t8 = tag & 0xffu;
        uint2* const snd = S->snd + r * 32 + lane;
        asm volatile("prefetch.tensormap [%0];" ::"l"(map) : "memory");
        if (PLACE && !isC) st_b64(snd, t8 ^ 0x80u, 0);
        uint2 f;
        for (int it = 0;; it++) {
            f = ld_b64(S->fire + (lane & 7));
            if (__all_sync(0xffffffffu, f.y == tag)) break;
            if (it > SPIN_MAX) __trap();
            __nanosleep(FPOLL);
        }
        const unsigned t0 = __shfl_sync(0xffffffffu, f.x, 0);
        unsigned t1 = t0 + (__reduce_add_sync(0xffffffffu, (int)(f.x - t0)) >> 5) + FIRE_NS;
        TR(2);
        if (elect()) {
            const int n1 = nreq - (isC ? (isA ? NLA : NLB) : 0);
            const int dt = !isC ? (isA ? FIRE_W / NSA : FIRE_W / NSB) : isA ? FIRE_W / (32 - NSA - NLA) : FIRE_W / (32 - NSB - NLB);
            const unsigned t2 = t1 + REC_NS;
            bool rec = isCA;
            int y = isCA ? 28 : y0;
#pragma unroll 1
            for (int i = 0; i < nreq; i++) {
                const int row = ((y & 3) * 8 + (y >> 2)) * 128;
                mbar_expect(bar_h + i * 16, 4096);
                mbar_expect(bar_h + i * 16 + 8, 4096);
                if (++y == 32) y = y0;
                if (i <= n1) {
                    unsigned t;
                    for (int it = 0; (int)((t = gt()) - t1) < 0 && it < 4096; it++) {}
                    t1 += dt;
                    if (rec && (int)(t - t2) >= 0) { mbar_arrive(sb + SB_BAR); rec = false; }
                }
                tma2d(sb + i * 8192, map, cb * 32, row, bar_h + i * 16);
                tma2d(sb + i * 8192 + 4096, map, cb * 32, row + 64, bar_h + i * 16 + 8);
            }
            TR(3);
            if (rec) {
                for (int it = 0; (int)(gt() - t2) < 0 && it < 4096; it++) {}
                mbar_arrive(sb + SB_BAR);
            }
        }
        __syncwarp();
        uint2 o = make_uint2(0, 0);
        if (isC) {
            for (int it = 0;; it++) {
                o = ld_b64(snd);
                if (__all_sync(0xffffffffu, (o.x & 0xffu) == t8)) break;
                if (it > SPIN_MAX) __trap();
            }
        }
        TR(4);
        uint32_t* const dst = reinterpret_cast<uint32_t*>(P.out) + (lane >> 4) * 512 + (isA ? 0 : 256) + cb * 16 + (lane & 15);
        const float2* q = reinterpret_cast<const float2*>(red) + (lane >> 4) * 20 + (lane & 15);
        bar_sync(5, isCA ? 384 : 256);
        const float2 p0 = q[0], p1 = q[40], p2 = q[80], p4 = q[160], p5 = q[200], p6 = q[240], p7 = q[280];
        const float sx = ((p0.x + p1.x) + (p2.x + __uint_as_float(o.x))) + ((p4.x + p5.x) + (p6.x + p7.x));
        const float sy = ((p0.y + p1.y) + (p2.y + __uint_as_float(o.y))) + ((p4.y + p5.y) + (p6.y + p7.y));
        if (isC) *dst = packbf(sx, sy);
        else st_b64(snd, tagf(sx, t8), __float_as_uint(sy));
        TR(6);
        TROUT();
        return;
    }
    {
        const int nw = isCA ? 3 : 7;
        float e[4][4];
#pragma unroll
        for (int i = 0; i < 4; i++) e[i][0] = e[i][1] = e[i][2] = e[i][3] = 0.f;
#pragma unroll 1
        for (int i = (warp < 8 ? warp + 3 : warp - 8) + 4 * isCA; i < nreq; i += nw) {
            const uint32_t bp = sb + SC_FR + ((y0 + i - 4 * isCA) * 32 + (lane & 7)) * 16;
            uint4 b[4];
#pragma unroll
            for (int j = 0; j < 4; j++) b[j] = lds128(bp + j * 128);
#pragma unroll
            for (int hf = 0; hf < 2; hf++) {
                uint32_t a[8][4];
                mbar_wait(bar_h + i * 16 + hf * 8, 0);
#pragma unroll
                for (int j = 0; j < 8; j++) ldsm4t(a[j], (wlane ^ ((j & 1) * 32)) + i * 8192 + hf * 4096 + (j >> 1) * 1024);
#pragma unroll
                for (int j = 0; j < 8; j++) {
                    const uint4& c = b[2 * hf + (j >> 2)];
                    mma16816(e[(j & 1) * 2 + ((j >> 1) & 1)], a[j], (j & 2) ? c.z : c.x, (j & 2) ? c.w : c.y);
                }
            }
        }
        float* rx = red + (warp < 8 ? warp + 4 : warp - 8) * 80 + (tq & 1) * 40 + (tq >> 1) * 16 + g;
        float s4[4];
#pragma unroll
        for (int c = 0; c < 4; c++) s4[c] = (tq & 2) ? e[2][c] + e[3][c] : e[0][c] + e[1][c];
        rx[0] = (tq & 1) ? s4[1] : s4[0];
        rx[8] = (tq & 1) ? s4[3] : s4[2];
        bar_arrive(5, isCA ? 384 : 256);
        TROUT();
    }
}

typedef CUresult (*EncodeFn)(CUtensorMap*, CUtensorMapDataType, cuuint32_t, void*, const cuuint64_t*, const cuuint64_t*,
                             const cuuint32_t*, const cuuint32_t*, CUtensorMapInterleave, CUtensorMapSwizzle,
                             CUtensorMapL2promotion, CUtensorMapFloatOOBfill);

void make_map(EncodeFn enc, CUtensorMap* m, const void* base, uint64_t cols, uint64_t rows, uint32_t bc, uint32_t br,
              CUtensorMapL2promotion promo, CUtensorMapSwizzle sw = CU_TENSOR_MAP_SWIZZLE_128B) {
    cuuint64_t dims[2] = {cols, rows};
    cuuint64_t strides[1] = {cols * 2};
    cuuint32_t box[2] = {bc, br};
    cuuint32_t es[2] = {1, 1};
    enc(m, CU_TENSOR_MAP_DATA_TYPE_BFLOAT16, 2, const_cast<void*>(base), dims, strides, box, es,
        CU_TENSOR_MAP_INTERLEAVE_NONE, sw, promo, CU_TENSOR_MAP_FLOAT_OOB_FILL_NONE);
}

}

extern "C" void kernel_launch(void* const* d_in, const int* in_sizes, int n_in, void* d_out, int out_size) {
    (void)in_sizes; (void)n_in; (void)out_size;
    static EncodeFn enc = nullptr;
    static void* scr = nullptr;
    if (!enc) {
        void* fn = nullptr;
        cudaDriverEntryPointQueryResult qr;
        cudaGetDriverEntryPoint("cuTensorMapEncodeTiled", &fn, cudaEnableDefault, &qr);
        enc = (EncodeFn)fn;
        cudaGetSymbolAddress(&scr, g_scr);
        cudaFuncSetAttribute(fused_decode_kernel, cudaFuncAttributeMaxDynamicSharedMemorySize, SMEM_BYTES);
    }
    Maps m;
    make_map(enc, &m.kv[0], d_in[1], 64, 1048576, 64, 64, CU_TENSOR_MAP_L2_PROMOTION_NONE);
    make_map(enc, &m.kv[1], d_in[2], 64, 1048576, 64, 64, CU_TENSOR_MAP_L2_PROMOTION_NONE);
    make_map(enc, &m.qa, d_in[3], 4096, 512, 64, 64, CU_TENSOR_MAP_L2_PROMOTION_NONE);
    make_map(enc, &m.qb, d_in[7], 4096, 512, 64, 256, CU_TENSOR_MAP_L2_PROMOTION_L2_256B);
    make_map(enc, &m.wo[0], d_in[10], 512, 4096, 32, 64, WPROMO, CU_TENSOR_MAP_SWIZZLE_64B);
    make_map(enc, &m.wo[1], d_in[4], 512, 4096, 32, 64, WPROMO, CU_TENSOR_MAP_SWIZZLE_64B);
    make_map(enc, &m.c, d_in[6], 512, 16384, 64, 64, CU_TENSOR_MAP_L2_PROMOTION_NONE);
    make_map(enc, &m.uk, d_in[8], 4096, 512, 64, 256, CU_TENSOR_MAP_L2_PROMOTION_L2_256B);
    make_map(enc, &m.uv, d_in[9], 4096, 512, 64, 256, CU_TENSOR_MAP_L2_PROMOTION_L2_256B);
    Params p;
    p.scr = (Scratch*)scr;
    p.ax = (const uint32_t*)d_in[0];
    p.bx = (const uint32_t*)d_in[5];
    p.out = (__nv_bfloat16*)d_out;
    p.wq = (const char*)d_in[3];
    fused_decode_kernel<<<128, 384, SMEM_BYTES, cudaStreamPerThread>>>(p, m);
}
```

```cpp
#include <cuda_runtime.h>
#include <cuda_bf16.h>
#include <cuda.h>
#include <stdint.h>
#include <float.h>

#define LIM 14
#define LIM0 12
#define RAMP_S 200
#define RAMP_T0 0
#define BAL 4
#define SKEW 2
#define ROT 48
#define FIRE_T 60
#define FIRE_NS 3500
#define FIRE_W 2200
#define NLA 3
#define NLB 7
#define NSA 13
#define NSB 13
#define REC_NS 1900
#define JMAP 2
#define WPROMO CU_TENSOR_MAP_L2_PROMOTION_L2_128B
#define PLACE 1
#define BDELAY 1000
#define QSLEEP 1500
#define BPOLL 1000
#define CPOLL 700
#define FPOLL 300

namespace {

constexpr int NG = 8, CPG = 8, NW = 4;
constexpr int UPG = 2048;
constexpr int NSL = 12, SPW = NSL / NW;
constexpr unsigned TICK_INC = UPG - NSL * CPG + NW * CPG;
constexpr int SPIN_MAX = 1 << 22;
constexpr float LOG2E = 1.4426950408889634f;
constexpr float SCALE = 0.08838834764831845f;
constexpr uint64_t EVICT_FIRST = 0x12F0000000000000ull;

constexpr int SA_SLOT = NSL * 16384;
constexpr int SA_Q    = SA_SLOT + 8 * NW * 132 * 4;
constexpr int SA_FULL = SA_Q + 2048;
constexpr int SA_EMPTY = SA_FULL + NSL * 16;
constexpr int SA_GOV  = SA_EMPTY + NSL * 8;
constexpr int SA_QBAR = SA_GOV + NSL * 8;
constexpr int SA_META = SA_QBAR + 8;
constexpr int SA_LIM  = SA_META + NSL * 4;
constexpr int SA_CNT  = SA_LIM + 16;
constexpr int SA_END  = SA_CNT + 64;
constexpr int PROW    = 2080;
constexpr int SB_STG  = 0;
constexpr int SB_QIMG = 131072;
constexpr int SB_P    = SB_QIMG + 32 * PROW;
constexpr int SB_AL   = SB_P + 8192;
constexpr int SB_X    = SB_AL + 256;
static_assert(SB_P % 1024 == 0, "swizzle atom");
constexpr int SB_QB   = SB_X + 4352;
constexpr int NT      = 40;
constexpr int SC_FR   = NT * 4096;
constexpr int SC_RED  = SB_QB + 1024;
constexpr int SB_BAR  = SC_RED + 2560;
constexpr int SB_CNT  = SB_BAR + (12 + NT) * 8;
static_assert(SC_FR + 16384 <= SB_P && 2 * (32 - NSA) <= NT && 2 * (32 - NSB) <= NT && NSA <= 16 && NSB <= 16, "projection slots");
constexpr int SB_END  = SB_CNT + 64;
constexpr int SMEM_BYTES = (SA_END > SB_END ? SA_END : SB_END);
static_assert(SMEM_BYTES <= 232448, "shared memory");

struct Scratch {
    uint4    bpart[32 * 32 * (PROW / 16)];
    uint4    apart[64 * CPG * 32];
    uint4    qimg[2 * 4096];
    uint4    qpub[64 * 32];
    uint4    frag[2][64 * 32];
    uint2    snd[32 * 32];
    uint2    aml[64 * CPG * 4];
    unsigned epoch[128 * 8];
    unsigned ctr[1088];
    uint2    fire[544];
    unsigned qflag[1088], bflag[1088];
};
__device__ __align__(1024) Scratch g_scr;

#define TRARG
#define TRPASS
#define TR(k)
#define TROUT()

__device__ __forceinline__ uint32_t s2u(const void* p) { return (uint32_t)__cvta_generic_to_shared(p); }
__device__ __forceinline__ bool elect() {
    uint32_t ok;
    asm volatile("{\n.reg .pred p;\nelect.sync _|p, 0xffffffff;\nselp.u32 %0,1,0,p;\n}" : "=r"(ok));
    return ok;
}
__device__ __forceinline__ void mbar_init(uint32_t b, int c) {
    asm volatile("mbarrier.init.shared::cta.b64 [%0], %1;" ::"r"(b), "r"(c) : "memory");
}
__device__ __forceinline__ void mbar_init_fence() { asm volatile("fence.mbarrier_init.release.cluster;" ::: "memory"); }
__device__ __forceinline__ void mbar_expect(uint32_t b, uint32_t bytes) {
    asm volatile("mbarrier.arrive.expect_tx.shared::cta.b64 _, [%0], %1;" ::"r"(b), "r"(bytes) : "memory");
}
__device__ __forceinline__ void mbar_arrive(uint32_t b) {
    asm volatile("mbarrier.arrive.shared::cta.b64 _, [%0];" ::"r"(b) : "memory");
}
__device__ __forceinline__ bool mbar_test(uint32_t b, uint32_t ph) {
    uint32_t ok;
    asm volatile("{\n.reg .pred p;\nmbarrier.test_wait.parity.shared::cta.b64 p, [%1], %2;\nselp.u32 %0,1,0,p;\n}"
                 : "=r"(ok) : "r"(b), "r"(ph) : "memory");
    return ok;
}
__device__ __forceinline__ void mbar_wait(uint32_t b, uint32_t ph) {
    asm volatile("{\n.reg .pred p;\n.reg .u32 n;\nmov.u32 n, 0;\n"
                 "W: mbarrier.try_wait.parity.shared::cta.b64 p, [%0], %1;\n@p bra.uni D;\n"
                 "add.u32 n, n, 1;\nsetp.lt.u32 p, n, %2;\n@p bra.uni W;\ntrap;\nD:\n}"
                 ::"r"(b), "r"(ph), "n"(SPIN_MAX) : "memory");
}
__device__ __forceinline__ void tma2d(uint32_t dst, const CUtensorMap* map, int c0, int c1, uint32_t bar) {
    asm volatile("cp.async.bulk.tensor.2d.shared::cluster.global.mbarrier::complete_tx::bytes [%0], [%1, {%3, %4}], [%2];"
                 ::"r"(dst), "l"(map), "r"(bar), "r"(c0), "r"(c1) : "memory");
}
__device__ __forceinline__ void tma2d_ef(uint32_t dst, const CUtensorMap* map, int c0, int c1, uint32_t bar) {
    asm volatile("cp.async.bulk.tensor.2d.shared::cluster.global.mbarrier::complete_tx::bytes.L2::cache_hint [%0], [%1, {%3, %4}], [%2], %5;"
                 ::"r"(dst), "l"(map), "r"(bar), "r"(c0), "r"(c1), "l"(EVICT_FIRST) : "memory");
}
__device__ __forceinline__ void tma4d_ef(uint32_t dst, const CUtensorMap* map, int c3, uint32_t bar) {
    asm volatile("cp.async.bulk.tensor.4d.shared::cluster.global.mbarrier::complete_tx::bytes.L2::cache_hint [%0], [%1, {0, 0, 0, %3}], [%2], %4;"
                 ::"r"(dst), "l"(map), "r"(bar), "r"(c3), "l"(EVICT_FIRST) : "memory");
}
__device__ __forceinline__ void bulk_g2s(uint32_t dst, const void* src, uint32_t bytes, uint32_t bar) {
    asm volatile("cp.async.bulk.shared::cluster.global.mbarrier::complete_tx::bytes [%0], [%1], %2, [%3];"
                 ::"r"(dst), "l"(src), "r"(bytes), "r"(bar) : "memory");
}
__device__ __forceinline__ void bulk_s2g(void* dst, uint32_t src, uint32_t bytes) {
    asm volatile("cp.async.bulk.global.shared::cta.bulk_group [%0], [%1], %2;" ::"l"(dst), "r"(src), "r"(bytes) : "memory");
}
__device__ __forceinline__ void fence_async_all() { asm volatile("fence.proxy.async;" ::: "memory"); }
__device__ __forceinline__ void bar_sync(int id, int n) { asm volatile("bar.sync %0, %1;" ::"r"(id), "r"(n) : "memory"); }
__device__ __forceinline__ void bar_arrive(int id, int n) { asm volatile("bar.arrive %0, %1;" ::"r"(id), "r"(n) : "memory"); }
__device__ __forceinline__ unsigned ld_relaxed1(const void* p) {
    unsigned v;
    asm volatile("ld.relaxed.gpu.global.u32 %0, [%1];" : "=r"(v) : "l"(p) : "memory");
    return v;
}
__device__ __forceinline__ unsigned atom_inc(unsigned* p) {
    unsigned v;
    asm volatile("atom.relaxed.gpu.global.add.u32 %0, [%1], 1;" : "=r"(v) : "l"(p) : "memory");
    return v;
}
__device__ __forceinline__ uint4 ld_b128(const void* p) {
    uint4 v;
    asm volatile("{\n.reg .b128 t;\nld.relaxed.gpu.global.b128 t, [%4];\nmov.b128 {%0,%1,%2,%3}, t;\n}"
                 : "=r"(v.x), "=r"(v.y), "=r"(v.z), "=r"(v.w) : "l"(p) : "memory");
    return v;
}
__device__ __forceinline__ void st_b128(void* p, uint4 v) {
    asm volatile("{\n.reg .b128 t;\nmov.b128 t, {%1,%2,%3,%4};\nst.relaxed.gpu.global.b128 [%0], t;\n}"
                 ::"l"(p), "r"(v.x), "r"(v.y), "r"(v.z), "r"(v.w) : "memory");
}
__device__ __forceinline__ uint2 ld_b64(const void* p) {
    uint2 v;
    asm volatile("{\n.reg .b64 a;\nld.relaxed.gpu.global.b64 a, [%2];\nmov.b64 {%0,%1}, a;\n}" : "=r"(v.x), "=r"(v.y) : "l"(p) : "memory");
    return v;
}
__device__ __forceinline__ void st_b64(void* p, uint32_t a, uint32_t b) {
    asm volatile("{\n.reg .b64 t;\nmov.b64 t, {%1,%2};\nst.relaxed.gpu.global.b64 [%0], t;\n}" ::"l"(p), "r"(a), "r"(b) : "memory");
}
__device__ __forceinline__ unsigned ld_acquire(const unsigned* p) {
    unsigned v;
    asm volatile("ld.acquire.gpu.global.u32 %0, [%1];" : "=r"(v) : "l"(p) : "memory");
    return v;
}
__device__ __forceinline__ void st_release(unsigned* p, unsigned v) {
    asm volatile("st.release.gpu.global.u32 [%0], %1;" ::"l"(p), "r"(v) : "memory");
}
__device__ __forceinline__ void ldsm4(uint32_t (&r)[4], uint32_t a) {
    asm volatile("ldmatrix.sync.aligned.m8n8.x4.shared.b16 {%0,%1,%2,%3}, [%4];"
                 : "=r"(r[0]), "=r"(r[1]), "=r"(r[2]), "=r"(r[3]) : "r"(a) : "memory");
}
__device__ __forceinline__ void ldsm4t(uint32_t (&r)[4], uint32_t a) {
    asm volatile("ldmatrix.sync.aligned.m8n8.x4.trans.shared.b16 {%0,%1,%2,%3}, [%4];"
                 : "=r"(r[0]), "=r"(r[1]), "=r"(r[2]), "=r"(r[3]) : "r"(a) : "memory");
}
__device__ __forceinline__ uint4 lds128(uint32_t a) {
    uint4 v;
    asm volatile("ld.shared.v4.u32 {%0, %1, %2, %3}, [%4];" : "=r"(v.x), "=r"(v.y), "=r"(v.z), "=r"(v.w) : "r"(a) : "memory");
    return v;
}
__device__ __forceinline__ uint32_t lds32(uint32_t a) {
    uint32_t v;
    asm volatile("ld.shared.u32 %0, [%1];" : "=r"(v) : "r"(a) : "memory");
    return v;
}
__device__ __forceinline__ void sts32(uint32_t a, uint32_t v) { asm volatile("st.shared.u32 [%0], %1;" ::"r"(a), "r"(v) : "memory"); }
__device__ __forceinline__ void mma16816(float (&d)[4], const uint32_t (&a)[4], uint32_t b0, uint32_t b1) {
    asm volatile("mma.sync.aligned.m16n8k16.row.col.f32.bf16.bf16.f32 {%0,%1,%2,%3}, {%4,%5,%6,%7}, {%8,%9}, {%0,%1,%2,%3};"
                 : "+f"(d[0]), "+f"(d[1]), "+f"(d[2]), "+f"(d[3])
                 : "r"(a[0]), "r"(a[1]), "r"(a[2]), "r"(a[3]), "r"(b0), "r"(b1));
}
__device__ __forceinline__ uint32_t prmt0(uint32_t a, uint32_t sel) {
    uint32_t d;
    asm volatile("prmt.b32 %0, %1, 0, %2;" : "=r"(d) : "r"(a), "r"(sel));
    return d;
}
__device__ __forceinline__ unsigned gt() {
    unsigned t;
    asm volatile("mov.u32 %0, %globaltimer_lo;" : "=r"(t));
    return t;
}
__device__ __forceinline__ unsigned clk32() {
    unsigned c;
    asm volatile("mov.u32 %0, %clock;" : "=r"(c));
    return c;
}
__device__ __forceinline__ float ex2(float x) {
    float y;
    asm("ex2.approx.ftz.f32 %0, %1;" : "=f"(y) : "f"(x));
    return y;
}
__device__ __forceinline__ float bf16r(float x) { return __bfloat162float(__float2bfloat16_rn(x)); }
__device__ __forceinline__ uint32_t packbf(float lo, float hi) {
    uint32_t r;
    asm("cvt.rn.bf16x2.f32 %0, %1, %2;" : "=r"(r) : "f"(hi), "f"(lo));
    return r;
}
__device__ __forceinline__ float bflo(uint32_t v) { return __uint_as_float(v << 16); }
__device__ __forceinline__ float bfhi(uint32_t v) { return __uint_as_float(v & 0xffff0000u); }
__device__ __forceinline__ uint32_t tagf(float v, uint32_t t8) { return (__float_as_uint(v) & 0xffffff00u) | t8; }
__device__ __forceinline__ float shx(float v, int m) { return __shfl_xor_sync(0xffffffffu, v, m); }

__device__ __forceinline__ float warp_max(float v) {
    int i = __float_as_int(v);
    i = __reduce_max_sync(0xffffffffu, i ^ ((i >> 31) & 0x7fffffff));
    return __int_as_float(i ^ ((i >> 31) & 0x7fffffff));
}

__device__ __forceinline__ uint64_t gdesc(uint32_t addr, uint32_t lbo, uint32_t sbo) {
    return (uint64_t)((addr & 0x3ffff) >> 4) | ((uint64_t)(lbo >> 4) << 16) | ((uint64_t)(sbo >> 4) << 32) | (1ull << 62);
}
__device__ __forceinline__ void wg_fence() { asm volatile("wgmma.fence.sync.aligned;" ::: "memory"); }
__device__ __forceinline__ void wg_commit() { asm volatile("wgmma.commit_group.sync.aligned;" ::: "memory"); }
__device__ __forceinline__ void wg_wait0() { asm volatile("wgmma.wait_group.sync.aligned 0;" ::: "memory"); }
template <int N> __device__ __forceinline__ void reg_fence(float (&r)[N]) {
#pragma unroll
    for (int i = 0; i < N; i++) asm volatile("" : "+f"(r[i])::"memory");
}
#define F8(a, o) "+f"(a[o]), "+f"(a[o + 1]), "+f"(a[o + 2]), "+f"(a[o + 3]), "+f"(a[o + 4]), "+f"(a[o + 5]), "+f"(a[o + 6]), "+f"(a[o + 7])
#define F32(a, o) F8(a, o), F8(a, o + 8), F8(a, o + 16), F8(a, o + 24)
__device__ __forceinline__ void wgmma_n64_ss(float (&d)[32], uint64_t da, uint64_t db, int scale_d) {
    asm volatile(
        "{\n.reg .pred p;\nsetp.ne.b32 p, %34, 0;\n"
        "wgmma.mma_async.sync.aligned.m64n64k16.f32.bf16.bf16 "
        "{%0,%1,%2,%3,%4,%5,%6,%7,%8,%9,%10,%11,%12,%13,%14,%15,%16,%17,%18,%19,%20,%21,%22,%23,%24,%25,%26,%27,%28,%29,%30,%31},"
        " %32, %33, p, 1, 1, 0, 0;\n}"
        : F32(d, 0) : "l"(da), "l"(db), "r"(scale_d));
}
__device__ __forceinline__ void wgmma_n32_ts(float (&d)[16], uint64_t da, uint64_t db) {
    asm volatile(
        "{\n.reg .pred p;\nsetp.ne.b32 p, 1, 0;\n"
        "wgmma.mma_async.sync.aligned.m64n32k16.f32.bf16.bf16 "
        "{%0,%1,%2,%3,%4,%5,%6,%7,%8,%9,%10,%11,%12,%13,%14,%15}, %16, %17, p, 1, 1, 1, 0;\n}"
        : F8(d, 0), F8(d, 8) : "l"(da), "l"(db));
}

struct Params {
    Scratch* scr;
    const uint32_t *ax, *bx;
    const char* wq;
    __nv_bfloat16* out;
};
struct Maps { CUtensorMap kv[2], qa, qb, wo[2], c, uk, uv; };

__device__ __forceinline__ void wait_flags(const unsigned* flags, unsigned tag, int lane) {
    for (int i = 0; !__all_sync(0xffffffffu, ld_acquire(flags + lane) == tag); i++) {
        if (i > SPIN_MAX) __trap();
        __nanosleep(BPOLL);
    }
}
__device__ __forceinline__ void load_slice(uint32_t dst, const CUtensorMap* map, int r, uint32_t bar) {
    mbar_expect(bar, 131072);
#pragma unroll
    for (int x = 0; x < 4; x++) tma2d(dst + x * 32768, map, r * 128 + (x & 1) * 64, (x >> 1) * 256, bar);
}
__device__ __forceinline__ void gemv_slice(uint32_t sb, int warp, int lane) {
    const int g = lane >> 2, tq = lane & 3;
    float d[4][4];
#pragma unroll
    for (int i = 0; i < 4; i++) d[i][0] = d[i][1] = d[i][2] = d[i][3] = 0.f;
    const uint32_t wb = sb + SB_STG + (warp >> 2) * 32768 + ((lane & 7) + 8 * (lane >> 4)) * 128 +
                        (((2 * (warp & 3) + ((lane >> 3) & 1)) ^ (lane & 7)) << 4);
    const uint32_t xb = sb + SB_X + ((g & 3) * 264 + tq) * 4;
#pragma unroll 1
    for (int k8 = 0; k8 < 4; k8++) {
        uint32_t a[8][4], b[8][2];
#pragma unroll
        for (int ks = 0; ks < 8; ks++) {
            ldsm4t(a[ks], wb + (k8 >> 1) * 65536 + (k8 & 1) * 16384 + ks * 2048);
            b[ks][0] = lds32(xb + k8 * 256 + ks * 32);
            b[ks][1] = lds32(xb + k8 * 256 + ks * 32 + 16);
        }
#pragma unroll
        for (int ks = 0; ks < 8; ks++) mma16816(d[ks & 3], a[ks], b[ks][0], b[ks][1]);
    }
    const float y0 = ((d[0][0] + d[1][0]) + (d[2][0] + d[3][0])) + ((d[0][1] + d[1][1]) + (d[2][1] + d[3][1]));
    const float y1 = ((d[0][2] + d[1][2]) + (d[2][2] + d[3][2])) + ((d[0][3] + d[1][3]) + (d[2][3] + d[3][3]));
    if (tq < 2) {
        sts32(sb + SB_QB + (tq * 128 + warp * 16 + g) * 4, __float_as_uint(y0));
        sts32(sb + SB_QB + (tq * 128 + warp * 16 + 8 + g) * 4, __float_as_uint(y1));
    }
}
__device__ __forceinline__ uint32_t wo_lane(uint32_t sb, int lane) {
    return sb + ((lane & 7) + 8 * (lane >> 4)) * 64 + ((((lane >> 3) & 1) ^ ((lane >> 1) & 3)) << 4);
}

__device__ __forceinline__ void latent_branch(const Params& P, const Maps& M, uint8_t* sm TRARG) {
    const uint32_t sb = s2u(sm);
    const int tid = threadIdx.x, lane = tid & 31, warp = tid >> 5, g = lane >> 2, tq = lane & 3, r = blockIdx.x >> 2;
    const uint32_t bar_w = sb + SB_BAR + 16, bar_x = sb + SB_BAR + 24;
    const unsigned tag = lds32(sb + SB_CNT) + 1;
    Scratch* const S = P.scr;
    const float* yb = reinterpret_cast<const float*>(sm + SB_QB);
    {
        float* xs = reinterpret_cast<float*>(sm + SB_X);
        const int crow0 = (r >> 4) * 8192 + (r & 15) * 64;
        {
            if (tid == 32) {
                __nanosleep(BDELAY);
                load_slice(sb + SB_STG, &M.qb, r, bar_w);
            }
            uint32_t* xh = reinterpret_cast<uint32_t*>(sm + SB_X) + tid;
            xh[0] = __ldg(P.bx + tid); xh[264] = 0; xh[528] = __ldg(P.bx + 256 + tid); xh[792] = 0;
            bar_sync(0, 256);
            mbar_wait(bar_w, 0);
            TR(0);
            gemv_slice(sb, warp, lane);
            bar_sync(0, 256);
            if (tid == 0) load_slice(sb + SB_STG, &M.uk, r, bar_w);
            uint32_t qb[8][2];
#pragma unroll
            for (int ks = 0; ks < 8; ks++) {
                const float2 a = *reinterpret_cast<const float2*>(yb + (g & 1) * 128 + ks * 16 + 2 * tq);
                const float2 b = *reinterpret_cast<const float2*>(yb + (g & 1) * 128 + ks * 16 + 8 + 2 * tq);
                qb[ks][0] = packbf(a.x, a.y);
                qb[ks][1] = packbf(b.x, b.y);
            }
            mbar_wait(bar_w, 1);
            const uint32_t wb = sb + SB_STG + (warp >> 2) * 65536 + ((warp & 3) * 64 + (lane & 15)) * 128;
#pragma unroll 1
            for (int mt = 0; mt < 4; mt++) {
                float d[4] = {0.f, 0.f, 0.f, 0.f};
#pragma unroll
                for (int ks = 0; ks < 8; ks++) {
                    uint32_t a[4];
                    ldsm4(a, wb + (ks >> 2) * 32768 + mt * 2048 + (((2 * (ks & 3) + (lane >> 4)) ^ (lane & 7)) << 4));
                    mma16816(d, a, qb[ks][0], qb[ks][1]);
                }
                if (tq == 0) {
                    const int c = warp * 64 + mt * 16 + g;
                    xs[c] = d[0]; xs[512 + c] = d[1]; xs[c + 8] = d[2]; xs[512 + c + 8] = d[3];
                }
            }
            bar_sync(0, 256);
            if (tid == 32) {
#pragma unroll
                for (int t = 0; t < 2; t++) {
                    mbar_expect(sb + SB_BAR + t * 8, 65536);
                    tma4d_ef(sb + SB_STG + t * 65536, &M.c, (crow0 >> 3) + t * 128, sb + SB_BAR + t * 8);
                }
            }
            const int b = tid >> 7, lo = (tid >> 6) & 1, ch = tid & 63;
            float v[8];
#pragma unroll
            for (int i = 0; i < 8; i++) {
                const float x = xs[b * 512 + ch * 8 + i];
                v[i] = lo ? x - bf16r(x) : x;
            }
            const int row = 16 * (r >> 3) + (r & 7) + 8 * lo;
            S->qimg[b * 4096 + (ch >> 3) * 512 + row * 8 + ((ch & 7) ^ (r & 7))] =
                make_uint4(packbf(v[0], v[1]), packbf(v[2], v[3]), packbf(v[4], v[5]), packbf(v[6], v[7]));
            bar_sync(0, 256);
            if (warp == 0) {
                if (lane == 0) { __threadfence(); st_release(S->qflag + r, tag); }
                wait_flags(S->qflag, tag, lane);
                if (lane == 0) {
                    fence_async_all();
                    mbar_expect(bar_x, 65536);
                    bulk_g2s(sb + SB_QIMG, S->qimg + (r >> 4) * 4096, 65536, bar_x);
                }
            }
            mbar_wait(bar_x, 0);
        }
        TR(1);
        {
            const int wg = warp >> 2;
            float acc[4][16];
#pragma unroll
            for (int i = 0; i < 64; i++) acc[i >> 4][i & 15] = 0.f;
            const int head = (warp & 3) * 8 + g;
            const uint32_t pa = sb + SB_P + wg * 4096;
            float* al = reinterpret_cast<float*>(sm + SB_AL) + wg * 32;
            float m = -FLT_MAX, l = 0.f;
#pragma unroll 1
            for (int t = 0; t < 8; t++) {
                const uint32_t stg = sb + SB_STG + (t & 1) * 65536;
                mbar_wait(sb + SB_BAR + (t & 1) * 8, (t >> 1) & 1);
                float s[32];
                uint32_t qa = sb + SB_QIMG;
                asm volatile("" : "+r"(qa));
                wg_fence();
#pragma unroll
                for (int k = 0; k < 32; k++) {
                    const uint32_t off = (k >> 2) * 8192 + (k & 3) * 32;
                    wgmma_n64_ss(s, gdesc(qa + off, 16, 1024), gdesc(stg + (k >> 2) * 1024 + (k & 3) * 32, 16, 8192), k > 0);
                }
                wg_commit();
                wg_wait0();
                reg_fence(s);
                float p[16], mx = m;
#pragma unroll
                for (int i = 0; i < 8; i++) {
                    p[2 * i] = bf16r(bf16r(s[4 * i] + s[4 * i + 2]) * SCALE);
                    p[2 * i + 1] = bf16r(bf16r(s[4 * i + 1] + s[4 * i + 3]) * SCALE);
                    mx = fmaxf(mx, fmaxf(p[2 * i], p[2 * i + 1]));
                }
                mx = fmaxf(mx, shx(mx, 1));
                mx = fmaxf(mx, shx(mx, 2));
                const float alpha = ex2((m - mx) * LOG2E);
                m = mx;
                float sum = 0.f;
#pragma unroll
                for (int i = 0; i < 8; i++) {
                    const float a = ex2((p[2 * i] - mx) * LOG2E), b = ex2((p[2 * i + 1] - mx) * LOG2E);
                    sum += a + b;
                    sts32(pa + head * 128 + ((i ^ g) << 4) + tq * 4, packbf(a, b));
                }
                l = fmaf(l, alpha, sum);
                if (tq == 0) al[head] = alpha;
                asm volatile("fence.proxy.async.shared::cta;" ::: "memory");
                bar_sync(1 + wg, 128);
#pragma unroll
                for (int j = 0; j < 4; j++) {
                    const float2 a = *reinterpret_cast<const float2*>(al + 8 * j + 2 * tq);
#pragma unroll
                    for (int i = 0; i < 4; i++) { acc[i][4 * j] *= a.x; acc[i][4 * j + 1] *= a.y; acc[i][4 * j + 2] *= a.x; acc[i][4 * j + 3] *= a.y; }
                }
#pragma unroll
                for (int i = 0; i < 4; i++) reg_fence(acc[i]);
                wg_fence();
#pragma unroll
                for (int kk = 0; kk < 4; kk++)
#pragma unroll
                    for (int i = 0; i < 4; i++)
                        wgmma_n32_ts(acc[i], gdesc(stg + (wg * 4 + i) * 1024 + kk * 16384, 1024, 8192), gdesc(pa + kk * 32, 16, 1024));
                wg_commit();
                wg_wait0();
#pragma unroll
                for (int i = 0; i < 4; i++) reg_fence(acc[i]);
                bar_sync(0, 256);
                if (tid == 0) {
                    if (t + 2 < 8) {
                        const uint32_t bar = sb + SB_BAR + (t & 1) * 8;
                        mbar_expect(bar, 65536);
                        tma4d_ef(stg, &M.c, (crow0 >> 3) + (t + 2) * 128, bar);
                    }
                    if (t == 7) load_slice(sb + SB_STG, &M.uv, r, bar_w);
                }
            }
            TR(2);
            float* dst = reinterpret_cast<float*>(sm + SB_QIMG + 2 * tq * PROW) + wg * 256 + (warp & 3) * 16 + g;
#pragma unroll
            for (int i = 0; i < 64; i++)
                dst[(((i >> 2) & 3) * 8 + (i & 1)) * (PROW / 4) + (i >> 4) * 64 + (i & 2) * 4] = acc[i >> 4][i & 15];
            l += shx(l, 1); l += shx(l, 2);
            if (wg == 0 && tq < 2) *reinterpret_cast<float4*>(sm + SB_QIMG + head * PROW + 2048 + tq * 16) = make_float4(m, l, 0.f, 0.f);
            asm volatile("fence.proxy.async.shared::cta;" ::: "memory");
            bar_sync(0, 256);
            if (warp == 0) {
                bulk_s2g(S->bpart + (lane * 32 + r) * (PROW / 16), sb + SB_QIMG + lane * PROW, PROW);
                asm volatile("cp.async.bulk.commit_group;" ::: "memory");
                asm volatile("cp.async.bulk.wait_group 0;" ::: "memory");
                fence_async_all();
                __threadfence();
                __syncwarp();
                if (lane == 0) st_release(S->bflag + r, tag);
                wait_flags(S->bflag, tag, lane);
                if (lane == 0) {
                    fence_async_all();
                    mbar_expect(bar_x, 32 * PROW);
                    bulk_g2s(sb + SB_QIMG, S->bpart + r * 32 * (PROW / 16), 32 * PROW, bar_x);
                }
            }
        }
        {
            const int b = tid >> 7, c4 = tid & 127;
            mbar_wait(bar_x, 1);
            TR(3);
            const float2 ml = *reinterpret_cast<const float2*>(sm + SB_QIMG + (b * 16 + (lane & 15)) * PROW + 2048);
            float MM = ml.x;
            MM = fmaxf(MM, shx(MM, 1)); MM = fmaxf(MM, shx(MM, 2)); MM = fmaxf(MM, shx(MM, 4)); MM = fmaxf(MM, shx(MM, 8));
            const float e = ex2((ml.x - MM) * LOG2E);
            float L = e * ml.y;
            L += shx(L, 1); L += shx(L, 2); L += shx(L, 4); L += shx(L, 8);
            const float wgt = e / L;
            float4 o = make_float4(0.f, 0.f, 0.f, 0.f);
#pragma unroll 4
            for (int i = 0; i < 16; i++) {
                const float w = __shfl_sync(0xffffffffu, wgt, i);
                const float4 v = *reinterpret_cast<const float4*>(sm + SB_QIMG + (b * 16 + i) * PROW + c4 * 16);
                o.x = fmaf(w, v.x, o.x); o.y = fmaf(w, v.y, o.y); o.z = fmaf(w, v.z, o.z); o.w = fmaf(w, v.w, o.w);
            }
            uint32_t* xh = reinterpret_cast<uint32_t*>(xs);
            const uint32_t h0 = packbf(o.x, o.y), h1 = packbf(o.z, o.w);
            *reinterpret_cast<uint2*>(xh + (2 * b) * 264 + c4 * 2) = make_uint2(h0, h1);
            *reinterpret_cast<uint2*>(xh + (2 * b + 1) * 264 + c4 * 2) =
                make_uint2(packbf(o.x - bflo(h0), o.y - bfhi(h0)), packbf(o.z - bflo(h1), o.w - bfhi(h1)));
            bar_sync(0, 256);
            mbar_wait(bar_w, 0);
            gemv_slice(sb, warp, lane);
            bar_sync(0, 256);
            if (tid < 64) {
                const float* y = yb + warp * 128 + 16 * g + 2 * tq;
                st_b128(S->frag[0] + (warp * 32 + r) * 32 + lane, make_uint4(packbf(y[0], y[1]), tag, packbf(y[8], y[9]), tag));
            }
        }
        TR(4);
    }
}

__global__ void __launch_bounds__(384, 1)
fused_decode_kernel(const Params P, const __grid_constant__ Maps M) {
    extern __shared__ __align__(1024) uint8_t sm[];
    const uint32_t sb = s2u(sm);
    const int tid = threadIdx.x, lane = tid & 31, bx = blockIdx.x;
    asm volatile("{\n.reg .pred p;\nsetp.lt.u32 p, %1, 256;\n@p prefetch.global.L2 [%0];\n}"
                 ::"l"(P.wq + (unsigned)(bx * 32768 + tid * 128)), "r"(tid) : "memory");
    const int warp = __shfl_sync(0xffffffffu, tid >> 5, 0);
    const int g = lane >> 2, tq = lane & 3;
    Scratch* const S = P.scr;

    if (!(bx & 1)) {
        const int grp = (bx >> 1) & 7, crk = bx >> 4;
        const int rowbase = grp * (UPG * 64);
        auto issue = [&](int slot, unsigned tk, int v) {
            const int row = rowbase + (int)((tk & ~255u) | ((tk + grp * ROT) & 255u)) * 64;
            const uint32_t full = sb + SA_FULL + slot * 16 + v * 8;
            mbar_expect(full, 8192);
            tma2d_ef(sb + slot * 16384 + v * 8192, &M.kv[v], 0, row, full);
        };
        if (warp >= 8) {
            const int w = warp - 8;
            const bool one = elect();
            if (one) {
                mbar_init(sb + SA_FULL + w * 16, 1);
                mbar_init_fence();
                TR(3);
                sts32(sb + SA_META + w * 4, 0);
                if (w < SKEW) issue(w, w * CPG + crk, 0);
#pragma unroll
                for (int i = 0; i < SPW; i++) {
                    if (i) mbar_init(sb + SA_FULL + (w + i * NW) * 16, 1);
                    mbar_init(sb + SA_FULL + (w + i * NW) * 16 + 8, 1);
                    mbar_init(sb + SA_GOV + (w + i * NW) * 8, 1);
                    mbar_init(sb + SA_EMPTY + (w + i * NW) * 8, 2);
                    mbar_arrive(sb + SA_EMPTY + (w + i * NW) * 8);
                }
                if (w < SKEW) mbar_arrive(sb + SA_EMPTY + w * 8);
                sts32(sb + SA_LIM + w * 4, LIM);
                mbar_init_fence();
            }
            __syncwarp();
            bar_arrive(2, (NW + 1) * 32);
            bar_arrive(1, (2 * NW + 1) * 32);
            unsigned c = 0, tbase = 0;
            int slot = w;
            uint32_t eph = 0;
#pragma unroll 1
            for (int n = 0;; n++) {
                unsigned tk = (n * NW + w) * CPG + crk;
                if (n == SPW) {
                    mbar_wait(sb + SA_EMPTY + w * 8, 1);
                    tbase = NSL * CPG - lds32(sb + SA_CNT + 32) * TICK_INC;
                }
                if (n >= SPW) {
                    const unsigned own = __shfl_sync(0xffffffffu, c, grp);
                    tk = own + tbase;
                    const int lag = (int)(__reduce_add_sync(0xffffffffu, c) - NG * own);
                    if (one) sts32(sb + SA_LIM + w * 4, lag > BAL * NG ? LIM + 1 : lag < -BAL * NG ? LIM - 1 : LIM);
                }
                mbar_wait(sb + SA_EMPTY + slot * 8, eph);
                if (tk >= UPG) {
                    if (one) { sts32(sb + SA_LIM + w * 4, 0); sts32(sb + SA_META + slot * 4, 8); mbar_arrive(sb + SA_FULL + slot * 16); }
                    return;
                }
                if (one && (n || w >= SKEW)) {
                    sts32(sb + SA_META + slot * 4, tk >> 8);
                    issue(slot, tk, 0);
                    if (tk == 300) TR(6);
                    if (tk == UPG - FIRE_T) { st_b64(S->fire + grp, gt(), lds32(sb + SA_CNT + 32) + 1); TR(4); }
                }
                if (n >= SPW - 1) {
                    if (lane == grp) c = atom_inc(S->ctr + lane);
                    else if (lane < NG) c = ld_relaxed1(S->ctr + lane);
                }
                mbar_wait(sb + SA_GOV + slot * 8, eph);
                if (one) issue(slot, tk, 1);
                TR(0);
                slot += NW;
                if (slot >= NSL) { slot -= NSL; eph ^= 1; }
                __syncwarp();
            }
        }
        if (warp == 0) {
            bool busy = lane < 2 * SKEW && !(lane & 1);
            uint32_t par = busy ? 0 : 1;
            int slot = SKEW;
            bool first = true;
            const unsigned c0 = clk32() + RAMP_T0;
            const int own = lane >= 2 * NSL ? -1 : ((lane >> 1) + (lane & 1) * SKEW) % NSL;
            const uint32_t fb = sb + SA_FULL + lane * 8, lw = sb + SA_LIM + ((lane >> 1) % NW) * 4;
            const uint32_t go = sb + ((lane & 1) ? SA_GOV : SA_EMPTY) + (lane >> 1) * 8;
            bar_sync(2, (NW + 1) * 32);
#pragma unroll 1
            for (int it = 0; it < SPIN_MAX; it++) {
                bool ok = true;
                if (busy) ok = mbar_test(fb, par);
                int lim = lds32(lw);
                if (first) lim = min(LIM0, SKEW + max((int)(clk32() - c0), 0) / RAMP_S);
                busy = busy && !ok && lim;
                const int n = __popc(__ballot_sync(0xffffffffu, busy));
                if (!__any_sync(0xffffffffu, lim)) return;
                const bool mine = own == slot && lim;
                if (!__any_sync(0xffffffffu, mine && (busy || n > lim - 2))) {
                    if (mine) { mbar_arrive(go); busy = true; par ^= 1; }
                    if (++slot == NSL) { slot = 0; first = false; }
                    it = 0;
                }
            }
            __trap();
        }
        if (warp == 2 || warp == 3) return;
        auto fetch_q = [&](int pl, unsigned tag) {
            uint4 v;
            for (int it = 0;; it++) {
                v = ld_b128(S->qpub + (grp * 8 + pl) * 32 + lane);
                if (__all_sync(0xffffffffu, v.y == tag)) break;
                if (it > SPIN_MAX) __trap();
            }
            *reinterpret_cast<uint2*>(sm + SA_Q + pl * 256 + lane * 8) = make_uint2(v.x, v.z);
        };
        if (warp == 1) {
            const unsigned epoch = ld_relaxed1(S->epoch + bx * 8);
            if (lane == 0) { mbar_init(sb + SA_QBAR, 32); mbar_init_fence(); }
            if (lane < 9) sts32(sb + SA_CNT + lane * 4, lane < 8 ? 0u : epoch);
            bar_arrive(1, (2 * NW + 1) * 32);
            if (lane == 0) S->epoch[bx * 8] = epoch + 1;
            __nanosleep(3000);
#pragma unroll 1
            for (int pl = 1; pl < 8; pl++) fetch_q(pl, epoch + 1);
            mbar_arrive(sb + SA_QBAR);
            return;
        }
        const int cw = warp - 4;
        bar_sync(1, (2 * NW + 1) * 32);
        const unsigned tag = lds32(sb + SA_CNT + 32) + 1;
        __nanosleep(QSLEEP);
        fetch_q(0, tag);
        __syncwarp();
        TR(0);

        const uint32_t t8 = tag & 0xffu;
        uint32_t koff[4], voff[4];
#pragma unroll
        for (int i = 0; i < 4; i++) {
            koff[i] = ((lane & 7) + 8 * ((lane >> 3) & 1)) * 128 + (((2 * i + (lane >> 4)) ^ (lane & 7)) << 4);
            voff[i] = ((lane & 7) + 8 * (lane >> 4)) * 128 + (((2 * i + ((lane >> 3) & 1)) ^ (lane & 7)) << 4);
        }
        uint32_t psel[4][2];
#pragma unroll
        for (int i = 0; i < 4; i++) {
            psel[i][0] = (g >> 1) != i ? 0x4444u : (g & 1) ? 0x1044u : 0x4410u;
            psel[i][1] = (g >> 1) != i ? 0x4444u : (g & 1) ? 0x3244u : 0x4432u;
        }
        uint32_t qf[4][2];
        auto load_q = [&](int pl) {
            const uint32_t q = sb + SA_Q + pl * 256 + ((g & 1) * 32 + tq) * 4;
#pragma unroll
            for (int ks = 0; ks < 4; ks++) { qf[ks][0] = lds32(q + ks * 32); qf[ks][1] = lds32(q + ks * 32 + 16); }
        };
        load_q(0);
        float acc[4][4], m = -FLT_MAX, l = 0.f, ls = 0.f;
#pragma unroll
        for (int i = 0; i < 4; i++) acc[i][0] = acc[i][1] = acc[i][2] = acc[i][3] = 0.f;
        int slot = cw, cur = 0;
        uint32_t ph = 0;
#pragma unroll 1
        for (;;) {
            mbar_wait(sb + SA_FULL + slot * 16, ph);
            const int pl = lds32(sb + SA_META + slot * 4);
            if (pl != cur) {
#pragma unroll 1
            for (; cur != pl; cur++) {
                float* s0 = reinterpret_cast<float*>(sm + SA_SLOT) + cur * (NW * 132);
                float* sw = s0 + cw * 132 + tq * 16 + (g >> 1) * 4 + (g & 1);
                sw[0] = (acc[0][0] + acc[1][0]) + (acc[2][0] + acc[3][0]);
                sw[2] = (acc[0][2] + acc[1][2]) + (acc[2][2] + acc[3][2]);
                sw[64] = (acc[0][1] + acc[1][1]) + (acc[2][1] + acc[3][1]);
                sw[66] = (acc[0][3] + acc[1][3]) + (acc[2][3] + acc[3][3]);
                if (lane == 0) *reinterpret_cast<float2*>(s0 + cw * 132 + 128) = make_float2(m, ls);
                __syncwarp();
                int old = 0;
                if (lane == 0) asm volatile("atom.acq_rel.cta.shared.inc.u32 %0, [%1], 255;" : "=r"(old) : "r"(sb + SA_CNT + cur * 4) : "memory");
                if (__shfl_sync(0xffffffffu, old, 0) == NW - 1) {
                    float2 ml[NW];
                    float4 v[NW];
#pragma unroll
                    for (int w = 0; w < NW; w++) {
                        ml[w] = *reinterpret_cast<const float2*>(s0 + w * 132 + 128);
                        v[w] = *reinterpret_cast<const float4*>(s0 + w * 132 + lane * 4);
                    }
                    float MM = ml[0].x;
#pragma unroll
                    for (int w = 1; w < NW; w++) MM = fmaxf(MM, ml[w].x);
                    float4 o = make_float4(0.f, 0.f, 0.f, 0.f);
                    float L = 0.f;
#pragma unroll
                    for (int w = 0; w < NW; w++) {
                        const float e = ex2((ml[w].x - MM) * LOG2E);
                        o.x = fmaf(e, v[w].x, o.x); o.y = fmaf(e, v[w].y, o.y); o.z = fmaf(e, v[w].z, o.z); o.w = fmaf(e, v[w].w, o.w);
                        L = fmaf(e, ml[w].y, L);
                    }
                    const int rec = (grp * 8 + cur) * CPG + crk;
                    st_b128(S->apart + rec * 32 + lane, make_uint4(tagf(o.x, t8), __float_as_uint(o.y), __float_as_uint(o.z), __float_as_uint(o.w)));
                    if (lane < 4) st_b64(S->aml + rec * 4 + lane, __float_as_uint(MM), tagf(L, t8));
                    if (PLACE && cur == 6) {
                        st_b128(S->apart + (rec + CPG) * 32 + lane, make_uint4(t8 ^ 0x80u, 0, 0, 0));
                        if (lane < 4) st_b64(S->aml + (rec + CPG) * 4 + lane, 0, t8 ^ 0x80u);
                    }
                    TR(2);
                }
#pragma unroll
                for (int i = 0; i < 4; i++) acc[i][0] = acc[i][1] = acc[i][2] = acc[i][3] = 0.f;
                m = -FLT_MAX; l = ls = 0.f;
            }
                if (pl == 8) break;
                mbar_wait(sb + SA_QBAR, 0);
                load_q(pl);
            }
            float s4[4][4];
            const uint32_t kb = sb + slot * 16384;
#pragma unroll
            for (int j = 0; j < 4; j++) {
                s4[j][0] = s4[j][1] = s4[j][2] = s4[j][3] = 0.f;
                const bool on = (g >> 1) == j;
#pragma unroll
                for (int ks = 0; ks < 4; ks++) {
                    uint32_t a[4];
                    ldsm4(a, kb + j * 2048 + koff[ks]);
                    mma16816(s4[j], a, on ? qf[ks][0] : 0u, on ? qf[ks][1] : 0u);
                }
            }
            float d[4];
#pragma unroll
            for (int r = 0; r < 4; r++) d[r] = (s4[0][r] + s4[1][r]) + (s4[2][r] + s4[3][r]);
            float sa = (g & 1) ? d[1] : d[0], sc = (g & 1) ? d[3] : d[2];
            sa += shx(sa, 4); sc += shx(sc, 4);
            uint32_t sp = packbf(sa, sc);
            sp = packbf(bflo(sp) * SCALE, bfhi(sp) * SCALE);
            sa = bflo(sp); sc = bfhi(sp);
            const float mx = warp_max(fmaxf(fmaxf(sa, sc), m));
            const float alpha = ex2((m - mx) * LOG2E);
            m = mx;
            const float pa = ex2((sa - mx) * LOG2E), pc = ex2((sc - mx) * LOG2E);
            const uint32_t pk = packbf(pa, pc);
            uint32_t pb[4][4][2];
#pragma unroll
            for (int j = 0; j < 4; j++) {
                const uint32_t pj = __shfl_sync(0xffffffffu, pk, 8 * tq + j);
#pragma unroll
                for (int i = 0; i < 4; i++) { pb[j][i][0] = prmt0(pj, psel[i][0]); pb[j][i][1] = prmt0(pj, psel[i][1]); }
            }
            l = fmaf(l, alpha, pa + pc);
            ls = l + shx(l, 8);
#pragma unroll
            for (int i = 0; i < 4; i++) { acc[i][0] *= alpha; acc[i][1] *= alpha; acc[i][2] *= alpha; acc[i][3] *= alpha; }
            mbar_wait(sb + SA_FULL + slot * 16 + 8, ph);
            TR(1);
            const uint32_t vb = kb + 8192;
#pragma unroll
            for (int i = 0; i < 4; i++)
#pragma unroll
                for (int j = 0; j < 4; j++) {
                    uint32_t a[4];
                    ldsm4t(a, vb + j * 2048 + voff[i]);
                    mma16816(acc[j], a, pb[j][i][0], pb[j][i][1]);
                }
            ls += shx(ls, 16); ls += shx(ls, 1); ls += shx(ls, 2);
            __syncwarp();
            if (lane == 0) mbar_arrive(sb + SA_EMPTY + slot * 8);
            slot += NW;
            if (slot >= NSL) { slot -= NSL; ph ^= 1; }
        }
        TROUT();
        return;
    }

    const int r = bx >> 2, isC = (bx >> 1) & 1;
    const uint32_t bar_h = sb + SB_BAR + 32;
    if (warp < 8) {
    {
        const uint32_t bar_q = bar_h + (NT + warp) * 8, box = sb + SB_QIMG + warp * 8192;
        if (elect()) {
            mbar_init(bar_q, 1);
            mbar_init_fence();
            mbar_expect(bar_q, 8192 + 256);
            tma2d(box, &M.qa, (bx >> 1) * 64, warp * 64, bar_q);
            bulk_g2s(sb + SB_P + 4096 + warp * 288, P.ax + warp * 32, 128, bar_q);
            bulk_g2s(sb + SB_P + 4096 + warp * 288 + 144, P.ax + 256 + warp * 32, 128, bar_q);
        }
        unsigned epoch = 0;
        if (warp < 2) epoch = ld_relaxed1(S->epoch + bx * 8);
        uint4* const qdst = S->qpub + ((lane >> 4) * 32 + r) * 32 + isC * 16 + (lane & 15);
        if (PLACE && warp == 0) st_b128(qdst, make_uint4(0, 0, 0, 0));
        if (tid == 32) {
#pragma unroll
            for (int i = 0; i < 4 + NT; i++) mbar_init(sb + SB_BAR + i * 8, 1);
            mbar_init_fence();
            sts32(sb + SB_CNT, epoch);
        }
        __syncwarp();
        mbar_wait(bar_q, 0);
        TR(0);
        uint32_t b[8];
#pragma unroll
        for (int i = 0; i < 8; i++) b[i] = lds32(sb + SB_P + 4096 + warp * 288 + (g & 1) * 144 + tq * 4 + i * 16);
        float d[4][4];
        uint32_t a[4][4][4];
#pragma unroll
        for (int i = 0; i < 4; i++) {
            d[i][0] = d[i][1] = d[i][2] = d[i][3] = 0.f;
#pragma unroll
            for (int ks = 0; ks < 4; ks++)
                ldsm4t(a[i][ks], box + ks * 2048 + ((lane & 7) + 8 * (lane >> 4)) * 128 + (((2 * i + ((lane >> 3) & 1)) ^ (lane & 7)) << 4));
        }
#pragma unroll
        for (int ks = 0; ks < 4; ks++)
#pragma unroll
            for (int i = 0; i < 4; i++) mma16816(d[i], a[i][ks], b[2 * ks], b[2 * ks + 1]);
        float* qred = reinterpret_cast<float*>(sm + SB_P);
#pragma unroll
        for (int c = 0; c < 4; c++)
            qred[warp * 128 + (c & 1) * 64 + tq * 16 + (c >> 1) * 8 + g] = tq == 0 ? d[0][c] : tq == 1 ? d[1][c] : tq == 2 ? d[2][c] : d[3][c];
        bar_sync(0, 256);
        if (warp == 0) {
            float4 v[8];
#pragma unroll
            for (int w = 0; w < 8; w++) v[w] = *reinterpret_cast<const float4*>(qred + w * 128 + lane * 4);
#pragma unroll
            for (int o = 4; o; o >>= 1)
#pragma unroll
                for (int w = 0; w < o; w++) { v[w].x += v[w + o].x; v[w].y += v[w + o].y; v[w].z += v[w + o].z; v[w].w += v[w + o].w; }
            st_b128(qdst, make_uint4(packbf(v[0].x, v[0].y), epoch + 1, packbf(v[0].z, v[0].w), epoch + 1));
            if (lane == 0) S->epoch[bx * 8] = epoch + 1;
        }
        TR(1);
    }
    if (!isC) latent_branch(P, M, sm TRPASS);
    }

    const int isA = (r >> JMAP) & 1, cb = ((r >> (JMAP + 1)) << JMAP) + (r & ((1 << JMAP) - 1)), nsnd = isA ? NSA : NSB, isCA = isC & isA;
    const int y0 = isC ? nsnd : 0, y1 = isC ? 32 - 4 * isA : nsnd;
    const int nreq = isC ? 32 - nsnd : nsnd;
    float* const red = reinterpret_cast<float*>(sm + SC_RED);
    const uint32_t wlane = wo_lane(sb, lane);
    if (warp < 8) {
        const unsigned tag = lds32(sb + SB_CNT) + 1;
        const uint32_t t8 = tag & 0xffu;
        if (isC) __nanosleep(8000);
#pragma unroll 1
        for (int step = 0;; step++) {
            if (isCA) {
                const int pair = warp * 8 + (step ? 7 : cb % 7);
                const uint2* mlp = S->aml + pair * (CPG * 4) + (lane & 7) * 4;
                const uint4* src = S->apart + pair * (CPG * 32) + lane;
                asm volatile("" : "+l"(mlp), "+l"(src));
                if (!step) {
                    for (int it = 0; !__all_sync(0xffffffffu, (ld_b64(mlp).y & 0xffu) == t8); it++) {
                        if (it > SPIN_MAX) __trap();
                        __nanosleep(CPOLL);
                    }
                } else {
                    mbar_wait(bar_h + (warp & 3) * 16, 0);
                    mbar_wait(bar_h + (warp & 3) * 16 + 8, 0);
                }
                uint32_t wf[2][8][4];
#pragma unroll
                for (int ks = 0; ks < 8; ks++) {
                    ldsm4t(wf[0][ks], wlane + (warp & 3) * 8192 + ks * 1024);
                    ldsm4t(wf[1][ks], (wlane ^ 32) + (warp & 3) * 8192 + ks * 1024);
                }
                if (step) mbar_wait(sb + SB_BAR, 0);
                TR(3);
                uint4 v[CPG];
                uint2 ml = ld_b64(mlp);
#pragma unroll
                for (int i = 0; i < CPG; i++) v[i] = ld_b128(src + i * 32);
                for (int it = 0;; it++) {
                    unsigned x = ml.y ^ t8;
#pragma unroll
                    for (int i = 0; i < CPG; i++) x |= v[i].x ^ t8;
                    if (!__any_sync(0xffffffffu, x & 0xffu)) break;
                    if (it > SPIN_MAX) __trap();
                    ml = ld_b64(mlp);
#pragma unroll
                    for (int i = 0; i < CPG; i++)
                        if ((v[i].x & 0xffu) != t8) v[i] = ld_b128(src + i * 32);
                }
                TR(2);
                const float e = ex2((__uint_as_float(ml.x) - warp_max(__uint_as_float(ml.x))) * LOG2E);
                float L = e * __uint_as_float(ml.y), oa[4], ob[4];
                L += shx(L, 1);
#pragma unroll
                for (int i = 0; i < CPG; i++) {
                    const float w = __shfl_sync(0xffffffffu, e, i);
                    float (&o)[4] = (i & 1) ? ob : oa;
                    o[0] = i < 2 ? w * __uint_as_float(v[i].x) : fmaf(w, __uint_as_float(v[i].x), o[0]);
                    o[1] = i < 2 ? w * __uint_as_float(v[i].y) : fmaf(w, __uint_as_float(v[i].y), o[1]);
                    o[2] = i < 2 ? w * __uint_as_float(v[i].z) : fmaf(w, __uint_as_float(v[i].z), o[2]);
                    o[3] = i < 2 ? w * __uint_as_float(v[i].w) : fmaf(w, __uint_as_float(v[i].w), o[3]);
                }
                L += shx(L, 2);
                L += shx(L, 4);
                float inv;
                asm("rcp.approx.ftz.f32 %0, %1;" : "=f"(inv) : "f"(L));
                const uint32_t b0 = packbf((oa[0] + ob[0]) * inv, (oa[1] + ob[1]) * inv), b1 = packbf((oa[2] + ob[2]) * inv, (oa[3] + ob[3]) * inv);
                float d[4][4];
#pragma unroll
                for (int i = 0; i < 4; i++) d[i][0] = d[i][1] = d[i][2] = d[i][3] = 0.f;
#pragma unroll
                for (int ks = 0; ks < 8; ks++) {
                    mma16816(d[ks & 1], wf[0][ks], g == ks ? b0 : 0u, g == ks ? b1 : 0u);
                    mma16816(d[2 + (ks & 1)], wf[1][ks], g == ks ? b0 : 0u, g == ks ? b1 : 0u);
                }
                const float x0 = (d[0][0] + d[0][1]) + (d[1][0] + d[1][1]), x1 = (d[0][2] + d[0][3]) + (d[1][2] + d[1][3]);
                const float x2 = (d[2][0] + d[2][1]) + (d[3][0] + d[3][1]), x3 = (d[2][2] + d[2][3]) + (d[3][2] + d[3][3]);
                const float z0 = ((tq & 2) ? x2 : x0) + shx((tq & 2) ? x0 : x2, 2), z1 = ((tq & 2) ? x3 : x1) + shx((tq & 2) ? x1 : x3, 2);
                red[(4 + (warp & 3)) * 80 + (warp >> 2) * 40 + tq * 8 + g] = ((tq & 1) ? z1 : z0) + shx((tq & 1) ? z0 : z1, 1);
                if (step) {
                    bar_arrive(5, 384);
                    TR(5);
                    TROUT();
                    return;
                }
                st_b128(S->frag[1] + pair * 32 + lane, make_uint4(b0, tag, b1, 0));
            }
            uint2* const bfr = reinterpret_cast<uint2*>(sm + SC_FR) + ((warp & 3) * 32 + (g >> 1) * 8 + (warp >> 2) * 4 + tq) * 2 + (g & 1);
            const int p0 = (y0 + 3 - (warp & 3)) >> 2, p1 = (y1 + 3 - (warp & 3)) >> 2;
            const uint4* fsrc = S->frag[0] + isA * 2048 + warp * 256 + lane;
            for (int it = 0;; it++) {
                const uint4 v = ld_b128(fsrc + (p1 - 1) * 32);
                if (__all_sync(0xffffffffu, v.y == tag)) {
                    uint4 u[4];
                    bool ok = true;
#pragma unroll
                    for (int k = 0; k < 4; k++) u[k] = ld_b128(fsrc + min(p0 + k, p1 - 1) * 32);
#pragma unroll
                    for (int k = 0; k < 4; k++) { ok = ok && u[k].y == tag; bfr[min(p0 + k, p1 - 1) * 256] = make_uint2(u[k].x, u[k].z); }
                    bfr[(p1 - 1) * 256] = make_uint2(v.x, v.z);
                    if (__all_sync(0xffffffffu, ok)) break;
                }
                if (it > SPIN_MAX) __trap();
                __nanosleep(CPOLL);
            }
            if (!isCA && warp < 4) break;
            bar_arrive(4, 384);
            if (!isCA) { TROUT(); return; }
        }
    }
    bar_sync(4, 384);
    if (warp == 11) {
        const CUtensorMap* map = &M.wo[isA];
        const unsigned tag = lds32(sb + SB_CNT) + 1;
        const uint32_t t8 = tag & 0xffu;
        uint2* const snd = S->snd + r * 32 + lane;
        asm volatile("prefetch.tensormap [%0];" ::"l"(map) : "memory");
        if (PLACE && !isC) st_b64(snd, t8 ^ 0x80u, 0);
        uint2 f;
        for (int it = 0;; it++) {
            f = ld_b64(S->fire + (lane & 7));
            if (__all_sync(0xffffffffu, f.y == tag)) break;
            if (it > SPIN_MAX) __trap();
            __nanosleep(FPOLL);
        }
        const unsigned t0 = __shfl_sync(0xffffffffu, f.x, 0);
        unsigned t1 = t0 + (__reduce_add_sync(0xffffffffu, (int)(f.x - t0)) >> 5) + FIRE_NS;
        TR(2);
        if (elect()) {
            const int n1 = nreq - (isC ? (isA ? NLA : NLB) : 0);
            const int dt = !isC ? (isA ? FIRE_W / NSA : FIRE_W / NSB) : isA ? FIRE_W / (32 - NSA - NLA) : FIRE_W / (32 - NSB - NLB);
            const unsigned t2 = t1 + REC_NS;
            bool rec = isCA;
            int y = isCA ? 28 : y0;
#pragma unroll 1
            for (int i = 0; i < nreq; i++) {
                const int row = ((y & 3) * 8 + (y >> 2)) * 128;
                mbar_expect(bar_h + i * 16, 4096);
                mbar_expect(bar_h + i * 16 + 8, 4096);
                if (++y == 32) y = y0;
                if (i <= n1) {
                    unsigned t;
                    for (int it = 0; (int)((t = gt()) - t1) < 0 && it < 4096; it++) {}
                    t1 += dt;
                    if (rec && (int)(t - t2) >= 0) { mbar_arrive(sb + SB_BAR); rec = false; }
                }
                tma2d(sb + i * 8192, map, cb * 32, row, bar_h + i * 16);
                tma2d(sb + i * 8192 + 4096, map, cb * 32, row + 64, bar_h + i * 16 + 8);
            }
            TR(3);
            if (rec) {
                for (int it = 0; (int)(gt() - t2) < 0 && it < 4096; it++) {}
                mbar_arrive(sb + SB_BAR);
            }
        }
        __syncwarp();
        uint2 o = make_uint2(0, 0);
        if (isC) {
            for (int it = 0;; it++) {
                o = ld_b64(snd);
                if (__all_sync(0xffffffffu, (o.x & 0xffu) == t8)) break;
                if (it > SPIN_MAX) __trap();
            }
        }
        TR(4);
        uint32_t* const dst = reinterpret_cast<uint32_t*>(P.out) + (lane >> 4) * 512 + (isA ? 0 : 256) + cb * 16 + (lane & 15);
        const float2* q = reinterpret_cast<const float2*>(red) + (lane >> 4) * 20 + (lane & 15);
        bar_sync(5, isCA ? 384 : 256);
        const float2 p0 = q[0], p1 = q[40], p2 = q[80], p4 = q[160], p5 = q[200], p6 = q[240], p7 = q[280];
        const float sx = ((p0.x + p1.x) + (p2.x + __uint_as_float(o.x))) + ((p4.x + p5.x) + (p6.x + p7.x));
        const float sy = ((p0.y + p1.y) + (p2.y + __uint_as_float(o.y))) + ((p4.y + p5.y) + (p6.y + p7.y));
        if (isC) *dst = packbf(sx, sy);
        else st_b64(snd, tagf(sx, t8), __float_as_uint(sy));
        TR(6);
        TROUT();
        return;
    }
    {
        const int nw = isCA ? 3 : 7;
        float e[4][4];
#pragma unroll
        for (int i = 0; i < 4; i++) e[i][0] = e[i][1] = e[i][2] = e[i][3] = 0.f;
#pragma unroll 1
        for (int i = (warp < 8 ? warp + 3 : warp - 8) + 4 * isCA; i < nreq; i += nw) {
            const uint32_t bp = sb + SC_FR + ((y0 + i - 4 * isCA) * 32 + (lane & 7)) * 16;
            uint4 b[4];
#pragma unroll
            for (int j = 0; j < 4; j++) b[j] = lds128(bp + j * 128);
#pragma unroll
            for (int hf = 0; hf < 2; hf++) {
                uint32_t a[8][4];
                mbar_wait(bar_h + i * 16 + hf * 8, 0);
#pragma unroll
                for (int j = 0; j < 8; j++) ldsm4t(a[j], (wlane ^ ((j & 1) * 32)) + i * 8192 + hf * 4096 + (j >> 1) * 1024);
#pragma unroll
                for (int j = 0; j < 8; j++) {
                    const uint4& c = b[2 * hf + (j >> 2)];
                    mma16816(e[(j & 1) * 2 + ((j >> 1) & 1)], a[j], (j & 2) ? c.z : c.x, (j & 2) ? c.w : c.y);
                }
            }
        }
        float* rx = red + (warp < 8 ? warp + 4 : warp - 8) * 80 + (tq & 1) * 40 + (tq >> 1) * 16 + g;
        float s4[4];
#pragma unroll
        for (int c = 0; c < 4; c++) s4[c] = (tq & 2) ? e[2][c] + e[3][c] : e[0][c] + e[1][c];
        rx[0] = (tq & 1) ? s4[1] : s4[0];
        rx[8] = (tq & 1) ? s4[3] : s4[2];
        bar_arrive(5, isCA ? 384 : 256);
        TROUT();
    }
}

typedef CUresult (*EncodeFn)(CUtensorMap*, CUtensorMapDataType, cuuint32_t, void*, const cuuint64_t*, const cuuint64_t*,
                             const cuuint32_t*, const cuuint32_t*, CUtensorMapInterleave, CUtensorMapSwizzle,
                             CUtensorMapL2promotion, CUtensorMapFloatOOBfill);

void make_map(EncodeFn enc, CUtensorMap* m, const void* base, uint64_t cols, uint64_t rows, uint32_t bc, uint32_t br,
              CUtensorMapL2promotion promo, CUtensorMapSwizzle sw = CU_TENSOR_MAP_SWIZZLE_128B) {
    cuuint64_t dims[2] = {cols, rows};
    cuuint64_t strides[1] = {cols * 2};
    cuuint32_t box[2] = {bc, br};
    cuuint32_t es[2] = {1, 1};
    enc(m, CU_TENSOR_MAP_DATA_TYPE_BFLOAT16, 2, const_cast<void*>(base), dims, strides, box, es,
        CU_TENSOR_MAP_INTERLEAVE_NONE, sw, promo, CU_TENSOR_MAP_FLOAT_OOB_FILL_NONE);
}

}

extern "C" void kernel_launch(void* const* d_in, const int* in_sizes, int n_in, void* d_out, int out_size) {
    (void)in_sizes; (void)n_in; (void)out_size;
    static EncodeFn enc = nullptr;
    static void* scr = nullptr;
    if (!enc) {
        void* fn = nullptr;
        cudaDriverEntryPointQueryResult qr;
        cudaGetDriverEntryPoint("cuTensorMapEncodeTiled", &fn, cudaEnableDefault, &qr);
        enc = (EncodeFn)fn;
        cudaGetSymbolAddress(&scr, g_scr);
        cudaFuncSetAttribute(fused_decode_kernel, cudaFuncAttributeMaxDynamicSharedMemorySize, SMEM_BYTES);
    }
    Maps m;
    make_map(enc, &m.kv[0], d_in[1], 64, 1048576, 64, 64, CU_TENSOR_MAP_L2_PROMOTION_NONE);
    make_map(enc, &m.kv[1], d_in[2], 64, 1048576, 64, 64, CU_TENSOR_MAP_L2_PROMOTION_NONE);
    make_map(enc, &m.qa, d_in[3], 4096, 512, 64, 64, CU_TENSOR_MAP_L2_PROMOTION_NONE);
    make_map(enc, &m.qb, d_in[7], 4096, 512, 64, 256, CU_TENSOR_MAP_L2_PROMOTION_L2_256B);
    make_map(enc, &m.wo[0], d_in[10], 512, 4096, 32, 64, WPROMO, CU_TENSOR_MAP_SWIZZLE_64B);
    make_map(enc, &m.wo[1], d_in[4], 512, 4096, 32, 64, WPROMO, CU_TENSOR_MAP_SWIZZLE_64B);
    {
        cuuint64_t dims[4] = {64, 8, 8, 2048}, strides[3] = {1024, 128, 8192};
        cuuint32_t box[4] = {64, 8, 8, 8}, es[4] = {1, 1, 1, 1};
        enc(&m.c, CU_TENSOR_MAP_DATA_TYPE_BFLOAT16, 4, d_in[6], dims, strides, box, es, CU_TENSOR_MAP_INTERLEAVE_NONE,
            CU_TENSOR_MAP_SWIZZLE_128B, CU_TENSOR_MAP_L2_PROMOTION_NONE, CU_TENSOR_MAP_FLOAT_OOB_FILL_NONE);
    }
    make_map(enc, &m.uk, d_in[8], 4096, 512, 64, 256, CU_TENSOR_MAP_L2_PROMOTION_L2_256B);
    make_map(enc, &m.uv, d_in[9], 4096, 512, 64, 256, CU_TENSOR_MAP_L2_PROMOTION_L2_256B);
    Params p;
    p.scr = (Scratch*)scr;
    p.ax = (const uint32_t*)d_in[0];
    p.bx = (const uint32_t*)d_in[5];
    p.out = (__nv_bfloat16*)d_out;
    p.wq = (const char*)d_in[3];
    fused_decode_kernel<<<128, 384, SMEM_BYTES, cudaStreamPerThread>>>(p, m);
}
```

```cpp
#include <cuda_runtime.h>
#include <cuda_bf16.h>
#include <cuda.h>
#include <stdint.h>
#include <float.h>

#define LIM 12
#define LIM0 10
#define RAMP_S 256
#define RAMP_T0 300
#define BAL 20
#define SKEW 3
#define ROT 128
#define FIRE_T 240
#define FIRE_NS 3300
#define FIRE_W 2050
#define NLA 6
#define NLB 8
#define NSA 13
#define NSB 13
#define REC_NS 1800
#define JMAP 2
#define WPROMO CU_TENSOR_MAP_L2_PROMOTION_L2_128B
#define REC0_NS 100
#define DPOLL 300
#define PLACE 1
#define BDELAY 1000
#define QSLEEP 1500
#define QPOLL 0
#define BPOLL 1000
#define CPOLL 700
#define FPOLL 300

namespace {

constexpr int NG = 2, CPG = 32, NW = 4;
constexpr int UPG = 8192;
constexpr int NSL = 12, SPW = NSL / NW;
constexpr unsigned TICK_INC = UPG - NSL * CPG + NW * CPG;
constexpr int SPIN_MAX = 1 << 22;
constexpr float LOG2E = 1.4426950408889634f;
constexpr float SCALE = 0.08838834764831845f;
constexpr uint64_t EVICT_FIRST = 0x12F0000000000000ull;

constexpr int SA_SLOT = NSL * 16384;
constexpr int SA_Q    = SA_SLOT + 8 * NW * 132 * 4;
constexpr int SA_FULL = SA_Q + 8192;
constexpr int SA_EMPTY = SA_FULL + NSL * 16;
constexpr int SA_GOV  = SA_EMPTY + NSL * 8;
constexpr int SA_MBAR = SA_GOV + NSL * 8;
constexpr int SA_QBAR = SA_MBAR + 128;
constexpr int SA_META = SA_QBAR + 16;
constexpr int SA_LIM  = SA_META + NSL * 4;
constexpr int SA_CNT  = SA_LIM + 16;
constexpr int SA_END  = SA_CNT + 64;
constexpr int PROW    = 2080;
constexpr int SB_STG  = 0;
constexpr int SB_QIMG = 131072;
constexpr int SB_P    = SB_QIMG + 32 * PROW;
constexpr int SB_AL   = SB_P + 8192;
constexpr int SB_X    = SB_AL + 256;
static_assert(SB_P % 1024 == 0, "swizzle atom");
constexpr int SB_QB   = SB_X + 4352;
constexpr int NT      = 40;
constexpr int SC_FR   = NT * 4096;
constexpr int SC_FP   = SC_FR + 16384;
constexpr int SC_RED  = SB_QB + 1024;
constexpr int SB_BAR  = SC_RED + 2560;
constexpr int SB_CNT  = SB_BAR + (12 + NT) * 8;
static_assert(SC_FP + 8448 <= SB_P && 2 * (32 - NSA) <= NT && 2 * (32 - NSB) <= NT && NSA <= 16 && NSB <= 16, "projection slots");
constexpr int SB_END  = SB_CNT + 64;
constexpr int SMEM_BYTES = (SA_END > SB_END ? SA_END : SB_END);
static_assert(SMEM_BYTES <= 232448, "shared memory");

struct Scratch {
    uint4    bpart[32 * 32 * (PROW / 16)];
    uint4    apart[64 * CPG * 32];
    uint4    qimg[2 * 4096];
    uint4    qpub[64 * 32];
    uint4    frag[2][64 * 32];
    uint2    snd[32 * 32];
    uint2    aml[64 * CPG * 4];
    unsigned epoch[128 * 8];
    unsigned ctr[1088];
    uint2    fire[544];
    unsigned qflag[1088], bflag[1088];
};
__device__ __align__(1024) Scratch g_scr;

#define TRARG
#define TRPASS
#define TR(k)
#define TROUT()

__device__ __forceinline__ uint32_t s2u(const void* p) { return (uint32_t)__cvta_generic_to_shared(p); }
__device__ __forceinline__ bool elect() {
    uint32_t ok;
    asm volatile("{\n.reg .pred p;\nelect.sync _|p, 0xffffffff;\nselp.u32 %0,1,0,p;\n}" : "=r"(ok));
    return ok;
}
__device__ __forceinline__ void mbar_init(uint32_t b, int c) {
    asm volatile("mbarrier.init.shared::cta.b64 [%0], %1;" ::"r"(b), "r"(c) : "memory");
}
__device__ __forceinline__ void mbar_init_fence() { asm volatile("fence.mbarrier_init.release.cluster;" ::: "memory"); }
__device__ __forceinline__ void mbar_expect(uint32_t b, uint32_t bytes) {
    asm volatile("mbarrier.arrive.expect_tx.shared::cta.b64 _, [%0], %1;" ::"r"(b), "r"(bytes) : "memory");
}
__device__ __forceinline__ void mbar_arrive(uint32_t b) {
    asm volatile("mbarrier.arrive.shared::cta.b64 _, [%0];" ::"r"(b) : "memory");
}
__device__ __forceinline__ bool mbar_test(uint32_t b, uint32_t ph) {
    uint32_t ok;
    asm volatile("{\n.reg .pred p;\nmbarrier.test_wait.parity.shared::cta.b64 p, [%1], %2;\nselp.u32 %0,1,0,p;\n}"
                 : "=r"(ok) : "r"(b), "r"(ph) : "memory");
    return ok;
}
__device__ __forceinline__ void mbar_wait(uint32_t b, uint32_t ph) {
    asm volatile("{\n.reg .pred p;\n.reg .u32 n;\nmov.u32 n, 0;\n"
                 "W: mbarrier.try_wait.parity.shared::cta.b64 p, [%0], %1;\n@p bra.uni D;\n"
                 "add.u32 n, n, 1;\nsetp.lt.u32 p, n, %2;\n@p bra.uni W;\ntrap;\nD:\n}"
                 ::"r"(b), "r"(ph), "n"(SPIN_MAX) : "memory");
}
__device__ __forceinline__ void tma2d(uint32_t dst, const CUtensorMap* map, int c0, int c1, uint32_t bar) {
    asm volatile("cp.async.bulk.tensor.2d.shared::cluster.global.mbarrier::complete_tx::bytes [%0], [%1, {%3, %4}], [%2];"
                 ::"r"(dst), "l"(map), "r"(bar), "r"(c0), "r"(c1) : "memory");
}
__device__ __forceinline__ void tma2d_ef(uint32_t dst, const CUtensorMap* map, int c0, int c1, uint32_t bar) {
    asm volatile("cp.async.bulk.tensor.2d.shared::cluster.global.mbarrier::complete_tx::bytes.L2::cache_hint [%0], [%1, {%3, %4}], [%2], %5;"
                 ::"r"(dst), "l"(map), "r"(bar), "r"(c0), "r"(c1), "l"(EVICT_FIRST) : "memory");
}
__device__ __forceinline__ void tma4d_ef(uint32_t dst, const CUtensorMap* map, int c3, uint32_t bar) {
    asm volatile("cp.async.bulk.tensor.4d.shared::cluster.global.mbarrier::complete_tx::bytes.L2::cache_hint [%0], [%1, {0, 0, 0, %3}], [%2], %4;"
                 ::"r"(dst), "l"(map), "r"(bar), "r"(c3), "l"(EVICT_FIRST) : "memory");
}
__device__ __forceinline__ void bulk_g2s(uint32_t dst, const void* src, uint32_t bytes, uint32_t bar) {
    asm volatile("cp.async.bulk.shared::cluster.global.mbarrier::complete_tx::bytes [%0], [%1], %2, [%3];"
                 ::"r"(dst), "l"(src), "r"(bytes), "r"(bar) : "memory");
}
__device__ __forceinline__ void bulk_s2g(void* dst, uint32_t src, uint32_t bytes) {
    asm volatile("cp.async.bulk.global.shared::cta.bulk_group [%0], [%1], %2;" ::"l"(dst), "r"(src), "r"(bytes) : "memory");
}
__device__ __forceinline__ void fence_async_all() { asm volatile("fence.proxy.async;" ::: "memory"); }
__device__ __forceinline__ void bar_sync(int id, int n) { asm volatile("bar.sync %0, %1;" ::"r"(id), "r"(n) : "memory"); }
__device__ __forceinline__ void bar_arrive(int id, int n) { asm volatile("bar.arrive %0, %1;" ::"r"(id), "r"(n) : "memory"); }
__device__ __forceinline__ unsigned ld_relaxed1(const void* p) {
    unsigned v;
    asm volatile("ld.relaxed.gpu.global.u32 %0, [%1];" : "=r"(v) : "l"(p) : "memory");
    return v;
}
__device__ __forceinline__ unsigned atom_inc(unsigned* p) {
    unsigned v;
    asm volatile("atom.relaxed.gpu.global.add.u32 %0, [%1], 1;" : "=r"(v) : "l"(p) : "memory");
    return v;
}
__device__ __forceinline__ uint4 ld_b128(const void* p) {
    uint4 v;
    asm volatile("{\n.reg .b128 t;\nld.relaxed.gpu.global.b128 t, [%4];\nmov.b128 {%0,%1,%2,%3}, t;\n}"
                 : "=r"(v.x), "=r"(v.y), "=r"(v.z), "=r"(v.w) : "l"(p) : "memory");
    return v;
}
__device__ __forceinline__ void st_b128(void* p, uint4 v) {
    asm volatile("{\n.reg .b128 t;\nmov.b128 t, {%1,%2,%3,%4};\nst.relaxed.gpu.global.b128 [%0], t;\n}"
                 ::"l"(p), "r"(v.x), "r"(v.y), "r"(v.z), "r"(v.w) : "memory");
}
__device__ __forceinline__ uint2 ld_b64(const void* p) {
    uint2 v;
    asm volatile("{\n.reg .b64 a;\nld.relaxed.gpu.global.b64 a, [%2];\nmov.b64 {%0,%1}, a;\n}" : "=r"(v.x), "=r"(v.y) : "l"(p) : "memory");
    return v;
}
__device__ __forceinline__ void st_b64(void* p, uint32_t a, uint32_t b) {
    asm volatile("{\n.reg .b64 t;\nmov.b64 t, {%1,%2};\nst.relaxed.gpu.global.b64 [%0], t;\n}" ::"l"(p), "r"(a), "r"(b) : "memory");
}
__device__ __forceinline__ unsigned ld_acquire(const unsigned* p) {
    unsigned v;
    asm volatile("ld.acquire.gpu.global.u32 %0, [%1];" : "=r"(v) : "l"(p) : "memory");
    return v;
}
__device__ __forceinline__ void st_release(unsigned* p, unsigned v) {
    asm volatile("st.release.gpu.global.u32 [%0], %1;" ::"l"(p), "r"(v) : "memory");
}
__device__ __forceinline__ void ldsm4(uint32_t (&r)[4], uint32_t a) {
    asm volatile("ldmatrix.sync.aligned.m8n8.x4.shared.b16 {%0,%1,%2,%3}, [%4];"
                 : "=r"(r[0]), "=r"(r[1]), "=r"(r[2]), "=r"(r[3]) : "r"(a) : "memory");
}
__device__ __forceinline__ void ldsm4t(uint32_t (&r)[4], uint32_t a) {
    asm volatile("ldmatrix.sync.aligned.m8n8.x4.trans.shared.b16 {%0,%1,%2,%3}, [%4];"
                 : "=r"(r[0]), "=r"(r[1]), "=r"(r[2]), "=r"(r[3]) : "r"(a) : "memory");
}
__device__ __forceinline__ uint4 lds128(uint32_t a) {
    uint4 v;
    asm volatile("ld.shared.v4.u32 {%0, %1, %2, %3}, [%4];" : "=r"(v.x), "=r"(v.y), "=r"(v.z), "=r"(v.w) : "r"(a) : "memory");
    return v;
}
__device__ __forceinline__ uint32_t lds32(uint32_t a) {
    uint32_t v;
    asm volatile("ld.shared.u32 %0, [%1];" : "=r"(v) : "r"(a) : "memory");
    return v;
}
__device__ __forceinline__ void sts32(uint32_t a, uint32_t v) { asm volatile("st.shared.u32 [%0], %1;" ::"r"(a), "r"(v) : "memory"); }
__device__ __forceinline__ void mma16816(float (&d)[4], const uint32_t (&a)[4], uint32_t b0, uint32_t b1) {
    asm volatile("mma.sync.aligned.m16n8k16.row.col.f32.bf16.bf16.f32 {%0,%1,%2,%3}, {%4,%5,%6,%7}, {%8,%9}, {%0,%1,%2,%3};"
                 : "+f"(d[0]), "+f"(d[1]), "+f"(d[2]), "+f"(d[3])
                 : "r"(a[0]), "r"(a[1]), "r"(a[2]), "r"(a[3]), "r"(b0), "r"(b1));
}
__device__ __forceinline__ uint32_t prmt0(uint32_t a, uint32_t sel) {
    uint32_t d;
    asm volatile("prmt.b32 %0, %1, 0, %2;" : "=r"(d) : "r"(a), "r"(sel));
    return d;
}
__device__ __forceinline__ unsigned gt() {
    unsigned t;
    asm volatile("mov.u32 %0, %globaltimer_lo;" : "=r"(t));
    return t;
}
__device__ __forceinline__ unsigned clk32() {
    unsigned c;
    asm volatile("mov.u32 %0, %clock;" : "=r"(c));
    return c;
}
__device__ __forceinline__ float ex2(float x) {
    float y;
    asm("ex2.approx.ftz.f32 %0, %1;" : "=f"(y) : "f"(x));
    return y;
}
__device__ __forceinline__ float bf16r(float x) { return __bfloat162float(__float2bfloat16_rn(x)); }
__device__ __forceinline__ uint32_t packbf(float lo, float hi) {
    uint32_t r;
    asm("cvt.rn.bf16x2.f32 %0, %1, %2;" : "=r"(r) : "f"(hi), "f"(lo));
    return r;
}
__device__ __forceinline__ float bflo(uint32_t v) { return __uint_as_float(v << 16); }
__device__ __forceinline__ float bfhi(uint32_t v) { return __uint_as_float(v & 0xffff0000u); }
__device__ __forceinline__ uint32_t tagf(float v, uint32_t t8) { return (__float_as_uint(v) & 0xffffff00u) | t8; }
__device__ __forceinline__ float shx(float v, int m) { return __shfl_xor_sync(0xffffffffu, v, m); }

__device__ __forceinline__ float warp_max(float v) {
    int i = __float_as_int(v);
    i = __reduce_max_sync(0xffffffffu, i ^ ((i >> 31) & 0x7fffffff));
    return __int_as_float(i ^ ((i >> 31) & 0x7fffffff));
}

__device__ __forceinline__ uint64_t gdesc(uint32_t addr, uint32_t lbo, uint32_t sbo) {
    return (uint64_t)((addr & 0x3ffff) >> 4) | ((uint64_t)(lbo >> 4) << 16) | ((uint64_t)(sbo >> 4) << 32) | (1ull << 62);
}
__device__ __forceinline__ void wg_fence() { asm volatile("wgmma.fence.sync.aligned;" ::: "memory"); }
__device__ __forceinline__ void wg_commit() { asm volatile("wgmma.commit_group.sync.aligned;" ::: "memory"); }
__device__ __forceinline__ void wg_wait0() { asm volatile("wgmma.wait_group.sync.aligned 0;" ::: "memory"); }
template <int N> __device__ __forceinline__ void reg_fence(float (&r)[N]) {
#pragma unroll
    for (int i = 0; i < N; i++) asm volatile("" : "+f"(r[i])::"memory");
}
#define F8(a, o) "+f"(a[o]), "+f"(a[o + 1]), "+f"(a[o + 2]), "+f"(a[o + 3]), "+f"(a[o + 4]), "+f"(a[o + 5]), "+f"(a[o + 6]), "+f"(a[o + 7])
#define F32(a, o) F8(a, o), F8(a, o + 8), F8(a, o + 16), F8(a, o + 24)
__device__ __forceinline__ void wgmma_n64_ss(float (&d)[32], uint64_t da, uint64_t db, int scale_d) {
    asm volatile(
        "{\n.reg .pred p;\nsetp.ne.b32 p, %34, 0;\n"
        "wgmma.mma_async.sync.aligned.m64n64k16.f32.bf16.bf16 "
        "{%0,%1,%2,%3,%4,%5,%6,%7,%8,%9,%10,%11,%12,%13,%14,%15,%16,%17,%18,%19,%20,%21,%22,%23,%24,%25,%26,%27,%28,%29,%30,%31},"
        " %32, %33, p, 1, 1, 0, 0;\n}"
        : F32(d, 0) : "l"(da), "l"(db), "r"(scale_d));
}
__device__ __forceinline__ void wgmma_n32_ts(float (&d)[16], uint64_t da, uint64_t db) {
    asm volatile(
        "{\n.reg .pred p;\nsetp.ne.b32 p, 1, 0;\n"
        "wgmma.mma_async.sync.aligned.m64n32k16.f32.bf16.bf16 "
        "{%0,%1,%2,%3,%4,%5,%6,%7,%8,%9,%10,%11,%12,%13,%14,%15}, %16, %17, p, 1, 1, 1, 0;\n}"
        : F8(d, 0), F8(d, 8) : "l"(da), "l"(db));
}

struct Params {
    Scratch* scr;
    const uint32_t *ax, *bx;
    const char* wq;
    __nv_bfloat16* out;
};
struct Maps { CUtensorMap kv[2], qa, qb, wo[2], c, uk, uv; };

__device__ __forceinline__ void wait_flags(const unsigned* flags, unsigned tag, int lane) {
    for (int i = 0; !__all_sync(0xffffffffu, ld_acquire(flags + lane) == tag); i++) {
        if (i > SPIN_MAX) __trap();
        __nanosleep(BPOLL);
    }
}
__device__ __forceinline__ void load_slice(uint32_t dst, const CUtensorMap* map, int r, uint32_t bar) {
    mbar_expect(bar, 131072);
#pragma unroll
    for (int x = 0; x < 4; x++) tma2d(dst + x * 32768, map, r * 128 + (x & 1) * 64, (x >> 1) * 256, bar);
}
__device__ __forceinline__ void gemv_slice(uint32_t sb, int warp, int lane) {
    const int g = lane >> 2, tq = lane & 3;
    float d[4][4];
#pragma unroll
    for (int i = 0; i < 4; i++) d[i][0] = d[i][1] = d[i][2] = d[i][3] = 0.f;
    const uint32_t wb = sb + SB_STG + (warp >> 2) * 32768 + ((lane & 7) + 8 * (lane >> 4)) * 128 +
                        (((2 * (warp & 3) + ((lane >> 3) & 1)) ^ (lane & 7)) << 4);
    const uint32_t xb = sb + SB_X + ((g & 3) * 264 + tq) * 4;
#pragma unroll 1
    for (int k8 = 0; k8 < 4; k8++) {
        uint32_t a[8][4], b[8][2];
#pragma unroll
        for (int ks = 0; ks < 8; ks++) {
            ldsm4t(a[ks], wb + (k8 >> 1) * 65536 + (k8 & 1) * 16384 + ks * 2048);
            b[ks][0] = lds32(xb + k8 * 256 + ks * 32);
            b[ks][1] = lds32(xb + k8 * 256 + ks * 32 + 16);
        }
#pragma unroll
        for (int ks = 0; ks < 8; ks++) mma16816(d[ks & 3], a[ks], b[ks][0], b[ks][1]);
    }
    const float y0 = ((d[0][0] + d[1][0]) + (d[2][0] + d[3][0])) + ((d[0][1] + d[1][1]) + (d[2][1] + d[3][1]));
    const float y1 = ((d[0][2] + d[1][2]) + (d[2][2] + d[3][2])) + ((d[0][3] + d[1][3]) + (d[2][3] + d[3][3]));
    if (tq < 2) {
        sts32(sb + SB_QB + (tq * 128 + warp * 16 + g) * 4, __float_as_uint(y0));
        sts32(sb + SB_QB + (tq * 128 + warp * 16 + 8 + g) * 4, __float_as_uint(y1));
    }
}
__device__ __forceinline__ uint32_t wo_lane(uint32_t sb, int lane) {
    return sb + ((lane & 7) + 8 * (lane >> 4)) * 64 + ((((lane >> 3) & 1) ^ ((lane >> 1) & 3)) << 4);
}

__device__ __forceinline__ void latent_branch(const Params& P, const Maps& M, uint8_t* sm TRARG) {
    const uint32_t sb = s2u(sm);
    const int tid = threadIdx.x, lane = tid & 31, warp = tid >> 5, g = lane >> 2, tq = lane & 3, r = blockIdx.x >> 2;
    const uint32_t bar_w = sb + SB_BAR + 16, bar_x = sb + SB_BAR + 24;
    const unsigned tag = lds32(sb + SB_CNT) + 1;
    Scratch* const S = P.scr;
    const float* yb = reinterpret_cast<const float*>(sm + SB_QB);
    {
        float* xs = reinterpret_cast<float*>(sm + SB_X);
        const int crow0 = (r >> 4) * 8192 + (r & 15) * 64;
        {
            if (tid == 32) {
                __nanosleep(BDELAY);
                load_slice(sb + SB_STG, &M.qb, r, bar_w);
            }
            uint32_t* xh = reinterpret_cast<uint32_t*>(sm + SB_X) + tid;
            xh[0] = __ldg(P.bx + tid); xh[264] = 0; xh[528] = __ldg(P.bx + 256 + tid); xh[792] = 0;
            bar_sync(0, 256);
            mbar_wait(bar_w, 0);
            TR(0);
            gemv_slice(sb, warp, lane);
            bar_sync(0, 256);
            if (tid == 0) load_slice(sb + SB_STG, &M.uk, r, bar_w);
            uint32_t qb[8][2];
#pragma unroll
            for (int ks = 0; ks < 8; ks++) {
                const float2 a = *reinterpret_cast<const float2*>(yb + (g & 1) * 128 + ks * 16 + 2 * tq);
                const float2 b = *reinterpret_cast<const float2*>(yb + (g & 1) * 128 + ks * 16 + 8 + 2 * tq);
                qb[ks][0] = packbf(a.x, a.y);
                qb[ks][1] = packbf(b.x, b.y);
            }
            mbar_wait(bar_w, 1);
            const uint32_t wb = sb + SB_STG + (warp >> 2) * 65536 + ((warp & 3) * 64 + (lane & 15)) * 128;
#pragma unroll 1
            for (int mt = 0; mt < 4; mt++) {
                float d[4] = {0.f, 0.f, 0.f, 0.f};
#pragma unroll
                for (int ks = 0; ks < 8; ks++) {
                    uint32_t a[4];
                    ldsm4(a, wb + (ks >> 2) * 32768 + mt * 2048 + (((2 * (ks & 3) + (lane >> 4)) ^ (lane & 7)) << 4));
                    mma16816(d, a, qb[ks][0], qb[ks][1]);
                }
                if (tq == 0) {
                    const int c = warp * 64 + mt * 16 + g;
                    xs[c] = d[0]; xs[512 + c] = d[1]; xs[c + 8] = d[2]; xs[512 + c + 8] = d[3];
                }
            }
            bar_sync(0, 256);
            if (tid == 32) {
#pragma unroll
                for (int t = 0; t < 2; t++) {
                    mbar_expect(sb + SB_BAR + t * 8, 65536);
                    tma4d_ef(sb + SB_STG + t * 65536, &M.c, (crow0 >> 3) + t * 128, sb + SB_BAR + t * 8);
                }
            }
            const int b = tid >> 7, lo = (tid >> 6) & 1, ch = tid & 63;
            float v[8];
#pragma unroll
            for (int i = 0; i < 8; i++) {
                const float x = xs[b * 512 + ch * 8 + i];
                v[i] = lo ? x - bf16r(x) : x;
            }
            const int row = 16 * (r >> 3) + (r & 7) + 8 * lo;
            S->qimg[b * 4096 + (ch >> 3) * 512 + row * 8 + ((ch & 7) ^ (r & 7))] =
                make_uint4(packbf(v[0], v[1]), packbf(v[2], v[3]), packbf(v[4], v[5]), packbf(v[6], v[7]));
            bar_sync(0, 256);
            if (warp == 0) {
                if (lane == 0) { __threadfence(); st_release(S->qflag + r, tag); }
                wait_flags(S->qflag, tag, lane);
                if (lane == 0) {
                    fence_async_all();
                    mbar_expect(bar_x, 65536);
                    bulk_g2s(sb + SB_QIMG, S->qimg + (r >> 4) * 4096, 65536, bar_x);
                }
            }
            mbar_wait(bar_x, 0);
        }
        TR(1);
        {
            const int wg = warp >> 2;
            float acc[4][16];
#pragma unroll
            for (int i = 0; i < 64; i++) acc[i >> 4][i & 15] = 0.f;
            const int head = (warp & 3) * 8 + g;
            const uint32_t pa = sb + SB_P + wg * 4096;
            float* al = reinterpret_cast<float*>(sm + SB_AL) + wg * 32;
            float m = -FLT_MAX, l = 0.f;
#pragma unroll 1
            for (int t = 0; t < 8; t++) {
                const uint32_t stg = sb + SB_STG + (t & 1) * 65536;
                mbar_wait(sb + SB_BAR + (t & 1) * 8, (t >> 1) & 1);
                float s[32];
                uint32_t qa = sb + SB_QIMG;
                asm volatile("" : "+r"(qa));
                wg_fence();
#pragma unroll
                for (int k = 0; k < 32; k++) {
                    const uint32_t off = (k >> 2) * 8192 + (k & 3) * 32;
                    wgmma_n64_ss(s, gdesc(qa + off, 16, 1024), gdesc(stg + (k >> 2) * 1024 + (k & 3) * 32, 16, 8192), k > 0);
                }
                wg_commit();
                wg_wait0();
                reg_fence(s);
                float p[16], mx = m;
#pragma unroll
                for (int i = 0; i < 8; i++) {
                    p[2 * i] = bf16r(bf16r(s[4 * i] + s[4 * i + 2]) * SCALE);
                    p[2 * i + 1] = bf16r(bf16r(s[4 * i + 1] + s[4 * i + 3]) * SCALE);
                    mx = fmaxf(mx, fmaxf(p[2 * i], p[2 * i + 1]));
                }
                mx = fmaxf(mx, shx(mx, 1));
                mx = fmaxf(mx, shx(mx, 2));
                const float alpha = ex2((m - mx) * LOG2E);
                m = mx;
                float sum = 0.f;
#pragma unroll
                for (int i = 0; i < 8; i++) {
                    const float a = ex2((p[2 * i] - mx) * LOG2E), b = ex2((p[2 * i + 1] - mx) * LOG2E);
                    sum += a + b;
                    sts32(pa + head * 128 + ((i ^ g) << 4) + tq * 4, packbf(a, b));
                }
                l = fmaf(l, alpha, sum);
                if (tq == 0) al[head] = alpha;
                asm volatile("fence.proxy.async.shared::cta;" ::: "memory");
                bar_sync(1 + wg, 128);
#pragma unroll
                for (int j = 0; j < 4; j++) {
                    const float2 a = *reinterpret_cast<const float2*>(al + 8 * j + 2 * tq);
#pragma unroll
                    for (int i = 0; i < 4; i++) { acc[i][4 * j] *= a.x; acc[i][4 * j + 1] *= a.y; acc[i][4 * j + 2] *= a.x; acc[i][4 * j + 3] *= a.y; }
                }
#pragma unroll
                for (int i = 0; i < 4; i++) reg_fence(acc[i]);
                wg_fence();
#pragma unroll
                for (int kk = 0; kk < 4; kk++)
#pragma unroll
                    for (int i = 0; i < 4; i++)
                        wgmma_n32_ts(acc[i], gdesc(stg + (wg * 4 + i) * 1024 + kk * 16384, 1024, 8192), gdesc(pa + kk * 32, 16, 1024));
                wg_commit();
                wg_wait0();
#pragma unroll
                for (int i = 0; i < 4; i++) reg_fence(acc[i]);
                bar_sync(0, 256);
                if (tid == 0) {
                    if (t + 2 < 8) {
                        const uint32_t bar = sb + SB_BAR + (t & 1) * 8;
                        mbar_expect(bar, 65536);
                        tma4d_ef(stg, &M.c, (crow0 >> 3) + (t + 2) * 128, bar);
                    }
                    if (t == 7) load_slice(sb + SB_STG, &M.uv, r, bar_w);
                }
            }
            TR(2);
            float* dst = reinterpret_cast<float*>(sm + SB_QIMG + 2 * tq * PROW) + wg * 256 + (warp & 3) * 16 + g;
#pragma unroll
            for (int i = 0; i < 64; i++)
                dst[(((i >> 2) & 3) * 8 + (i & 1)) * (PROW / 4) + (i >> 4) * 64 + (i & 2) * 4] = acc[i >> 4][i & 15];
            l += shx(l, 1); l += shx(l, 2);
            if (wg == 0 && tq < 2) *reinterpret_cast<float4*>(sm + SB_QIMG + head * PROW + 2048 + tq * 16) = make_float4(m, l, 0.f, 0.f);
            asm volatile("fence.proxy.async.shared::cta;" ::: "memory");
            bar_sync(0, 256);
            if (warp == 0) {
                bulk_s2g(S->bpart + (lane * 32 + r) * (PROW / 16), sb + SB_QIMG + lane * PROW, PROW);
                asm volatile("cp.async.bulk.commit_group;" ::: "memory");
                asm volatile("cp.async.bulk.wait_group 0;" ::: "memory");
                fence_async_all();
                __threadfence();
                __syncwarp();
                if (lane == 0) st_release(S->bflag + r, tag);
                wait_flags(S->bflag, tag, lane);
                if (lane == 0) {
                    fence_async_all();
                    mbar_expect(bar_x, 32 * PROW);
                    bulk_g2s(sb + SB_QIMG, S->bpart + r * 32 * (PROW / 16), 32 * PROW, bar_x);
                }
            }
        }
        {
            const int b = tid >> 7, c4 = tid & 127;
            mbar_wait(bar_x, 1);
            TR(3);
            const float2 ml = *reinterpret_cast<const float2*>(sm + SB_QIMG + (b * 16 + (lane & 15)) * PROW + 2048);
            float MM = ml.x;
            MM = fmaxf(MM, shx(MM, 1)); MM = fmaxf(MM, shx(MM, 2)); MM = fmaxf(MM, shx(MM, 4)); MM = fmaxf(MM, shx(MM, 8));
            const float e = ex2((ml.x - MM) * LOG2E);
            float L = e * ml.y;
            L += shx(L, 1); L += shx(L, 2); L += shx(L, 4); L += shx(L, 8);
            const float wgt = e / L;
            float4 o = make_float4(0.f, 0.f, 0.f, 0.f);
#pragma unroll 4
            for (int i = 0; i < 16; i++) {
                const float w = __shfl_sync(0xffffffffu, wgt, i);
                const float4 v = *reinterpret_cast<const float4*>(sm + SB_QIMG + (b * 16 + i) * PROW + c4 * 16);
                o.x = fmaf(w, v.x, o.x); o.y = fmaf(w, v.y, o.y); o.z = fmaf(w, v.z, o.z); o.w = fmaf(w, v.w, o.w);
            }
            uint32_t* xh = reinterpret_cast<uint32_t*>(xs);
            const uint32_t h0 = packbf(o.x, o.y), h1 = packbf(o.z, o.w);
            *reinterpret_cast<uint2*>(xh + (2 * b) * 264 + c4 * 2) = make_uint2(h0, h1);
            *reinterpret_cast<uint2*>(xh + (2 * b + 1) * 264 + c4 * 2) =
                make_uint2(packbf(o.x - bflo(h0), o.y - bfhi(h0)), packbf(o.z - bflo(h1), o.w - bfhi(h1)));
            bar_sync(0, 256);
            mbar_wait(bar_w, 0);
            gemv_slice(sb, warp, lane);
            bar_sync(0, 256);
            if (tid < 64) {
                const float* y = yb + warp * 128 + 16 * g + 2 * tq;
                st_b128(S->frag[0] + (warp * 32 + r) * 32 + lane, make_uint4(packbf(y[0], y[1]), tag, packbf(y[8], y[9]), tag));
            }
        }
        TR(4);
    }
}

__global__ void __launch_bounds__(480, 1)
fused_decode_kernel(const Params P, const __grid_constant__ Maps M) {
    extern __shared__ __align__(1024) uint8_t sm[];
    const uint32_t sb = s2u(sm);
    const int tid = threadIdx.x, lane = tid & 31, bx = blockIdx.x;
    asm volatile("{\n.reg .pred p;\nsetp.lt.u32 p, %1, 256;\n@p prefetch.global.L2 [%0];\n}"
                 ::"l"(P.wq + (unsigned)(bx * 32768 + tid * 128)), "r"(tid) : "memory");
    const int warp = __shfl_sync(0xffffffffu, tid >> 5, 0);
    const int g = lane >> 2, tq = lane & 3;
    Scratch* const S = P.scr;

    if (!(bx & 1)) {
        const int grp = (bx >> 1) & 1, crk = bx >> 2;
        const int rowbase = grp * (UPG * 64);
        auto issue = [&](int slot, unsigned tk, int v) {
            const int row = rowbase + (int)((tk & ~255u) | ((tk + grp * ROT) & 255u)) * 64;
            const uint32_t full = sb + SA_FULL + slot * 16 + v * 8;
            mbar_expect(full, 8192);
            tma2d_ef(sb + slot * 16384 + v * 8192, &M.kv[v], 0, row, full);
        };
        if (warp >= 8) {
            const int w = warp - 8;
            if (w >= NW) return;
            const bool one = elect();
            if (one) {
                mbar_init(sb + SA_FULL + w * 16, 1);
                mbar_init_fence();
                TR(3);
                sts32(sb + SA_META + w * 4, 0);
                if (w < SKEW) issue(w, w * CPG + crk, 0);
#pragma unroll
                for (int i = 0; i < SPW; i++) {
                    if (i) mbar_init(sb + SA_FULL + (w + i * NW) * 16, 1);
                    mbar_init(sb + SA_FULL + (w + i * NW) * 16 + 8, 1);
                    mbar_init(sb + SA_GOV + (w + i * NW) * 8, 1);
                    mbar_init(sb + SA_EMPTY + (w + i * NW) * 8, 2);
                    mbar_arrive(sb + SA_EMPTY + (w + i * NW) * 8);
                }
                if (w < SKEW) mbar_arrive(sb + SA_EMPTY + w * 8);
                sts32(sb + SA_LIM + w * 4, LIM);
                mbar_init_fence();
            }
            __syncwarp();
            bar_arrive(2, (NW + 1) * 32);
            bar_arrive(1, (2 * NW + 2) * 32);
            unsigned c = 0, tbase = 0;
            int slot = w;
            uint32_t eph = 0;
#pragma unroll 1
            for (int n = 0;; n++) {
                unsigned tk = (n * NW + w) * CPG + crk;
                if (n == SPW) {
                    mbar_wait(sb + SA_EMPTY + w * 8, 1);
                    tbase = NSL * CPG - lds32(sb + SA_CNT) * TICK_INC;
                }
                if (n >= SPW) {
                    const unsigned own = __shfl_sync(0xffffffffu, c, grp);
                    tk = own + tbase;
                    const int lag = (int)(__reduce_add_sync(0xffffffffu, c) - NG * own);
                    if (one) sts32(sb + SA_LIM + w * 4, lag > BAL * NG ? LIM + 1 : lag < -BAL * NG ? LIM - 1 : LIM);
                }
                mbar_wait(sb + SA_EMPTY + slot * 8, eph);
                if (tk >= UPG) {
                    if (one) { sts32(sb + SA_LIM + w * 4, 0); sts32(sb + SA_META + slot * 4, 32); mbar_arrive(sb + SA_FULL + slot * 16); }
                    return;
                }
                if (one && (n || w >= SKEW)) {
                    sts32(sb + SA_META + slot * 4, tk >> 8);
                    issue(slot, tk, 0);
                    if (tk == 1200) TR(6);
                    if (tk == UPG - FIRE_T) { st_b64(S->fire + grp, gt(), lds32(sb + SA_CNT) + 1); TR(4); }
                }
                if (n >= SPW - 1) {
                    if (lane == grp) c = atom_inc(S->ctr + lane);
                    else if (lane < NG) c = ld_relaxed1(S->ctr + lane);
                }
                mbar_wait(sb + SA_GOV + slot * 8, eph);
                if (one) issue(slot, tk, 1);
                TR(0);
                slot += NW;
                if (slot >= NSL) { slot -= NSL; eph ^= 1; }
                __syncwarp();
            }
        }
        if (warp == 0) {
            bool busy = lane < 2 * SKEW && !(lane & 1);
            uint32_t par = busy ? 0 : 1;
            int slot = SKEW;
            bool first = true;
            const unsigned c0 = clk32() + RAMP_T0;
            const int own = lane >= 2 * NSL ? -1 : ((lane >> 1) + (lane & 1) * SKEW) % NSL;
            const uint32_t fb = sb + SA_FULL + lane * 8, lw = sb + SA_LIM + ((lane >> 1) % NW) * 4;
            const uint32_t go = sb + ((lane & 1) ? SA_GOV : SA_EMPTY) + (lane >> 1) * 8;
            bar_sync(2, (NW + 1) * 32);
#pragma unroll 1
            for (int it = 0; it < SPIN_MAX; it++) {
                bool ok = true;
                if (busy) ok = mbar_test(fb, par);
                int lim = lds32(lw);
                if (first) lim = min(LIM0, SKEW + max((int)(clk32() - c0), 0) / RAMP_S);
                busy = busy && !ok && lim;
                const int n = __popc(__ballot_sync(0xffffffffu, busy));
                if (!__any_sync(0xffffffffu, lim)) return;
                const bool mine = own == slot && lim;
                if (!__any_sync(0xffffffffu, mine && (busy || n > lim - 2))) {
                    if (mine) { mbar_arrive(go); busy = true; par ^= 1; }
                    if (++slot == NSL) { slot = 0; first = false; }
                    it = 0;
                }
            }
            __trap();
        }
        {
            int w3 = warp;
            asm volatile("" : "+r"(w3));
            if (w3 == 3) return;
        }
        if (warp == 1) {
            const uint4* const qsrc = S->qpub + grp * 1024 + lane;
            uint2* const qdst = reinterpret_cast<uint2*>(sm + SA_Q) + lane;
            const unsigned epoch = ld_relaxed1(S->epoch + bx * 8);
            if (lane == 0) {
                mbar_init(sb + SA_QBAR, 32);
                mbar_init(sb + SA_QBAR + 8, 32);
#pragma unroll
                for (int i = 0; i < 8; i++) { mbar_init(sb + SA_MBAR + i * 16, NW); mbar_init(sb + SA_MBAR + i * 16 + 8, 1); }
                mbar_init_fence();
                sts32(sb + SA_CNT, epoch);
            }
            __syncwarp();
            bar_arrive(1, (2 * NW + 2) * 32);
            if (lane == 0) S->epoch[bx * 8] = epoch + 1;
            __nanosleep(QSLEEP);
            for (int it = 0;; it++) {
                const uint4 u = ld_b128(qsrc), v = ld_b128(qsrc + 32);
                if (__all_sync(0xffffffffu, u.y == epoch + 1 && v.y == epoch + 1)) {
                    qdst[0] = make_uint2(u.x, u.z);
                    qdst[32] = make_uint2(v.x, v.z);
                    break;
                }
                if (it > SPIN_MAX) __trap();
                if (QPOLL) __nanosleep(QPOLL);
            }
            mbar_arrive(sb + SA_QBAR + 8);
#pragma unroll 1
            for (int h = 2, it = 0; h < 32; it++) {
                uint4 v[10];
                bool ok = true;
#pragma unroll
                for (int k = 0; k < 10; k++) v[k] = ld_b128(qsrc + (h + k) * 32);
#pragma unroll
                for (int k = 0; k < 10; k++) { ok = ok && v[k].y == epoch + 1; qdst[(h + k) * 32] = make_uint2(v[k].x, v[k].z); }
                if (__all_sync(0xffffffffu, ok)) h += 10;
                else __nanosleep(300);
                if (it > SPIN_MAX) __trap();
            }
            mbar_arrive(sb + SA_QBAR);
            return;
        }
        bar_sync(1, (2 * NW + 2) * 32);
        if (warp == 2) {
            const uint32_t t8 = (lds32(sb + SA_CNT) + 1) & 0xffu;
            uint4* dst = S->apart + (grp * 32 * CPG + crk) * 32 + lane;
            uint2* dml = S->aml + (grp * 32 * CPG + crk) * 4 + (lane & 3);
#pragma unroll 1
            for (int h = 0; h < 32; h++, dst += CPG * 32, dml += CPG * 4) {
                const float* s0 = reinterpret_cast<const float*>(sm + SA_SLOT) + (h & 7) * (NW * 132);
                mbar_wait(sb + SA_MBAR + (h & 7) * 16, (h >> 3) & 1);
                float2 ml[NW];
                float4 v[NW];
#pragma unroll
                for (int w = 0; w < NW; w++) {
                    ml[w] = *reinterpret_cast<const float2*>(s0 + w * 132 + 128);
                    v[w] = *reinterpret_cast<const float4*>(s0 + w * 132 + lane * 4);
                }
                const float MM = fmaxf(fmaxf(ml[0].x, ml[1].x), fmaxf(ml[2].x, ml[3].x));
                float e[NW];
#pragma unroll
                for (int w = 0; w < NW; w++) e[w] = ex2((ml[w].x - MM) * LOG2E);
                st_b128(dst, make_uint4(tagf(fmaf(e[0], v[0].x, e[1] * v[1].x) + fmaf(e[2], v[2].x, e[3] * v[3].x), t8),
                                        __float_as_uint(fmaf(e[0], v[0].y, e[1] * v[1].y) + fmaf(e[2], v[2].y, e[3] * v[3].y)),
                                        __float_as_uint(fmaf(e[0], v[0].z, e[1] * v[1].z) + fmaf(e[2], v[2].z, e[3] * v[3].z)),
                                        __float_as_uint(fmaf(e[0], v[0].w, e[1] * v[1].w) + fmaf(e[2], v[2].w, e[3] * v[3].w))));
                if (lane < 4) st_b64(dml, __float_as_uint(MM), tagf(fmaf(e[0], ml[0].y, e[1] * ml[1].y) + fmaf(e[2], ml[2].y, e[3] * ml[3].y), t8));
                TR(2);
                if (PLACE && (h == 27 || h == 28)) {
                    st_b128(dst + 3 * CPG * 32, make_uint4(t8 ^ 0x80u, 0, 0, 0));
                    if (lane < 4) st_b64(dml + 3 * CPG * 4, 0, t8 ^ 0x80u);
                }
                __syncwarp();
                if (lane == 0) mbar_arrive(sb + SA_MBAR + (h & 7) * 16 + 8);
            }
            TROUT();
            return;
        }
        const int cw = warp - 4;
        uint32_t koff[4], voff[4];
#pragma unroll
        for (int i = 0; i < 4; i++) {
            koff[i] = ((lane & 7) + 8 * ((lane >> 3) & 1)) * 128 + (((2 * i + (lane >> 4)) ^ (lane & 7)) << 4);
            voff[i] = ((lane & 7) + 8 * (lane >> 4)) * 128 + (((2 * i + ((lane >> 3) & 1)) ^ (lane & 7)) << 4);
        }
        uint32_t psel[4][2];
#pragma unroll
        for (int i = 0; i < 4; i++) {
            psel[i][0] = (g >> 1) != i ? 0x4444u : (g & 1) ? 0x1044u : 0x4410u;
            psel[i][1] = (g >> 1) != i ? 0x4444u : (g & 1) ? 0x3244u : 0x4432u;
        }
        uint32_t qf[4][2];
        auto load_q = [&](int pl) {
            const uint32_t q = sb + SA_Q + pl * 256 + ((g & 1) * 32 + tq) * 4;
#pragma unroll
            for (int ks = 0; ks < 4; ks++) { qf[ks][0] = lds32(q + ks * 32); qf[ks][1] = lds32(q + ks * 32 + 16); }
        };
        mbar_wait(sb + SA_QBAR + 8, 0);
        TR(0);
        load_q(0);
        float acc[4][4], m = -FLT_MAX, l = 0.f, ls = 0.f;
#pragma unroll
        for (int i = 0; i < 4; i++) acc[i][0] = acc[i][1] = acc[i][2] = acc[i][3] = 0.f;
        int slot = cw, cur = 0;
        uint32_t ph = 0;
#pragma unroll 1
        for (;;) {
            mbar_wait(sb + SA_FULL + slot * 16, ph);
            const int pl = lds32(sb + SA_META + slot * 4);
            if (pl != cur) {
#pragma unroll 1
                do {
                    float* s0 = reinterpret_cast<float*>(sm + SA_SLOT) + ((cur & 7) * NW + cw) * 132;
                    float* sw = s0 + tq * 16 + (g >> 1) * 4 + (g & 1);
                    sw[0] = (acc[0][0] + acc[1][0]) + (acc[2][0] + acc[3][0]);
                    sw[2] = (acc[0][2] + acc[1][2]) + (acc[2][2] + acc[3][2]);
                    sw[64] = (acc[0][1] + acc[1][1]) + (acc[2][1] + acc[3][1]);
                    sw[66] = (acc[0][3] + acc[1][3]) + (acc[2][3] + acc[3][3]);
                    if (lane == 0) *reinterpret_cast<float2*>(s0 + 128) = make_float2(m, ls);
                    __syncwarp();
                    if (lane == 0) mbar_arrive(sb + SA_MBAR + (cur & 7) * 16);
                    if (++cur == 32) { TROUT(); return; }
#pragma unroll
                    for (int i = 0; i < 4; i++) acc[i][0] = acc[i][1] = acc[i][2] = acc[i][3] = 0.f;
                    m = -FLT_MAX; l = ls = 0.f;
                    mbar_wait(sb + SA_MBAR + (cur & 7) * 16 + 8, ((cur >> 3) & 1) ^ 1);
                    if (cur == 2) mbar_wait(sb + SA_QBAR, 0);
                } while (cur != pl);
                load_q(pl);
            }
            float s4[4][4];
            const uint32_t kb = sb + slot * 16384;
#pragma unroll
            for (int j = 0; j < 4; j++) {
                s4[j][0] = s4[j][1] = s4[j][2] = s4[j][3] = 0.f;
                const bool on = (g >> 1) == j;
#pragma unroll
                for (int ks = 0; ks < 4; ks++) {
                    uint32_t a[4];
                    ldsm4(a, kb + j * 2048 + koff[ks]);
                    mma16816(s4[j], a, on ? qf[ks][0] : 0u, on ? qf[ks][1] : 0u);
                }
            }
            float d[4];
#pragma unroll
            for (int r = 0; r < 4; r++) d[r] = (s4[0][r] + s4[1][r]) + (s4[2][r] + s4[3][r]);
            float sa = (g & 1) ? d[1] : d[0], sc = (g & 1) ? d[3] : d[2];
            sa += shx(sa, 4); sc += shx(sc, 4);
            uint32_t sp = packbf(sa, sc);
            sp = packbf(bflo(sp) * SCALE, bfhi(sp) * SCALE);
            sa = bflo(sp); sc = bfhi(sp);
            const float mx = warp_max(fmaxf(fmaxf(sa, sc), m));
            const float alpha = ex2((m - mx) * LOG2E);
            m = mx;
            const float pa = ex2((sa - mx) * LOG2E), pc = ex2((sc - mx) * LOG2E);
            const uint32_t pk = packbf(pa, pc);
            uint32_t pb[4][4][2];
#pragma unroll
            for (int j = 0; j < 4; j++) {
                const uint32_t pj = __shfl_sync(0xffffffffu, pk, 8 * tq + j);
#pragma unroll
                for (int i = 0; i < 4; i++) { pb[j][i][0] = prmt0(pj, psel[i][0]); pb[j][i][1] = prmt0(pj, psel[i][1]); }
            }
            l = fmaf(l, alpha, pa + pc);
            ls = l + shx(l, 8);
#pragma unroll
            for (int i = 0; i < 4; i++) { acc[i][0] *= alpha; acc[i][1] *= alpha; acc[i][2] *= alpha; acc[i][3] *= alpha; }
            mbar_wait(sb + SA_FULL + slot * 16 + 8, ph);
            TR(1);
            const uint32_t vb = kb + 8192;
#pragma unroll
            for (int i = 0; i < 4; i++)
#pragma unroll
                for (int j = 0; j < 4; j++) {
                    uint32_t a[4];
                    ldsm4t(a, vb + j * 2048 + voff[i]);
                    mma16816(acc[j], a, pb[j][i][0], pb[j][i][1]);
                }
            ls += shx(ls, 16); ls += shx(ls, 1); ls += shx(ls, 2);
            __syncwarp();
            if (lane == 0) mbar_arrive(sb + SA_EMPTY + slot * 8);
            slot += NW;
            if (slot >= NSL) { slot -= NSL; ph ^= 1; }
        }
    }

    const int r = bx >> 2, isC = (bx >> 1) & 1;
    const uint32_t bar_h = sb + SB_BAR + 32;
    if (warp < 8) {
    {
        const uint32_t bar_q = bar_h + (NT + warp) * 8, box = sb + SB_QIMG + warp * 8192;
        if (elect()) {
            mbar_init(bar_q, 1);
            mbar_init_fence();
            mbar_expect(bar_q, 8192 + 256);
            tma2d(box, &M.qa, (bx >> 1) * 64, warp * 64, bar_q);
            bulk_g2s(sb + SB_P + 4096 + warp * 288, P.ax + warp * 32, 128, bar_q);
            bulk_g2s(sb + SB_P + 4096 + warp * 288 + 144, P.ax + 256 + warp * 32, 128, bar_q);
        }
        unsigned epoch = 0;
        if (warp < 2) epoch = ld_relaxed1(S->epoch + bx * 8);
        uint4* const qdst = S->qpub + ((lane >> 4) * 32 + r) * 32 + isC * 16 + (lane & 15);
        if (PLACE && warp == 0) st_b128(qdst, make_uint4(0, 0, 0, 0));
        if (tid == 32) {
#pragma unroll
            for (int i = 0; i < 4 + NT; i++) mbar_init(sb + SB_BAR + i * 8, 1);
            mbar_init_fence();
            sts32(sb + SB_CNT, epoch);
        }
        __syncwarp();
        mbar_wait(bar_q, 0);
        TR(0);
        uint32_t b[8];
#pragma unroll
        for (int i = 0; i < 8; i++) b[i] = lds32(sb + SB_P + 4096 + warp * 288 + (g & 1) * 144 + tq * 4 + i * 16);
        float d[4][4];
        uint32_t a[4][4][4];
#pragma unroll
        for (int i = 0; i < 4; i++) {
            d[i][0] = d[i][1] = d[i][2] = d[i][3] = 0.f;
#pragma unroll
            for (int ks = 0; ks < 4; ks++)
                ldsm4t(a[i][ks], box + ks * 2048 + ((lane & 7) + 8 * (lane >> 4)) * 128 + (((2 * i + ((lane >> 3) & 1)) ^ (lane & 7)) << 4));
        }
#pragma unroll
        for (int ks = 0; ks < 4; ks++)
#pragma unroll
            for (int i = 0; i < 4; i++) mma16816(d[i], a[i][ks], b[2 * ks], b[2 * ks + 1]);
        float* qred = reinterpret_cast<float*>(sm + SB_P);
#pragma unroll
        for (int c = 0; c < 4; c++)
            qred[warp * 128 + (c & 1) * 64 + tq * 16 + (c >> 1) * 8 + g] = tq == 0 ? d[0][c] : tq == 1 ? d[1][c] : tq == 2 ? d[2][c] : d[3][c];
        bar_sync(0, 256);
        if (warp == 0) {
            float4 v[8];
#pragma unroll
            for (int w = 0; w < 8; w++) v[w] = *reinterpret_cast<const float4*>(qred + w * 128 + lane * 4);
#pragma unroll
            for (int o = 4; o; o >>= 1)
#pragma unroll
                for (int w = 0; w < o; w++) { v[w].x += v[w + o].x; v[w].y += v[w + o].y; v[w].z += v[w + o].z; v[w].w += v[w + o].w; }
            st_b128(qdst, make_uint4(packbf(v[0].x, v[0].y), epoch + 1, packbf(v[0].z, v[0].w), epoch + 1));
            if (lane == 0) S->epoch[bx * 8] = epoch + 1;
        }
        TR(1);
    }
    if (!isC) latent_branch(P, M, sm TRPASS);
    bar_arrive(6, 288);
    }

    constexpr int ND = 2;
    const int isA = (r >> JMAP) & 1, cb = ((r >> (JMAP + 1)) << JMAP) + (r & ((1 << JMAP) - 1)), nsnd = isA ? NSA : NSB, isCA = isC & isA;
    const int y0 = isC ? nsnd : 0, y1 = isC ? 32 - ND * isA : nsnd;
    const int nreq = isC ? 32 - nsnd : nsnd;
    float* const red = reinterpret_cast<float*>(sm + SC_RED);
    const uint32_t wlane = wo_lane(sb, lane);
    auto fetch_frag = [&](int y, int b, unsigned tag, unsigned ns) {
        for (int it = 0;; it++) {
            const uint4 v = ld_b128(S->frag[0] + isA * 2048 + (b * 32 + y) * 32 + lane);
            if (__all_sync(0xffffffffu, v.y == tag)) {
                reinterpret_cast<uint2*>(sm + SC_FR)[(y * 32 + (g >> 1) * 8 + b * 4 + tq) * 2 + (g & 1)] = make_uint2(v.x, v.z);
                return;
            }
            if (it > SPIN_MAX) __trap();
            __nanosleep(ns);
        }
    };
    if (warp < 8) {
        const unsigned tag = lds32(sb + SB_CNT) + 1;
        const uint32_t t8 = tag & 0xffu;
        uint32_t bs[2], wf[4][4];
        float d[2][4];
        const uint32_t wa = (wlane ^ ((warp & 1) * 32)) + (warp & 2) * 2048;
        const int ks0 = (warp & 2) * 2;
        if (isC) __nanosleep(4000);
#pragma unroll 1
        for (int op = isCA ? 0 : 1;; op++) {
            const int step = isCA ? max(op - 1, 0) : 0, h = step ? 31 - ND + step : isA ? cb : 16 + cb;
            if (op != 1) {
                if (!isCA && (!isC || h >= 32 - ND)) break;
                const int rec = ((warp >> 2) * 32 + h) * CPG + (warp & 3) * 8;
                const uint2* mlp = S->aml + (rec + (lane & 7)) * 4;
                const uint4* src = S->apart + rec * 32 + lane;
                asm volatile("" : "+l"(mlp), "+l"(src));
                if (!step) {
                    for (int it = 0; !__all_sync(0xffffffffu, (ld_b64(mlp).y & 0xffu) == t8); it++) {
                        if (it > SPIN_MAX) __trap();
                        __nanosleep(h > 25 ? DPOLL : CPOLL);
                    }
                } else if (step < ND) {
                    mbar_wait(sb + SB_BAR + 8, 0);
                } else {
                    d[0][0] = d[0][1] = d[0][2] = d[0][3] = d[1][0] = d[1][1] = d[1][2] = d[1][3] = 0.f;
#pragma unroll
                    for (int k = 0; k < ND; k++) {
                        mbar_wait(bar_h + k * 16 + (warp & 2) * 4, 0);
#pragma unroll
                        for (int ks = 0; ks < 4; ks++) ldsm4t(wf[ks], wa + k * 8192 + ks * 1024);
                        if (k < ND - 1) {
#pragma unroll
                            for (int ks = 0; ks < 4; ks++) mma16816(d[ks & 1], wf[ks], g == ks0 + ks ? bs[0] : 0u, g == ks0 + ks ? bs[1] : 0u);
                        }
                    }
                    mbar_wait(sb + SB_BAR, 0);
                }
                TR(3);
                uint4 v[8];
                uint2 ml = ld_b64(mlp);
#pragma unroll
                for (int i = 0; i < 8; i++) v[i] = ld_b128(src + i * 32);
                for (int it = 0;; it++) {
                    unsigned x = ml.y ^ t8;
#pragma unroll
                    for (int i = 0; i < 8; i++) x |= v[i].x ^ t8;
                    if (!__any_sync(0xffffffffu, x & 0xffu)) break;
                    if (it > SPIN_MAX) __trap();
                    ml = ld_b64(mlp);
#pragma unroll
                    for (int i = 0; i < 8; i++)
                        if ((v[i].x & 0xffu) != t8) v[i] = ld_b128(src + i * 32);
                }
                TR(2);
                const float mw = warp_max(__uint_as_float(ml.x)), e = ex2((__uint_as_float(ml.x) - mw) * LOG2E);
                float L = e * __uint_as_float(ml.y), oa[4], ob[4];
                L += shx(L, 1);
#pragma unroll
                for (int i = 0; i < 8; i++) {
                    const float w = __shfl_sync(0xffffffffu, e, i);
                    float (&o)[4] = (i & 1) ? ob : oa;
                    o[0] = i < 2 ? w * __uint_as_float(v[i].x) : fmaf(w, __uint_as_float(v[i].x), o[0]);
                    o[1] = i < 2 ? w * __uint_as_float(v[i].y) : fmaf(w, __uint_as_float(v[i].y), o[1]);
                    o[2] = i < 2 ? w * __uint_as_float(v[i].z) : fmaf(w, __uint_as_float(v[i].z), o[2]);
                    o[3] = i < 2 ? w * __uint_as_float(v[i].w) : fmaf(w, __uint_as_float(v[i].w), o[3]);
                }
                float* fp = reinterpret_cast<float*>(sm + SC_FP) + ((step & 1) * 8 + (warp & 4)) * 132;
                *reinterpret_cast<float4*>(fp + (warp & 3) * 132 + lane * 4) = make_float4(oa[0] + ob[0], oa[1] + ob[1], oa[2] + ob[2], oa[3] + ob[3]);
                L += shx(L, 2);
                L += shx(L, 4);
                if (lane == 0) *reinterpret_cast<float2*>(fp + (warp & 3) * 132 + 128) = make_float2(mw, L);
                bar_sync(1 + (warp >> 2), 128);
                float2 q[4];
                float4 u[4];
#pragma unroll
                for (int w = 0; w < 4; w++) {
                    q[w] = *reinterpret_cast<const float2*>(fp + w * 132 + 128);
                    u[w] = *reinterpret_cast<const float4*>(fp + w * 132 + lane * 4);
                }
                const float MM = fmaxf(fmaxf(q[0].x, q[1].x), fmaxf(q[2].x, q[3].x));
                float f[4], inv;
#pragma unroll
                for (int w = 0; w < 4; w++) f[w] = ex2((q[w].x - MM) * LOG2E);
                asm("rcp.approx.ftz.f32 %0, %1;" : "=f"(inv) : "f"(fmaf(f[0], q[0].y, f[1] * q[1].y) + fmaf(f[2], q[2].y, f[3] * q[3].y)));
                const uint32_t b0 = packbf((fmaf(f[0], u[0].x, f[1] * u[1].x) + fmaf(f[2], u[2].x, f[3] * u[3].x)) * inv,
                                           (fmaf(f[0], u[0].y, f[1] * u[1].y) + fmaf(f[2], u[2].y, f[3] * u[3].y)) * inv);
                const uint32_t b1 = packbf((fmaf(f[0], u[0].z, f[1] * u[1].z) + fmaf(f[2], u[2].z, f[3] * u[3].z)) * inv,
                                           (fmaf(f[0], u[0].w, f[1] * u[1].w) + fmaf(f[2], u[2].w, f[3] * u[3].w)) * inv);
                if (step == ND) {
#pragma unroll
                    for (int ks = 0; ks < 4; ks++) mma16816(d[ks & 1], wf[ks], g == ks0 + ks ? b0 : 0u, g == ks0 + ks ? b1 : 0u);
                    const float x0 = (d[0][0] + d[0][1]) + (d[1][0] + d[1][1]), x1 = (d[0][2] + d[0][3]) + (d[1][2] + d[1][3]);
                    const float z = ((tq & 1) ? x1 : x0) + shx((tq & 1) ? x0 : x1, 1);
                    if ((tq & 2) == (warp & 2)) red[(6 + (tq >> 1)) * 80 + (warp >> 2) * 40 + (warp & 1) * 16 + (tq & 1) * 8 + g] = z;
                    bar_arrive(5, 480);
                    TR(5);
                    TROUT();
                    return;
                }
                bs[0] = b0; bs[1] = b1;
                if (!step && !(warp & 3)) st_b128(S->frag[1] + ((warp >> 2) * 32 + h) * 32 + lane, make_uint4(b0, tag, b1, 0));
                if (!isCA) break;
            } else {
#pragma unroll 1
                for (int y = y0 + ((warp - y0) & 3); y < y1 - 3 * isCA; y += 4) fetch_frag(y, warp >> 2, tag, CPOLL);
                TR(6);
                bar_arrive(4, 448);
            }
        }
        TROUT();
        return;
    }
    if (warp == 14) {
        bar_sync(6, 288);
        const CUtensorMap* map = &M.wo[isA];
        const unsigned tag = lds32(sb + SB_CNT) + 1;
        const uint32_t t8 = tag & 0xffu;
        uint2* const snd = S->snd + r * 32 + lane;
        asm volatile("prefetch.tensormap [%0];" ::"l"(map) : "memory");
        if (PLACE && !isC) st_b64(snd, t8 ^ 0x80u, 0);
        if (!isCA) for (int i = lane; i < 160; i += 32) red[480 + i] = 0.f;
        for (int it = 0; ld_b128(S->frag[1] + 25 * 32).y != tag; it++) {
            if (it > SPIN_MAX) __trap();
            __nanosleep(2000);
        }
        uint2 f;
        for (int it = 0;; it++) {
            f = ld_b64(S->fire + (lane & 1));
            if (__all_sync(0xffffffffu, f.y == tag)) break;
            if (it > SPIN_MAX) __trap();
            __nanosleep(FPOLL);
        }
        const unsigned t0 = __shfl_sync(0xffffffffu, f.x, 0);
        unsigned t1 = t0 + (__reduce_add_sync(0xffffffffu, (int)(f.x - t0)) >> 5) + FIRE_NS;
        TR(2);
        if (elect()) {
            const int n1 = nreq - (isC ? (isA ? NLA : NLB) : 0);
            const int dt = !isC ? (isA ? FIRE_W / NSA : FIRE_W / NSB) : isA ? FIRE_W / (32 - NSA - NLA) : FIRE_W / (32 - NSB - NLB);
            unsigned t2 = t1 + REC0_NS;
            int rec = isCA ? 2 : 0;
            int y = isCA ? 32 - ND : y0;
#pragma unroll 1
            for (int i = 0; i < nreq; i++) {
                const int row = y * 128;
                mbar_expect(bar_h + i * 16, 4096);
                mbar_expect(bar_h + i * 16 + 8, 4096);
                if (++y == 32) y = y0;
                if (i <= n1) {
                    unsigned t;
                    for (int it = 0; (int)((t = gt()) - t1) < 0 && it < 4096; it++) {}
                    t1 += dt;
                    if (rec && (int)(t - t2) >= 0) { mbar_arrive(sb + SB_BAR + --rec * 8); t2 += REC_NS - REC0_NS; }
                }
                tma2d(sb + i * 8192, map, cb * 32, row, bar_h + i * 16);
                tma2d(sb + i * 8192 + 4096, map, cb * 32, row + 64, bar_h + i * 16 + 8);
            }
            TR(3);
            while (rec) {
                for (int it = 0; (int)(gt() - t2) < 0 && it < 4096; it++) {}
                mbar_arrive(sb + SB_BAR + --rec * 8);
                t2 += REC_NS - REC0_NS;
            }
        }
        __syncwarp();
        uint2 o = make_uint2(0, 0);
        if (isC) {
            for (int it = 0;; it++) {
                o = ld_b64(snd);
                if (__all_sync(0xffffffffu, (o.x & 0xffu) == t8)) break;
                if (it > SPIN_MAX) __trap();
            }
        }
        TR(4);
        uint32_t* const dst = reinterpret_cast<uint32_t*>(P.out) + (lane >> 4) * 512 + (isA ? 0 : 256) + cb * 16 + (lane & 15);
        const float2* q = reinterpret_cast<const float2*>(red) + (lane >> 4) * 20 + (lane & 15);
        bar_sync(5, isCA ? 480 : 224);
        const float2 p0 = q[0], p1 = q[40], p2 = q[80], p3 = q[120], p4 = q[160], p5 = q[200], p6 = q[240], p7 = q[280];
        const float sx = (((p0.x + __uint_as_float(o.x)) + p1.x) + (p2.x + p3.x)) + ((p4.x + p5.x) + (p6.x + p7.x));
        const float sy = (((p0.y + __uint_as_float(o.y)) + p1.y) + (p2.y + p3.y)) + ((p4.y + p5.y) + (p6.y + p7.y));
        if (isC) *dst = packbf(sx, sy);
        else st_b64(snd, tagf(sx, t8), __float_as_uint(sy));
        TR(6);
        TROUT();
        return;
    }
    {
        constexpr int nw = 6;
        bar_sync(4, 448);
        const int yl = y1 - 1 - (y1 - 1 - y0 - (warp - 8)) % nw;
        if (isCA && yl >= y1 - 3) {
            const unsigned tag = lds32(sb + SB_CNT) + 1;
#pragma unroll 1
            for (int b = 0; b < 2; b++) fetch_frag(yl, b, tag, DPOLL);
            __syncwarp();
            TR(6);
        }
        float e[4][4];
#pragma unroll
        for (int i = 0; i < 4; i++) e[i][0] = e[i][1] = e[i][2] = e[i][3] = 0.f;
#pragma unroll 1
        for (int i = warp - 8 + ND * isCA; i < nreq; i += nw) {
            const uint32_t bp = sb + SC_FR + ((y0 + i - ND * isCA) * 32 + (lane & 7)) * 16;
            uint4 b[4];
#pragma unroll
            for (int j = 0; j < 4; j++) b[j] = lds128(bp + j * 128);
#pragma unroll
            for (int hf = 0; hf < 2; hf++) {
                uint32_t a[8][4];
                mbar_wait(bar_h + i * 16 + hf * 8, 0);
#pragma unroll
                for (int j = 0; j < 8; j++) ldsm4t(a[j], (wlane ^ ((j & 1) * 32)) + i * 8192 + hf * 4096 + (j >> 1) * 1024);
#pragma unroll
                for (int j = 0; j < 8; j++) {
                    const uint4& c = b[2 * hf + (j >> 2)];
                    mma16816(e[(j & 1) * 2 + ((j >> 1) & 1)], a[j], (j & 2) ? c.z : c.x, (j & 2) ? c.w : c.y);
                }
            }
        }
        float* rx = red + (warp - 8) * 80 + (tq & 1) * 40 + (tq >> 1) * 16 + g;
        float s4[4];
#pragma unroll
        for (int c = 0; c < 4; c++) s4[c] = (tq & 2) ? e[2][c] + e[3][c] : e[0][c] + e[1][c];
        rx[0] = (tq & 1) ? s4[1] : s4[0];
        rx[8] = (tq & 1) ? s4[3] : s4[2];
        bar_arrive(5, isCA ? 480 : 224);
        TROUT();
    }
}

typedef CUresult (*EncodeFn)(CUtensorMap*, CUtensorMapDataType, cuuint32_t, void*, const cuuint64_t*, const cuuint64_t*,
                             const cuuint32_t*, const cuuint32_t*, CUtensorMapInterleave, CUtensorMapSwizzle,
                             CUtensorMapL2promotion, CUtensorMapFloatOOBfill);

void make_map(EncodeFn enc, CUtensorMap* m, const void* base, uint64_t cols, uint64_t rows, uint32_t bc, uint32_t br,
              CUtensorMapL2promotion promo, CUtensorMapSwizzle sw = CU_TENSOR_MAP_SWIZZLE_128B) {
    cuuint64_t dims[2] = {cols, rows};
    cuuint64_t strides[1] = {cols * 2};
    cuuint32_t box[2] = {bc, br};
    cuuint32_t es[2] = {1, 1};
    enc(m, CU_TENSOR_MAP_DATA_TYPE_BFLOAT16, 2, const_cast<void*>(base), dims, strides, box, es,
        CU_TENSOR_MAP_INTERLEAVE_NONE, sw, promo, CU_TENSOR_MAP_FLOAT_OOB_FILL_NONE);
}

}

extern "C" void kernel_launch(void* const* d_in, const int* in_sizes, int n_in, void* d_out, int out_size) {
    (void)in_sizes; (void)n_in; (void)out_size;
    static EncodeFn enc = nullptr;
    static void* scr = nullptr;
    if (!enc) {
        void* fn = nullptr;
        cudaDriverEntryPointQueryResult qr;
        cudaGetDriverEntryPoint("cuTensorMapEncodeTiled", &fn, cudaEnableDefault, &qr);
        enc = (EncodeFn)fn;
        cudaGetSymbolAddress(&scr, g_scr);
        cudaFuncSetAttribute(fused_decode_kernel, cudaFuncAttributeMaxDynamicSharedMemorySize, SMEM_BYTES);
    }
    Maps m;
    make_map(enc, &m.kv[0], d_in[1], 64, 1048576, 64, 64, CU_TENSOR_MAP_L2_PROMOTION_NONE);
    make_map(enc, &m.kv[1], d_in[2], 64, 1048576, 64, 64, CU_TENSOR_MAP_L2_PROMOTION_NONE);
    make_map(enc, &m.qa, d_in[3], 4096, 512, 64, 64, CU_TENSOR_MAP_L2_PROMOTION_NONE);
    make_map(enc, &m.qb, d_in[7], 4096, 512, 64, 256, CU_TENSOR_MAP_L2_PROMOTION_L2_256B);
    make_map(enc, &m.wo[0], d_in[10], 512, 4096, 32, 64, WPROMO, CU_TENSOR_MAP_SWIZZLE_64B);
    make_map(enc, &m.wo[1], d_in[4], 512, 4096, 32, 64, WPROMO, CU_TENSOR_MAP_SWIZZLE_64B);
    {
        cuuint64_t dims[4] = {64, 8, 8, 2048}, strides[3] = {1024, 128, 8192};
        cuuint32_t box[4] = {64, 8, 8, 8}, es[4] = {1, 1, 1, 1};
        enc(&m.c, CU_TENSOR_MAP_DATA_TYPE_BFLOAT16, 4, d_in[6], dims, strides, box, es, CU_TENSOR_MAP_INTERLEAVE_NONE,
            CU_TENSOR_MAP_SWIZZLE_128B, CU_TENSOR_MAP_L2_PROMOTION_NONE, CU_TENSOR_MAP_FLOAT_OOB_FILL_NONE);
    }
    make_map(enc, &m.uk, d_in[8], 4096, 512, 64, 256, CU_TENSOR_MAP_L2_PROMOTION_L2_256B);
    make_map(enc, &m.uv, d_in[9], 4096, 512, 64, 256, CU_TENSOR_MAP_L2_PROMOTION_L2_256B);
    Params p;
    p.scr = (Scratch*)scr;
    p.ax = (const uint32_t*)d_in[0];
    p.bx = (const uint32_t*)d_in[5];
    p.out = (__nv_bfloat16*)d_out;
    p.wq = (const char*)d_in[3];
    fused_decode_kernel<<<128, 480, SMEM_BYTES, cudaStreamPerThread>>>(p, m);
}
```

```cpp
#include <cuda_runtime.h>
#include <cuda_bf16.h>
#include <cuda.h>
#include <stdint.h>
#include <float.h>

#define LIM 12
#define LIM0 8
#define RAMP_S 256
#define RAMP_T0 300
#define BAL 20
#define SKEW 3
#define ROT 128
#define FIRE_T 240
#define FIRE_NS 3300
#define FIRE_W 2050
#define NLA 6
#define NLB 8
#define NSA 13
#define NSB 13
#define REC_NS 1800
#define JMAP 2
#define WPROMO CU_TENSOR_MAP_L2_PROMOTION_L2_128B
#define REC0_NS 100
#define DPOLL 300
#define PFM 1
#define QPOLL 300
#define BSTAG 500
#define SPROMO CU_TENSOR_MAP_L2_PROMOTION_NONE
#define XD0 1000
#define XDS 12
#define XPM 15
#define XPOS 1
#define PLACE 1
#define BSTART 3000
#define QSLEEP 1500
#define BPOLL 1000
#define CPOLL 700
#define FPOLL 300

namespace {

constexpr int NG = 2, CPG = 32, NW = 4;
constexpr int UPG = 8192;
constexpr int NSL = 12, SPW = NSL / NW;
constexpr unsigned TICK_INC = UPG - NSL * CPG + NW * CPG;
constexpr int SPIN_MAX = 1 << 22;
constexpr float LOG2E = 1.4426950408889634f;
constexpr float SCALE = 0.08838834764831845f;
constexpr uint64_t EVICT_FIRST = 0x12F0000000000000ull;

constexpr int SA_SLOT = NSL * 16384;
constexpr int SA_Q    = SA_SLOT + 8 * NW * 132 * 4;
constexpr int SA_FULL = SA_Q + 8192;
constexpr int SA_EMPTY = SA_FULL + NSL * 16;
constexpr int SA_GOV  = SA_EMPTY + NSL * 8;
constexpr int SA_MBAR = SA_GOV + NSL * 8;
constexpr int SA_QBAR = SA_MBAR + 128;
constexpr int SA_META = SA_QBAR + 24;
constexpr int SA_LIM  = SA_META + NSL * 4;
constexpr int SA_CNT  = SA_LIM + 16;
constexpr int SA_END  = SA_CNT + 64;
constexpr int PROW    = 2080;
constexpr int SB_STG  = 0;
constexpr int SB_QIMG = 131072;
constexpr int SB_P    = SB_QIMG + 32 * PROW;
constexpr int SB_AL   = SB_P + 8192;
constexpr int SB_X    = SB_AL + 256;
static_assert(SB_P % 1024 == 0, "swizzle atom");
constexpr int SB_QB   = SB_X + 4352;
constexpr int NT      = 40;
constexpr int SC_FR   = NT * 4096;
constexpr int SC_FP   = SC_FR + 16384;
constexpr int SC_RED  = SB_QB + 1024;
constexpr int SB_BAR  = SC_RED + 2560;
constexpr int SB_CNT  = SB_BAR + (12 + NT) * 8;
static_assert(SC_FP + 8448 <= SB_P && 2 * (32 - NSA) <= NT && 2 * (32 - NSB) <= NT && NSA <= 16 && NSB <= 16, "projection slots");
constexpr int SB_END  = SB_CNT + 64;
constexpr int SMEM_BYTES = (SA_END > SB_END ? SA_END : SB_END);
static_assert(SMEM_BYTES <= 232448, "shared memory");

struct Scratch {
    uint4    bpart[32 * 32 * (PROW / 16)];
    uint4    apart[64 * CPG * 32];
    uint4    qimg[2 * 4096];
    uint4    qpub[64 * 32];
    uint4    frag[2][64 * 32];
    uint2    snd[32 * 32];
    uint2    aml[64 * CPG * 4];
    unsigned epoch[128 * 8];
    unsigned ctr[1088];
    uint2    fire[544];
    unsigned qflag[1088], bflag[1088];
};
__device__ __align__(1024) Scratch g_scr;

#define TRARG
#define TRPASS
#define TR(k)
#define TROUT()

__device__ __forceinline__ uint32_t s2u(const void* p) { return (uint32_t)__cvta_generic_to_shared(p); }
__device__ __forceinline__ bool elect() {
    uint32_t ok;
    asm volatile("{\n.reg .pred p;\nelect.sync _|p, 0xffffffff;\nselp.u32 %0,1,0,p;\n}" : "=r"(ok));
    return ok;
}
__device__ __forceinline__ void mbar_init(uint32_t b, int c) {
    asm volatile("mbarrier.init.shared::cta.b64 [%0], %1;" ::"r"(b), "r"(c) : "memory");
}
__device__ __forceinline__ void mbar_init_fence() { asm volatile("fence.mbarrier_init.release.cluster;" ::: "memory"); }
__device__ __forceinline__ void mbar_expect(uint32_t b, uint32_t bytes) {
    asm volatile("mbarrier.arrive.expect_tx.shared::cta.b64 _, [%0], %1;" ::"r"(b), "r"(bytes) : "memory");
}
__device__ __forceinline__ void mbar_arrive(uint32_t b) {
    asm volatile("mbarrier.arrive.shared::cta.b64 _, [%0];" ::"r"(b) : "memory");
}
__device__ __forceinline__ bool mbar_test(uint32_t b, uint32_t ph) {
    uint32_t ok;
    asm volatile("{\n.reg .pred p;\nmbarrier.test_wait.parity.shared::cta.b64 p, [%1], %2;\nselp.u32 %0,1,0,p;\n}"
                 : "=r"(ok) : "r"(b), "r"(ph) : "memory");
    return ok;
}
__device__ __forceinline__ void mbar_wait(uint32_t b, uint32_t ph) {
    asm volatile("{\n.reg .pred p;\n.reg .u32 n;\nmov.u32 n, 0;\n"
                 "W: mbarrier.try_wait.parity.shared::cta.b64 p, [%0], %1;\n@p bra.uni D;\n"
                 "add.u32 n, n, 1;\nsetp.lt.u32 p, n, %2;\n@p bra.uni W;\ntrap;\nD:\n}"
                 ::"r"(b), "r"(ph), "n"(SPIN_MAX) : "memory");
}
__device__ __forceinline__ void tma2d(uint32_t dst, const CUtensorMap* map, int c0, int c1, uint32_t bar) {
    asm volatile("cp.async.bulk.tensor.2d.shared::cluster.global.mbarrier::complete_tx::bytes [%0], [%1, {%3, %4}], [%2];"
                 ::"r"(dst), "l"(map), "r"(bar), "r"(c0), "r"(c1) : "memory");
}
__device__ __forceinline__ void tma2d_ef(uint32_t dst, const CUtensorMap* map, int c0, int c1, uint32_t bar) {
    asm volatile("cp.async.bulk.tensor.2d.shared::cluster.global.mbarrier::complete_tx::bytes.L2::cache_hint [%0], [%1, {%3, %4}], [%2], %5;"
                 ::"r"(dst), "l"(map), "r"(bar), "r"(c0), "r"(c1), "l"(EVICT_FIRST) : "memory");
}
__device__ __forceinline__ void tma4d_ef(uint32_t dst, const CUtensorMap* map, int c3, uint32_t bar) {
    asm volatile("cp.async.bulk.tensor.4d.shared::cluster.global.mbarrier::complete_tx::bytes.L2::cache_hint [%0], [%1, {0, 0, 0, %3}], [%2], %4;"
                 ::"r"(dst), "l"(map), "r"(bar), "r"(c3), "l"(EVICT_FIRST) : "memory");
}
__device__ __forceinline__ void bulk_g2s(uint32_t dst, const void* src, uint32_t bytes, uint32_t bar) {
    asm volatile("cp.async.bulk.shared::cluster.global.mbarrier::complete_tx::bytes [%0], [%1], %2, [%3];"
                 ::"r"(dst), "l"(src), "r"(bytes), "r"(bar) : "memory");
}
__device__ __forceinline__ void bulk_s2g(void* dst, uint32_t src, uint32_t bytes) {
    asm volatile("cp.async.bulk.global.shared::cta.bulk_group [%0], [%1], %2;" ::"l"(dst), "r"(src), "r"(bytes) : "memory");
}
__device__ __forceinline__ void fence_async_all() { asm volatile("fence.proxy.async;" ::: "memory"); }
__device__ __forceinline__ void bar_sync(int id, int n) { asm volatile("bar.sync %0, %1;" ::"r"(id), "r"(n) : "memory"); }
__device__ __forceinline__ void bar_arrive(int id, int n) { asm volatile("bar.arrive %0, %1;" ::"r"(id), "r"(n) : "memory"); }
__device__ __forceinline__ unsigned ld_relaxed1(const void* p) {
    unsigned v;
    asm volatile("ld.relaxed.gpu.global.u32 %0, [%1];" : "=r"(v) : "l"(p) : "memory");
    return v;
}
__device__ __forceinline__ unsigned atom_inc(unsigned* p) {
    unsigned v;
    asm volatile("atom.relaxed.gpu.global.add.u32 %0, [%1], 1;" : "=r"(v) : "l"(p) : "memory");
    return v;
}
__device__ __forceinline__ uint4 ld_b128(const void* p) {
    uint4 v;
    asm volatile("{\n.reg .b128 t;\nld.relaxed.gpu.global.b128 t, [%4];\nmov.b128 {%0,%1,%2,%3}, t;\n}"
                 : "=r"(v.x), "=r"(v.y), "=r"(v.z), "=r"(v.w) : "l"(p) : "memory");
    return v;
}
__device__ __forceinline__ void st_b128(void* p, uint4 v) {
    asm volatile("{\n.reg .b128 t;\nmov.b128 t, {%1,%2,%3,%4};\nst.relaxed.gpu.global.b128 [%0], t;\n}"
                 ::"l"(p), "r"(v.x), "r"(v.y), "r"(v.z), "r"(v.w) : "memory");
}
__device__ __forceinline__ uint2 ld_b64(const void* p) {
    uint2 v;
    asm volatile("{\n.reg .b64 a;\nld.relaxed.gpu.global.b64 a, [%2];\nmov.b64 {%0,%1}, a;\n}" : "=r"(v.x), "=r"(v.y) : "l"(p) : "memory");
    return v;
}
__device__ __forceinline__ void st_b64(void* p, uint32_t a, uint32_t b) {
    asm volatile("{\n.reg .b64 t;\nmov.b64 t, {%1,%2};\nst.relaxed.gpu.global.b64 [%0], t;\n}" ::"l"(p), "r"(a), "r"(b) : "memory");
}
__device__ __forceinline__ unsigned ld_acquire(const unsigned* p) {
    unsigned v;
    asm volatile("ld.acquire.gpu.global.u32 %0, [%1];" : "=r"(v) : "l"(p) : "memory");
    return v;
}
__device__ __forceinline__ void st_release(unsigned* p, unsigned v) {
    asm volatile("st.release.gpu.global.u32 [%0], %1;" ::"l"(p), "r"(v) : "memory");
}
__device__ __forceinline__ void ldsm4(uint32_t (&r)[4], uint32_t a) {
    asm volatile("ldmatrix.sync.aligned.m8n8.x4.shared.b16 {%0,%1,%2,%3}, [%4];"
                 : "=r"(r[0]), "=r"(r[1]), "=r"(r[2]), "=r"(r[3]) : "r"(a) : "memory");
}
__device__ __forceinline__ void ldsm4t(uint32_t (&r)[4], uint32_t a) {
    asm volatile("ldmatrix.sync.aligned.m8n8.x4.trans.shared.b16 {%0,%1,%2,%3}, [%4];"
                 : "=r"(r[0]), "=r"(r[1]), "=r"(r[2]), "=r"(r[3]) : "r"(a) : "memory");
}
__device__ __forceinline__ uint4 lds128(uint32_t a) {
    uint4 v;
    asm volatile("ld.shared.v4.u32 {%0, %1, %2, %3}, [%4];" : "=r"(v.x), "=r"(v.y), "=r"(v.z), "=r"(v.w) : "r"(a) : "memory");
    return v;
}
__device__ __forceinline__ uint32_t lds32(uint32_t a) {
    uint32_t v;
    asm volatile("ld.shared.u32 %0, [%1];" : "=r"(v) : "r"(a) : "memory");
    return v;
}
__device__ __forceinline__ void sts32(uint32_t a, uint32_t v) { asm volatile("st.shared.u32 [%0], %1;" ::"r"(a), "r"(v) : "memory"); }
__device__ __forceinline__ void mma16816(float (&d)[4], const uint32_t (&a)[4], uint32_t b0, uint32_t b1) {
    asm volatile("mma.sync.aligned.m16n8k16.row.col.f32.bf16.bf16.f32 {%0,%1,%2,%3}, {%4,%5,%6,%7}, {%8,%9}, {%0,%1,%2,%3};"
                 : "+f"(d[0]), "+f"(d[1]), "+f"(d[2]), "+f"(d[3])
                 : "r"(a[0]), "r"(a[1]), "r"(a[2]), "r"(a[3]), "r"(b0), "r"(b1));
}
__device__ __forceinline__ uint32_t prmt0(uint32_t a, uint32_t sel) {
    uint32_t d;
    asm volatile("prmt.b32 %0, %1, 0, %2;" : "=r"(d) : "r"(a), "r"(sel));
    return d;
}
__device__ __forceinline__ unsigned gt() {
    unsigned t;
    asm volatile("mov.u32 %0, %globaltimer_lo;" : "=r"(t));
    return t;
}
__device__ __forceinline__ unsigned clk32() {
    unsigned c;
    asm volatile("mov.u32 %0, %clock;" : "=r"(c));
    return c;
}
__device__ __forceinline__ float ex2(float x) {
    float y;
    asm("ex2.approx.ftz.f32 %0, %1;" : "=f"(y) : "f"(x));
    return y;
}
__device__ __forceinline__ float bf16r(float x) { return __bfloat162float(__float2bfloat16_rn(x)); }
__device__ __forceinline__ uint32_t packbf(float lo, float hi) {
    uint32_t r;
    asm("cvt.rn.bf16x2.f32 %0, %1, %2;" : "=r"(r) : "f"(hi), "f"(lo));
    return r;
}
__device__ __forceinline__ float bflo(uint32_t v) { return __uint_as_float(v << 16); }
__device__ __forceinline__ float bfhi(uint32_t v) { return __uint_as_float(v & 0xffff0000u); }
__device__ __forceinline__ uint32_t tagf(float v, uint32_t t8) { return (__float_as_uint(v) & 0xffffff00u) | t8; }
__device__ __forceinline__ float shx(float v, int m) { return __shfl_xor_sync(0xffffffffu, v, m); }

__device__ __forceinline__ float warp_max(float v) {
    int i = __float_as_int(v);
    i = __reduce_max_sync(0xffffffffu, i ^ ((i >> 31) & 0x7fffffff));
    return __int_as_float(i ^ ((i >> 31) & 0x7fffffff));
}

__device__ __forceinline__ uint64_t gdesc(uint32_t addr, uint32_t lbo, uint32_t sbo) {
    return (uint64_t)((addr & 0x3ffff) >> 4) | ((uint64_t)(lbo >> 4) << 16) | ((uint64_t)(sbo >> 4) << 32) | (1ull << 62);
}
__device__ __forceinline__ void wg_fence() { asm volatile("wgmma.fence.sync.aligned;" ::: "memory"); }
__device__ __forceinline__ void wg_commit() { asm volatile("wgmma.commit_group.sync.aligned;" ::: "memory"); }
__device__ __forceinline__ void wg_wait0() { asm volatile("wgmma.wait_group.sync.aligned 0;" ::: "memory"); }
template <int N> __device__ __forceinline__ void reg_fence(float (&r)[N]) {
#pragma unroll
    for (int i = 0; i < N; i++) asm volatile("" : "+f"(r[i])::"memory");
}
#define F8(a, o) "+f"(a[o]), "+f"(a[o + 1]), "+f"(a[o + 2]), "+f"(a[o + 3]), "+f"(a[o + 4]), "+f"(a[o + 5]), "+f"(a[o + 6]), "+f"(a[o + 7])
#define F32(a, o) F8(a, o), F8(a, o + 8), F8(a, o + 16), F8(a, o + 24)
__device__ __forceinline__ void wgmma_n64_ss(float (&d)[32], uint64_t da, uint64_t db, int scale_d) {
    asm volatile(
        "{\n.reg .pred p;\nsetp.ne.b32 p, %34, 0;\n"
        "wgmma.mma_async.sync.aligned.m64n64k16.f32.bf16.bf16 "
        "{%0,%1,%2,%3,%4,%5,%6,%7,%8,%9,%10,%11,%12,%13,%14,%15,%16,%17,%18,%19,%20,%21,%22,%23,%24,%25,%26,%27,%28,%29,%30,%31},"
        " %32, %33, p, 1, 1, 0, 0;\n}"
        : F32(d, 0) : "l"(da), "l"(db), "r"(scale_d));
}
__device__ __forceinline__ void wgmma_n32_ts(float (&d)[16], uint64_t da, uint64_t db) {
    asm volatile(
        "{\n.reg .pred p;\nsetp.ne.b32 p, 1, 0;\n"
        "wgmma.mma_async.sync.aligned.m64n32k16.f32.bf16.bf16 "
        "{%0,%1,%2,%3,%4,%5,%6,%7,%8,%9,%10,%11,%12,%13,%14,%15}, %16, %17, p, 1, 1, 1, 0;\n}"
        : F8(d, 0), F8(d, 8) : "l"(da), "l"(db));
}

struct Params {
    Scratch* scr;
    const uint32_t *ax, *bx;
    const char* wq;
    __nv_bfloat16* out;
};
struct Maps { CUtensorMap kv[2], qa, qb, wo[2], c, uk, uv; };

__device__ __forceinline__ void wait_flags(const unsigned* flags, unsigned tag, int lane) {
    for (int i = 0; !__all_sync(0xffffffffu, ld_acquire(flags + lane) == tag); i++) {
        if (i > SPIN_MAX) __trap();
        __nanosleep(BPOLL);
    }
}
__device__ __forceinline__ void load_slice(uint32_t dst, const CUtensorMap* map, int r, uint32_t bar) {
    mbar_expect(bar, 131072);
#pragma unroll
    for (int x = 0; x < 4; x++) tma2d(dst + x * 32768, map, r * 128 + (x & 1) * 64, (x >> 1) * 256, bar);
}
__device__ __forceinline__ void gemv_slice(uint32_t sb, int warp, int lane) {
    const int g = lane >> 2, tq = lane & 3;
    float d[4][4];
#pragma unroll
    for (int i = 0; i < 4; i++) d[i][0] = d[i][1] = d[i][2] = d[i][3] = 0.f;
    const uint32_t wb = sb + SB_STG + (warp >> 2) * 32768 + ((lane & 7) + 8 * (lane >> 4)) * 128 +
                        (((2 * (warp & 3) + ((lane >> 3) & 1)) ^ (lane & 7)) << 4);
    const uint32_t xb = sb + SB_X + ((g & 3) * 264 + tq) * 4;
#pragma unroll 1
    for (int k8 = 0; k8 < 4; k8++) {
        uint32_t a[8][4], b[8][2];
#pragma unroll
        for (int ks = 0; ks < 8; ks++) {
            ldsm4t(a[ks], wb + (k8 >> 1) * 65536 + (k8 & 1) * 16384 + ks * 2048);
            b[ks][0] = lds32(xb + k8 * 256 + ks * 32);
            b[ks][1] = lds32(xb + k8 * 256 + ks * 32 + 16);
        }
#pragma unroll
        for (int ks = 0; ks < 8; ks++) mma16816(d[ks & 3], a[ks], b[ks][0], b[ks][1]);
    }
    const float y0 = ((d[0][0] + d[1][0]) + (d[2][0] + d[3][0])) + ((d[0][1] + d[1][1]) + (d[2][1] + d[3][1]));
    const float y1 = ((d[0][2] + d[1][2]) + (d[2][2] + d[3][2])) + ((d[0][3] + d[1][3]) + (d[2][3] + d[3][3]));
    if (tq < 2) {
        sts32(sb + SB_QB + (tq * 128 + warp * 16 + g) * 4, __float_as_uint(y0));
        sts32(sb + SB_QB + (tq * 128 + warp * 16 + 8 + g) * 4, __float_as_uint(y1));
    }
}
__device__ __forceinline__ uint32_t wo_lane(uint32_t sb, int lane) {
    return sb + ((lane & 7) + 8 * (lane >> 4)) * 64 + ((((lane >> 3) & 1) ^ ((lane >> 1) & 3)) << 4);
}

__device__ __forceinline__ void latent_branch(const Params& P, const Maps& M, uint8_t* sm TRARG) {
    const uint32_t sb = s2u(sm);
    const int tid = threadIdx.x, lane = tid & 31, warp = tid >> 5, g = lane >> 2, tq = lane & 3, r = blockIdx.x >> 2;
    const uint32_t bar_w = sb + SB_BAR + 16, bar_x = sb + SB_BAR + 24;
    const unsigned tag = lds32(sb + SB_CNT) + 1;
    Scratch* const S = P.scr;
    const float* yb = reinterpret_cast<const float*>(sm + SB_QB);
    {
        float* xs = reinterpret_cast<float*>(sm + SB_X);
        const int crow0 = (r >> 4) * 8192 + (r & 15) * 64;
        {
            uint32_t* xh = reinterpret_cast<uint32_t*>(sm + SB_X) + tid;
            xh[0] = __ldg(P.bx + tid); xh[264] = 0; xh[528] = __ldg(P.bx + 256 + tid); xh[792] = 0;
            bar_sync(0, 256);
            mbar_wait(bar_w, 0);
            TR(0);
            gemv_slice(sb, warp, lane);
            bar_sync(0, 256);
            if (tid == 0) load_slice(sb + SB_STG, &M.uk, r, bar_w);
            uint32_t qb[8][2];
#pragma unroll
            for (int ks = 0; ks < 8; ks++) {
                const float2 a = *reinterpret_cast<const float2*>(yb + (g & 1) * 128 + ks * 16 + 2 * tq);
                const float2 b = *reinterpret_cast<const float2*>(yb + (g & 1) * 128 + ks * 16 + 8 + 2 * tq);
                qb[ks][0] = packbf(a.x, a.y);
                qb[ks][1] = packbf(b.x, b.y);
            }
            mbar_wait(bar_w, 1);
            const uint32_t wb = sb + SB_STG + (warp >> 2) * 65536 + ((warp & 3) * 64 + (lane & 15)) * 128;
#pragma unroll 1
            for (int mt = 0; mt < 4; mt++) {
                float d[4] = {0.f, 0.f, 0.f, 0.f};
#pragma unroll
                for (int ks = 0; ks < 8; ks++) {
                    uint32_t a[4];
                    ldsm4(a, wb + (ks >> 2) * 32768 + mt * 2048 + (((2 * (ks & 3) + (lane >> 4)) ^ (lane & 7)) << 4));
                    mma16816(d, a, qb[ks][0], qb[ks][1]);
                }
                if (tq == 0) {
                    const int c = warp * 64 + mt * 16 + g;
                    xs[c] = d[0]; xs[512 + c] = d[1]; xs[c + 8] = d[2]; xs[512 + c + 8] = d[3];
                }
            }
            bar_sync(0, 256);
            if (tid == 32) {
#pragma unroll
                for (int t = 0; t < 2; t++) {
                    mbar_expect(sb + SB_BAR + t * 8, 65536);
                    tma4d_ef(sb + SB_STG + t * 65536, &M.c, (crow0 >> 3) + t * 128, sb + SB_BAR + t * 8);
                }
            }
            const int b = tid >> 7, lo = (tid >> 6) & 1, ch = tid & 63;
            float v[8];
#pragma unroll
            for (int i = 0; i < 8; i++) {
                const float x = xs[b * 512 + ch * 8 + i];
                v[i] = lo ? x - bf16r(x) : x;
            }
            const int row = 16 * (r >> 3) + (r & 7) + 8 * lo;
            S->qimg[b * 4096 + (ch >> 3) * 512 + row * 8 + ((ch & 7) ^ (r & 7))] =
                make_uint4(packbf(v[0], v[1]), packbf(v[2], v[3]), packbf(v[4], v[5]), packbf(v[6], v[7]));
            bar_sync(0, 256);
            if (warp == 0) {
                if (lane == 0) { __threadfence(); st_release(S->qflag + r, tag); }
                wait_flags(S->qflag, tag, lane);
                if (lane == 0) {
                    fence_async_all();
                    mbar_expect(bar_x, 65536);
                    bulk_g2s(sb + SB_QIMG, S->qimg + (r >> 4) * 4096, 65536, bar_x);
                }
            }
            mbar_wait(bar_x, 0);
        }
        TR(1);
        {
            const int wg = warp >> 2;
            float acc[4][16];
#pragma unroll
            for (int i = 0; i < 64; i++) acc[i >> 4][i & 15] = 0.f;
            const int head = (warp & 3) * 8 + g;
            const uint32_t pa = sb + SB_P + wg * 4096;
            float* al = reinterpret_cast<float*>(sm + SB_AL) + wg * 32;
            float m = -FLT_MAX, l = 0.f;
#pragma unroll 1
            for (int t = 0; t < 8; t++) {
                const uint32_t stg = sb + SB_STG + (t & 1) * 65536;
                mbar_wait(sb + SB_BAR + (t & 1) * 8, (t >> 1) & 1);
                float s[32];
                uint32_t qa = sb + SB_QIMG;
                asm volatile("" : "+r"(qa));
                wg_fence();
#pragma unroll
                for (int k = 0; k < 32; k++) {
                    const uint32_t off = (k >> 2) * 8192 + (k & 3) * 32;
                    wgmma_n64_ss(s, gdesc(qa + off, 16, 1024), gdesc(stg + (k >> 2) * 1024 + (k & 3) * 32, 16, 8192), k > 0);
                }
                wg_commit();
                wg_wait0();
                reg_fence(s);
                float p[16], mx = m;
#pragma unroll
                for (int i = 0; i < 8; i++) {
                    p[2 * i] = bf16r(bf16r(s[4 * i] + s[4 * i + 2]) * SCALE);
                    p[2 * i + 1] = bf16r(bf16r(s[4 * i + 1] + s[4 * i + 3]) * SCALE);
                    mx = fmaxf(mx, fmaxf(p[2 * i], p[2 * i + 1]));
                }
                mx = fmaxf(mx, shx(mx, 1));
                mx = fmaxf(mx, shx(mx, 2));
                const float alpha = ex2((m - mx) * LOG2E);
                m = mx;
                float sum = 0.f;
#pragma unroll
                for (int i = 0; i < 8; i++) {
                    const float a = ex2((p[2 * i] - mx) * LOG2E), b = ex2((p[2 * i + 1] - mx) * LOG2E);
                    sum += a + b;
                    sts32(pa + head * 128 + ((i ^ g) << 4) + tq * 4, packbf(a, b));
                }
                l = fmaf(l, alpha, sum);
                if (tq == 0) al[head] = alpha;
                asm volatile("fence.proxy.async.shared::cta;" ::: "memory");
                bar_sync(1 + wg, 128);
#pragma unroll
                for (int j = 0; j < 4; j++) {
                    const float2 a = *reinterpret_cast<const float2*>(al + 8 * j + 2 * tq);
#pragma unroll
                    for (int i = 0; i < 4; i++) { acc[i][4 * j] *= a.x; acc[i][4 * j + 1] *= a.y; acc[i][4 * j + 2] *= a.x; acc[i][4 * j + 3] *= a.y; }
                }
#pragma unroll
                for (int i = 0; i < 4; i++) reg_fence(acc[i]);
                wg_fence();
#pragma unroll
                for (int kk = 0; kk < 4; kk++)
#pragma unroll
                    for (int i = 0; i < 4; i++)
                        wgmma_n32_ts(acc[i], gdesc(stg + (wg * 4 + i) * 1024 + kk * 16384, 1024, 8192), gdesc(pa + kk * 32, 16, 1024));
                wg_commit();
                wg_wait0();
#pragma unroll
                for (int i = 0; i < 4; i++) reg_fence(acc[i]);
                bar_sync(0, 256);
                if (tid == 0) {
                    if (t + 2 < 8) {
                        const uint32_t bar = sb + SB_BAR + (t & 1) * 8;
                        mbar_expect(bar, 65536);
                        tma4d_ef(stg, &M.c, (crow0 >> 3) + (t + 2) * 128, bar);
                    }
                    if (t == 7) load_slice(sb + SB_STG, &M.uv, r, bar_w);
                }
            }
            TR(2);
            float* dst = reinterpret_cast<float*>(sm + SB_QIMG + 2 * tq * PROW) + wg * 256 + (warp & 3) * 16 + g;
#pragma unroll
            for (int i = 0; i < 64; i++)
                dst[(((i >> 2) & 3) * 8 + (i & 1)) * (PROW / 4) + (i >> 4) * 64 + (i & 2) * 4] = acc[i >> 4][i & 15];
            l += shx(l, 1); l += shx(l, 2);
            if (wg == 0 && tq < 2) *reinterpret_cast<float4*>(sm + SB_QIMG + head * PROW + 2048 + tq * 16) = make_float4(m, l, 0.f, 0.f);
            asm volatile("fence.proxy.async.shared::cta;" ::: "memory");
            bar_sync(0, 256);
            if (warp == 0) {
                bulk_s2g(S->bpart + (lane * 32 + r) * (PROW / 16), sb + SB_QIMG + lane * PROW, PROW);
                asm volatile("cp.async.bulk.commit_group;" ::: "memory");
                asm volatile("cp.async.bulk.wait_group 0;" ::: "memory");
                fence_async_all();
                __threadfence();
                __syncwarp();
                if (lane == 0) st_release(S->bflag + r, tag);
                wait_flags(S->bflag, tag, lane);
                if (lane == 0) {
                    fence_async_all();
                    mbar_expect(bar_x, 32 * PROW);
                    bulk_g2s(sb + SB_QIMG, S->bpart + r * 32 * (PROW / 16), 32 * PROW, bar_x);
                }
            }
        }
        {
            const int b = tid >> 7, c4 = tid & 127;
            mbar_wait(bar_x, 1);
            TR(3);
            const float2 ml = *reinterpret_cast<const float2*>(sm + SB_QIMG + (b * 16 + (lane & 15)) * PROW + 2048);
            float MM = ml.x;
            MM = fmaxf(MM, shx(MM, 1)); MM = fmaxf(MM, shx(MM, 2)); MM = fmaxf(MM, shx(MM, 4)); MM = fmaxf(MM, shx(MM, 8));
            const float e = ex2((ml.x - MM) * LOG2E);
            float L = e * ml.y;
            L += shx(L, 1); L += shx(L, 2); L += shx(L, 4); L += shx(L, 8);
            const float wgt = e / L;
            float4 o = make_float4(0.f, 0.f, 0.f, 0.f);
#pragma unroll 4
            for (int i = 0; i < 16; i++) {
                const float w = __shfl_sync(0xffffffffu, wgt, i);
                const float4 v = *reinterpret_cast<const float4*>(sm + SB_QIMG + (b * 16 + i) * PROW + c4 * 16);
                o.x = fmaf(w, v.x, o.x); o.y = fmaf(w, v.y, o.y); o.z = fmaf(w, v.z, o.z); o.w = fmaf(w, v.w, o.w);
            }
            uint32_t* xh = reinterpret_cast<uint32_t*>(xs);
            const uint32_t h0 = packbf(o.x, o.y), h1 = packbf(o.z, o.w);
            *reinterpret_cast<uint2*>(xh + (2 * b) * 264 + c4 * 2) = make_uint2(h0, h1);
            *reinterpret_cast<uint2*>(xh + (2 * b + 1) * 264 + c4 * 2) =
                make_uint2(packbf(o.x - bflo(h0), o.y - bfhi(h0)), packbf(o.z - bflo(h1), o.w - bfhi(h1)));
            bar_sync(0, 256);
            mbar_wait(bar_w, 0);
            gemv_slice(sb, warp, lane);
            bar_sync(0, 256);
            if (tid < 64) {
                const float* y = yb + warp * 128 + 16 * g + 2 * tq;
                st_b128(S->frag[0] + (warp * 32 + r) * 32 + lane, make_uint4(packbf(y[0], y[1]), tag, packbf(y[8], y[9]), tag));
            }
        }
        TR(4);
    }
}

__global__ void __launch_bounds__(480, 1)
fused_decode_kernel(const Params P, const __grid_constant__ Maps M) {
    extern __shared__ __align__(1024) uint8_t sm[];
    const uint32_t sb = s2u(sm);
    const int tid = threadIdx.x, lane = tid & 31, bx = blockIdx.x;
    asm volatile("{\n.reg .pred p;\nsetp.lt.u32 p, %1, 256;\n@p prefetch.global.L2 [%0];\n}"
                 ::"l"(P.wq + (PFM ? (unsigned)(((bx & 1) * 256 + tid) * 8192 + (bx >> 1) * 128) : (unsigned)(bx * 32768 + tid * 128))), "r"(tid) : "memory");
    const int warp = __shfl_sync(0xffffffffu, tid >> 5, 0);
    const int g = lane >> 2, tq = lane & 3;
    Scratch* const S = P.scr;

    if (!(bx & 1)) {
        const int grp = (bx >> 1) & 1, crk = bx >> 2;
        const int rowbase = grp * (UPG * 64);
        auto issue = [&](int slot, unsigned tk, int v) {
            const int row = rowbase + (int)((tk & ~255u) | ((tk + grp * ROT) & 255u)) * 64;
            const uint32_t full = sb + SA_FULL + slot * 16 + v * 8;
            mbar_expect(full, 8192);
            tma2d_ef(sb + slot * 16384 + v * 8192, &M.kv[v], 0, row, full);
        };
        if (warp >= 8) {
            const int w = warp - 8;
            if (w >= NW) {
                if (w == NW && !(bx & XPM)) asm volatile("prefetch.global.L2 [%0];" ::"l"(((lane & 16) ? P.bx : P.ax) + (lane & 15) * 32) : "memory");
                return;
            }
            const bool one = elect();
            if (one) {
                mbar_init(sb + SA_FULL + w * 16, 1);
                mbar_init_fence();
                TR(3);
                sts32(sb + SA_META + w * 4, 0);
                if (w < SKEW) issue(w, w * CPG + crk, 0);
#pragma unroll
                for (int i = 0; i < SPW; i++) {
                    if (i) mbar_init(sb + SA_FULL + (w + i * NW) * 16, 1);
                    mbar_init(sb + SA_FULL + (w + i * NW) * 16 + 8, 1);
                    mbar_init(sb + SA_GOV + (w + i * NW) * 8, 1);
                    mbar_init(sb + SA_EMPTY + (w + i * NW) * 8, 2);
                    mbar_arrive(sb + SA_EMPTY + (w + i * NW) * 8);
                }
                if (w < SKEW) mbar_arrive(sb + SA_EMPTY + w * 8);
                sts32(sb + SA_LIM + w * 4, LIM);
                mbar_init_fence();
            }
            __syncwarp();
            bar_arrive(2, (NW + 1) * 32);
            bar_arrive(1, (2 * NW + 2) * 32);
            unsigned c = 0, tbase = 0;
            int slot = w;
            uint32_t eph = 0;
#pragma unroll 1
            for (int n = 0;; n++) {
                unsigned tk = (n * NW + w) * CPG + crk;
                if (n == SPW) {
                    mbar_wait(sb + SA_EMPTY + w * 8, 1);
                    tbase = NSL * CPG - lds32(sb + SA_CNT) * TICK_INC;
                }
                if (n >= SPW) {
                    const unsigned own = __shfl_sync(0xffffffffu, c, grp);
                    tk = own + tbase;
                    const int lag = (int)(__reduce_add_sync(0xffffffffu, c) - NG * own);
                    if (one) sts32(sb + SA_LIM + w * 4, lag > BAL * NG ? LIM + 1 : lag < -BAL * NG ? LIM - 1 : LIM);
                }
                mbar_wait(sb + SA_EMPTY + slot * 8, eph);
                if (tk >= UPG) {
                    if (one) { sts32(sb + SA_LIM + w * 4, 0); sts32(sb + SA_META + slot * 4, 32); mbar_arrive(sb + SA_FULL + slot * 16); }
                    return;
                }
                if (one && (n || w >= SKEW)) {
                    sts32(sb + SA_META + slot * 4, tk >> 8);
                    issue(slot, tk, 0);
                    if (tk == 1200) TR(6);
                    if (tk == UPG - FIRE_T) { st_b64(S->fire + grp, gt(), lds32(sb + SA_CNT) + 1); TR(4); }
                }
                if (n >= SPW - 1) {
                    if (lane == grp) c = atom_inc(S->ctr + lane);
                    else if (lane < NG) c = ld_relaxed1(S->ctr + lane);
                }
                mbar_wait(sb + SA_GOV + slot * 8, eph);
                if (one) issue(slot, tk, 1);
                TR(0);
                slot += NW;
                if (slot >= NSL) { slot -= NSL; eph ^= 1; }
                __syncwarp();
            }
        }
        if (warp == 0) {
            bool busy = lane < 2 * SKEW && !(lane & 1);
            uint32_t par = busy ? 0 : 1;
            int slot = SKEW;
            bool first = true;
            const unsigned c0 = clk32() + RAMP_T0;
            const int own = lane >= 2 * NSL ? -1 : ((lane >> 1) + (lane & 1) * SKEW) % NSL;
            const uint32_t fb = sb + SA_FULL + lane * 8, lw = sb + SA_LIM + ((lane >> 1) % NW) * 4;
            const uint32_t go = sb + ((lane & 1) ? SA_GOV : SA_EMPTY) + (lane >> 1) * 8;
            bar_sync(2, (NW + 1) * 32);
#pragma unroll 1
            for (int it = 0; it < SPIN_MAX; it++) {
                bool ok = true;
                if (busy) ok = mbar_test(fb, par);
                int lim = lds32(lw);
                if (first) lim = min(LIM0, SKEW + max((int)(clk32() - c0), 0) / RAMP_S);
                busy = busy && !ok && lim;
                const int n = __popc(__ballot_sync(0xffffffffu, busy));
                if (!__any_sync(0xffffffffu, lim)) return;
                const bool mine = own == slot && lim;
                if (!__any_sync(0xffffffffu, mine && (busy || n > lim - 2))) {
                    if (mine) { mbar_arrive(go); busy = true; par ^= 1; }
                    if (++slot == NSL) { slot = 0; first = false; }
                    it = 0;
                }
            }
            __trap();
        }
        {
            int w3 = warp;
            asm volatile("" : "+r"(w3));
            if (w3 == 3) return;
        }
        if (warp == 1) {
            const uint4* const qsrc = S->qpub + grp * 1024 + lane;
            uint2* const qdst = reinterpret_cast<uint2*>(sm + SA_Q) + lane;
            const unsigned epoch = ld_relaxed1(S->epoch + bx * 8);
            if (lane == 0) {
                mbar_init(sb + SA_QBAR, 32);
                mbar_init(sb + SA_QBAR + 8, 32);
                mbar_init(sb + SA_QBAR + 16, 32);
#pragma unroll
                for (int i = 0; i < 8; i++) { mbar_init(sb + SA_MBAR + i * 16, NW); mbar_init(sb + SA_MBAR + i * 16 + 8, 1); }
                mbar_init_fence();
                sts32(sb + SA_CNT, epoch);
            }
            __syncwarp();
            bar_arrive(1, (2 * NW + 2) * 32);
            if (lane == 0) S->epoch[bx * 8] = epoch + 1;
            __nanosleep(QSLEEP);
            for (int it = 0;; it++) {
                const uint4 u = ld_b128(qsrc);
                if (__all_sync(0xffffffffu, u.y == epoch + 1)) { qdst[0] = make_uint2(u.x, u.z); break; }
                if (it > SPIN_MAX) __trap();
            }
            mbar_arrive(sb + SA_QBAR);
#pragma unroll 1
            for (int h = 0, it = 0; h < 32; it++) {
                uint4 v[8];
                bool ok = true;
#pragma unroll
                for (int k = 0; k < 8; k++) v[k] = ld_b128(qsrc + (h + k) * 32);
#pragma unroll
                for (int k = 0; k < 8; k++) { ok = ok && v[k].y == epoch + 1; qdst[(h + k) * 32] = make_uint2(v[k].x, v[k].z); }
                if (__all_sync(0xffffffffu, ok)) {
                    if (!h) mbar_arrive(sb + SA_QBAR + 8);
                    h += 8;
                } else if (QPOLL) __nanosleep(QPOLL);
                if (it > SPIN_MAX) __trap();
            }
            mbar_arrive(sb + SA_QBAR + 16);
            return;
        }
        bar_sync(1, (2 * NW + 2) * 32);
        if (warp == 2) {
            const uint32_t t8 = (lds32(sb + SA_CNT) + 1) & 0xffu;
            uint4* dst = S->apart + (grp * 32 * CPG + crk) * 32 + lane;
            uint2* dml = S->aml + (grp * 32 * CPG + crk) * 4 + (lane & 3);
#pragma unroll 1
            for (int h = 0; h < 32; h++, dst += CPG * 32, dml += CPG * 4) {
                const float* s0 = reinterpret_cast<const float*>(sm + SA_SLOT) + (h & 7) * (NW * 132);
                mbar_wait(sb + SA_MBAR + (h & 7) * 16, (h >> 3) & 1);
                float2 ml[NW];
                float4 v[NW];
#pragma unroll
                for (int w = 0; w < NW; w++) {
                    ml[w] = *reinterpret_cast<const float2*>(s0 + w * 132 + 128);
                    v[w] = *reinterpret_cast<const float4*>(s0 + w * 132 + lane * 4);
                }
                const float MM = fmaxf(fmaxf(ml[0].x, ml[1].x), fmaxf(ml[2].x, ml[3].x));
                float e[NW];
#pragma unroll
                for (int w = 0; w < NW; w++) e[w] = ex2((ml[w].x - MM) * LOG2E);
                st_b128(dst, make_uint4(tagf(fmaf(e[0], v[0].x, e[1] * v[1].x) + fmaf(e[2], v[2].x, e[3] * v[3].x), t8),
                                        __float_as_uint(fmaf(e[0], v[0].y, e[1] * v[1].y) + fmaf(e[2], v[2].y, e[3] * v[3].y)),
                                        __float_as_uint(fmaf(e[0], v[0].z, e[1] * v[1].z) + fmaf(e[2], v[2].z, e[3] * v[3].z)),
                                        __float_as_uint(fmaf(e[0], v[0].w, e[1] * v[1].w) + fmaf(e[2], v[2].w, e[3] * v[3].w))));
                if (lane < 4) st_b64(dml, __float_as_uint(MM), tagf(fmaf(e[0], ml[0].y, e[1] * ml[1].y) + fmaf(e[2], ml[2].y, e[3] * ml[3].y), t8));
                TR(2);
                if (PLACE && (h == 27 || h == 28)) {
                    st_b128(dst + 3 * CPG * 32, make_uint4(t8 ^ 0x80u, 0, 0, 0));
                    if (lane < 4) st_b64(dml + 3 * CPG * 4, 0, t8 ^ 0x80u);
                }
                __syncwarp();
                if (lane == 0) mbar_arrive(sb + SA_MBAR + (h & 7) * 16 + 8);
            }
            TROUT();
            return;
        }
        const int cw = warp - 4;
        uint32_t koff[4], voff[4];
#pragma unroll
        for (int i = 0; i < 4; i++) {
            koff[i] = ((lane & 7) + 8 * ((lane >> 3) & 1)) * 128 + (((2 * i + (lane >> 4)) ^ (lane & 7)) << 4);
            voff[i] = ((lane & 7) + 8 * (lane >> 4)) * 128 + (((2 * i + ((lane >> 3) & 1)) ^ (lane & 7)) << 4);
        }
        uint32_t psel[4][2];
#pragma unroll
        for (int i = 0; i < 4; i++) {
            psel[i][0] = (g >> 1) != i ? 0x4444u : (g & 1) ? 0x1044u : 0x4410u;
            psel[i][1] = (g >> 1) != i ? 0x4444u : (g & 1) ? 0x3244u : 0x4432u;
        }
        uint32_t qf[4][2];
        auto load_q = [&](int pl) {
            const uint32_t q = sb + SA_Q + pl * 256 + ((g & 1) * 32 + tq) * 4;
#pragma unroll
            for (int ks = 0; ks < 4; ks++) { qf[ks][0] = lds32(q + ks * 32); qf[ks][1] = lds32(q + ks * 32 + 16); }
        };
        mbar_wait(sb + SA_QBAR, 0);
        TR(0);
        load_q(0);
        float acc[4][4], m = -FLT_MAX, l = 0.f, ls = 0.f;
#pragma unroll
        for (int i = 0; i < 4; i++) acc[i][0] = acc[i][1] = acc[i][2] = acc[i][3] = 0.f;
        int slot = cw, cur = 0;
        uint32_t ph = 0;
#pragma unroll 1
        for (;;) {
            mbar_wait(sb + SA_FULL + slot * 16, ph);
            const int pl = lds32(sb + SA_META + slot * 4);
            if (pl != cur) {
#pragma unroll 1
                do {
                    float* s0 = reinterpret_cast<float*>(sm + SA_SLOT) + ((cur & 7) * NW + cw) * 132;
                    float* sw = s0 + tq * 16 + (g >> 1) * 4 + (g & 1);
                    sw[0] = (acc[0][0] + acc[1][0]) + (acc[2][0] + acc[3][0]);
                    sw[2] = (acc[0][2] + acc[1][2]) + (acc[2][2] + acc[3][2]);
                    sw[64] = (acc[0][1] + acc[1][1]) + (acc[2][1] + acc[3][1]);
                    sw[66] = (acc[0][3] + acc[1][3]) + (acc[2][3] + acc[3][3]);
                    if (lane == 0) *reinterpret_cast<float2*>(s0 + 128) = make_float2(m, ls);
                    __syncwarp();
                    if (lane == 0) mbar_arrive(sb + SA_MBAR + (cur & 7) * 16);
                    if (++cur == 32) { TROUT(); return; }
#pragma unroll
                    for (int i = 0; i < 4; i++) acc[i][0] = acc[i][1] = acc[i][2] = acc[i][3] = 0.f;
                    m = -FLT_MAX; l = ls = 0.f;
                    mbar_wait(sb + SA_MBAR + (cur & 7) * 16 + 8, ((cur >> 3) & 1) ^ 1);
                    if (cur == 1 || cur == 8) mbar_wait(sb + SA_QBAR + 8 + (cur & 8), 0);
                } while (cur != pl);
                load_q(pl);
            }
            float s4[4][4];
            const uint32_t kb = sb + slot * 16384;
#pragma unroll
            for (int j = 0; j < 4; j++) {
                s4[j][0] = s4[j][1] = s4[j][2] = s4[j][3] = 0.f;
                const bool on = (g >> 1) == j;
#pragma unroll
                for (int ks = 0; ks < 4; ks++) {
                    uint32_t a[4];
                    ldsm4(a, kb + j * 2048 + koff[ks]);
                    mma16816(s4[j], a, on ? qf[ks][0] : 0u, on ? qf[ks][1] : 0u);
                }
            }
            float d[4];
#pragma unroll
            for (int r = 0; r < 4; r++) d[r] = (s4[0][r] + s4[1][r]) + (s4[2][r] + s4[3][r]);
            float sa = (g & 1) ? d[1] : d[0], sc = (g & 1) ? d[3] : d[2];
            sa += shx(sa, 4); sc += shx(sc, 4);
            uint32_t sp = packbf(sa, sc);
            sp = packbf(bflo(sp) * SCALE, bfhi(sp) * SCALE);
            sa = bflo(sp); sc = bfhi(sp);
            const float mx = warp_max(fmaxf(fmaxf(sa, sc), m));
            const float alpha = ex2((m - mx) * LOG2E);
            m = mx;
            const float pa = ex2((sa - mx) * LOG2E), pc = ex2((sc - mx) * LOG2E);
            const uint32_t pk = packbf(pa, pc);
            uint32_t pb[4][4][2];
#pragma unroll
            for (int j = 0; j < 4; j++) {
                const uint32_t pj = __shfl_sync(0xffffffffu, pk, 8 * tq + j);
#pragma unroll
                for (int i = 0; i < 4; i++) { pb[j][i][0] = prmt0(pj, psel[i][0]); pb[j][i][1] = prmt0(pj, psel[i][1]); }
            }
            l = fmaf(l, alpha, pa + pc);
            ls = l + shx(l, 8);
#pragma unroll
            for (int i = 0; i < 4; i++) { acc[i][0] *= alpha; acc[i][1] *= alpha; acc[i][2] *= alpha; acc[i][3] *= alpha; }
            mbar_wait(sb + SA_FULL + slot * 16 + 8, ph);
            TR(1);
            const uint32_t vb = kb + 8192;
#pragma unroll
            for (int i = 0; i < 4; i++)
#pragma unroll
                for (int j = 0; j < 4; j++) {
                    uint32_t a[4];
                    ldsm4t(a, vb + j * 2048 + voff[i]);
                    mma16816(acc[j], a, pb[j][i][0], pb[j][i][1]);
                }
            ls += shx(ls, 16); ls += shx(ls, 1); ls += shx(ls, 2);
            __syncwarp();
            if (lane == 0) mbar_arrive(sb + SA_EMPTY + slot * 8);
            slot += NW;
            if (slot >= NSL) { slot -= NSL; ph ^= 1; }
        }
    }

    const int r = bx >> 2, isC = (bx >> 1) & 1;
    const uint32_t bar_h = sb + SB_BAR + 32;
    if (warp == 8 && !isC) {
        const unsigned c0 = clk32();
        bar_sync(7, 64);
        while ((int)(clk32() - c0) < BSTART + (r & 7) * BSTAG) {}
        if (elect()) load_slice(sb + SB_STG, &M.qb, r, sb + SB_BAR + 16);
        __syncwarp();
    }
    if (warp < 8) {
    {
        const uint32_t bar_q = bar_h + (NT + warp) * 8, box = sb + SB_QIMG + warp * 8192;
        if (elect()) {
            mbar_init(bar_q, 1);
            mbar_init_fence();
            mbar_expect(bar_q, 8192 + 256);
            tma2d(box, &M.qa, (bx >> 1) * 64, warp * 64, bar_q);
        }
        __syncwarp();
        unsigned epoch = 0;
        if (warp < 2) epoch = ld_relaxed1(S->epoch + bx * 8);
        uint4* const qdst = S->qpub + ((lane >> 4) * 32 + r) * 32 + isC * 16 + (lane & 15);
        if (PLACE && warp == 0) st_b128(qdst, make_uint4(0, 0, 0, 0));
        if (elect()) {
            for (const unsigned c0 = clk32(); (int)(clk32() - c0) < XD0 + (bx >> 1) * XDS;) {}
            bulk_g2s(sb + SB_P + 4096 + warp * 288, P.ax + warp * 32, 128, bar_q);
            bulk_g2s(sb + SB_P + 4096 + warp * 288 + 144, P.ax + 256 + warp * 32, 128, bar_q);
        }
        if (tid == 32) {
#pragma unroll
            for (int i = 0; i < 4 + NT; i++) mbar_init(sb + SB_BAR + i * 8, 1);
            mbar_init_fence();
            sts32(sb + SB_CNT, epoch);
        }
        __syncwarp();
        if (warp == 1 && !isC) bar_arrive(7, 64);
        mbar_wait(bar_q, 0);
        TR(0);
        uint32_t b[8];
#pragma unroll
        for (int i = 0; i < 8; i++) b[i] = lds32(sb + SB_P + 4096 + warp * 288 + (g & 1) * 144 + tq * 4 + i * 16);
        float d[4][4];
        uint32_t a[4][4][4];
#pragma unroll
        for (int i = 0; i < 4; i++) {
            d[i][0] = d[i][1] = d[i][2] = d[i][3] = 0.f;
#pragma unroll
            for (int ks = 0; ks < 4; ks++)
                ldsm4t(a[i][ks], box + ks * 2048 + ((lane & 7) + 8 * (lane >> 4)) * 128 + (((2 * i + ((lane >> 3) & 1)) ^ (lane & 7)) << 4));
        }
#pragma unroll
        for (int ks = 0; ks < 4; ks++)
#pragma unroll
            for (int i = 0; i < 4; i++) mma16816(d[i], a[i][ks], b[2 * ks], b[2 * ks + 1]);
        float* qred = reinterpret_cast<float*>(sm + SB_P);
#pragma unroll
        for (int c = 0; c < 4; c++)
            qred[warp * 128 + (c & 1) * 64 + tq * 16 + (c >> 1) * 8 + g] = tq == 0 ? d[0][c] : tq == 1 ? d[1][c] : tq == 2 ? d[2][c] : d[3][c];
        bar_sync(0, 256);
        if (warp == 0) {
            float4 v[8];
#pragma unroll
            for (int w = 0; w < 8; w++) v[w] = *reinterpret_cast<const float4*>(qred + w * 128 + lane * 4);
#pragma unroll
            for (int o = 4; o; o >>= 1)
#pragma unroll
                for (int w = 0; w < o; w++) { v[w].x += v[w + o].x; v[w].y += v[w + o].y; v[w].z += v[w + o].z; v[w].w += v[w + o].w; }
            st_b128(qdst, make_uint4(packbf(v[0].x, v[0].y), epoch + 1, packbf(v[0].z, v[0].w), epoch + 1));
            if (lane == 0) S->epoch[bx * 8] = epoch + 1;
        }
        TR(1);
    }
    if (!isC) latent_branch(P, M, sm TRPASS);
    bar_arrive(6, 288);
    }

    constexpr int ND = 2;
    const int isA = (r >> JMAP) & 1, cb = ((r >> (JMAP + 1)) << JMAP) + (r & ((1 << JMAP) - 1)), nsnd = isA ? NSA : NSB, isCA = isC & isA;
    const int y0 = isC ? nsnd : 0, y1 = isC ? 32 - ND * isA : nsnd;
    const int nreq = isC ? 32 - nsnd : nsnd;
    float* const red = reinterpret_cast<float*>(sm + SC_RED);
    const uint32_t wlane = wo_lane(sb, lane);
    auto fetch_frag = [&](int y, int b, unsigned tag, unsigned ns) {
        for (int it = 0;; it++) {
            const uint4 v = ld_b128(S->frag[0] + isA * 2048 + (b * 32 + y) * 32 + lane);
            if (__all_sync(0xffffffffu, v.y == tag)) {
                reinterpret_cast<uint2*>(sm + SC_FR)[(y * 32 + (g >> 1) * 8 + b * 4 + tq) * 2 + (g & 1)] = make_uint2(v.x, v.z);
                return;
            }
            if (it > SPIN_MAX) __trap();
            __nanosleep(ns);
        }
    };
    if (warp < 8) {
        const unsigned tag = lds32(sb + SB_CNT) + 1;
        const uint32_t t8 = tag & 0xffu;
        uint32_t bs[2], wf[4][4];
        float d[2][4];
        const uint32_t wa = (wlane ^ ((warp & 1) * 32)) + (warp & 2) * 2048;
        const int ks0 = (warp & 2) * 2;
        if (isC) __nanosleep(4000);
#pragma unroll 1
        for (int op = isCA ? 0 : 1;; op++) {
            const int step = isCA ? max(op - 1, 0) : 0, h = step ? 31 - ND + step : isA ? cb : 16 + cb;
            if (op != 1) {
                if (!isCA && (!isC || h >= 32 - ND)) break;
                const int rec = ((warp >> 2) * 32 + h) * CPG + (warp & 3) * 8;
                const uint2* mlp = S->aml + (rec + (lane & 7)) * 4;
                const uint4* src = S->apart + rec * 32 + lane;
                asm volatile("" : "+l"(mlp), "+l"(src));
                if (!step) {
                    for (int it = 0; !__all_sync(0xffffffffu, (ld_b64(mlp).y & 0xffu) == t8); it++) {
                        if (it > SPIN_MAX) __trap();
                        __nanosleep(h > 25 ? DPOLL : CPOLL);
                    }
                } else if (step < ND) {
                    mbar_wait(sb + SB_BAR + 8, 0);
                } else {
                    d[0][0] = d[0][1] = d[0][2] = d[0][3] = d[1][0] = d[1][1] = d[1][2] = d[1][3] = 0.f;
#pragma unroll
                    for (int k = 0; k < ND; k++) {
                        mbar_wait(bar_h + k * 16 + (warp & 2) * 4, 0);
#pragma unroll
                        for (int ks = 0; ks < 4; ks++) ldsm4t(wf[ks], wa + k * 8192 + ks * 1024);
                        if (k < ND - 1) {
#pragma unroll
                            for (int ks = 0; ks < 4; ks++) mma16816(d[ks & 1], wf[ks], g == ks0 + ks ? bs[0] : 0u, g == ks0 + ks ? bs[1] : 0u);
                        }
                    }
                    mbar_wait(sb + SB_BAR, 0);
                }
                TR(3);
                uint4 v[8];
                uint2 ml = ld_b64(mlp);
#pragma unroll
                for (int i = 0; i < 8; i++) v[i] = ld_b128(src + i * 32);
                for (int it = 0;; it++) {
                    unsigned x = ml.y ^ t8;
#pragma unroll
                    for (int i = 0; i < 8; i++) x |= v[i].x ^ t8;
                    if (!__any_sync(0xffffffffu, x & 0xffu)) break;
                    if (it > SPIN_MAX) __trap();
                    ml = ld_b64(mlp);
#pragma unroll
                    for (int i = 0; i < 8; i++)
                        if ((v[i].x & 0xffu) != t8) v[i] = ld_b128(src + i * 32);
                }
                TR(2);
                const float mw = warp_max(__uint_as_float(ml.x)), e = ex2((__uint_as_float(ml.x) - mw) * LOG2E);
                float L = e * __uint_as_float(ml.y), oa[4], ob[4];
                L += shx(L, 1);
#pragma unroll
                for (int i = 0; i < 8; i++) {
                    const float w = __shfl_sync(0xffffffffu, e, i);
                    float (&o)[4] = (i & 1) ? ob : oa;
                    o[0] = i < 2 ? w * __uint_as_float(v[i].x) : fmaf(w, __uint_as_float(v[i].x), o[0]);
                    o[1] = i < 2 ? w * __uint_as_float(v[i].y) : fmaf(w, __uint_as_float(v[i].y), o[1]);
                    o[2] = i < 2 ? w * __uint_as_float(v[i].z) : fmaf(w, __uint_as_float(v[i].z), o[2]);
                    o[3] = i < 2 ? w * __uint_as_float(v[i].w) : fmaf(w, __uint_as_float(v[i].w), o[3]);
                }
                float* fp = reinterpret_cast<float*>(sm + SC_FP) + ((step & 1) * 8 + (warp & 4)) * 132;
                *reinterpret_cast<float4*>(fp + (warp & 3) * 132 + lane * 4) = make_float4(oa[0] + ob[0], oa[1] + ob[1], oa[2] + ob[2], oa[3] + ob[3]);
                L += shx(L, 2);
                L += shx(L, 4);
                if (lane == 0) *reinterpret_cast<float2*>(fp + (warp & 3) * 132 + 128) = make_float2(mw, L);
                bar_sync(1 + (warp >> 2), 128);
                float2 q[4];
                float4 u[4];
#pragma unroll
                for (int w = 0; w < 4; w++) {
                    q[w] = *reinterpret_cast<const float2*>(fp + w * 132 + 128);
                    u[w] = *reinterpret_cast<const float4*>(fp + w * 132 + lane * 4);
                }
                const float MM = fmaxf(fmaxf(q[0].x, q[1].x), fmaxf(q[2].x, q[3].x));
                float f[4], inv;
#pragma unroll
                for (int w = 0; w < 4; w++) f[w] = ex2((q[w].x - MM) * LOG2E);
                asm("rcp.approx.ftz.f32 %0, %1;" : "=f"(inv) : "f"(fmaf(f[0], q[0].y, f[1] * q[1].y) + fmaf(f[2], q[2].y, f[3] * q[3].y)));
                const uint32_t b0 = packbf((fmaf(f[0], u[0].x, f[1] * u[1].x) + fmaf(f[2], u[2].x, f[3] * u[3].x)) * inv,
                                           (fmaf(f[0], u[0].y, f[1] * u[1].y) + fmaf(f[2], u[2].y, f[3] * u[3].y)) * inv);
                const uint32_t b1 = packbf((fmaf(f[0], u[0].z, f[1] * u[1].z) + fmaf(f[2], u[2].z, f[3] * u[3].z)) * inv,
                                           (fmaf(f[0], u[0].w, f[1] * u[1].w) + fmaf(f[2], u[2].w, f[3] * u[3].w)) * inv);
                if (step == ND) {
#pragma unroll
                    for (int ks = 0; ks < 4; ks++) mma16816(d[ks & 1], wf[ks], g == ks0 + ks ? b0 : 0u, g == ks0 + ks ? b1 : 0u);
                    const float x0 = (d[0][0] + d[0][1]) + (d[1][0] + d[1][1]), x1 = (d[0][2] + d[0][3]) + (d[1][2] + d[1][3]);
                    const float z = ((tq & 1) ? x1 : x0) + shx((tq & 1) ? x0 : x1, 1);
                    if ((tq & 2) == (warp & 2)) red[(6 + (tq >> 1)) * 80 + (warp >> 2) * 40 + (warp & 1) * 16 + (tq & 1) * 8 + g] = z;
                    bar_arrive(5, 480);
                    TR(5);
                    TROUT();
                    return;
                }
                bs[0] = b0; bs[1] = b1;
                if (!step && !(warp & 3)) st_b128(S->frag[1] + ((warp >> 2) * 32 + h) * 32 + lane, make_uint4(b0, tag, b1, 0));
                if (!isCA) break;
            } else {
#pragma unroll 1
                for (int y = y0 + ((warp - y0) & 3); y < y1 - 3 * isCA; y += 4) fetch_frag(y, warp >> 2, tag, CPOLL);
                TR(6);
                bar_arrive(4, 448);
            }
        }
        TROUT();
        return;
    }
    if (warp == 14) {
        bar_sync(6, 288);
        const CUtensorMap* map = &M.wo[isA];
        const unsigned tag = lds32(sb + SB_CNT) + 1;
        const uint32_t t8 = tag & 0xffu;
        uint2* const snd = S->snd + r * 32 + lane;
        asm volatile("prefetch.tensormap [%0];" ::"l"(map) : "memory");
        if (PLACE && !isC) st_b64(snd, t8 ^ 0x80u, 0);
        if (!isCA) for (int i = lane; i < 160; i += 32) red[480 + i] = 0.f;
        for (int it = 0; ld_b128(S->frag[1] + 25 * 32).y != tag; it++) {
            if (it > SPIN_MAX) __trap();
            __nanosleep(2000);
        }
        uint2 f;
        for (int it = 0;; it++) {
            f = ld_b64(S->fire + (lane & 1));
            if (__all_sync(0xffffffffu, f.y == tag)) break;
            if (it > SPIN_MAX) __trap();
            __nanosleep(FPOLL);
        }
        const unsigned t0 = __shfl_sync(0xffffffffu, f.x, 0);
        unsigned t1 = t0 + (__reduce_add_sync(0xffffffffu, (int)(f.x - t0)) >> 5) + FIRE_NS;
        TR(2);
        if (elect()) {
            const int n1 = nreq - (isC ? (isA ? NLA : NLB) : 0);
            const int dt = !isC ? (isA ? FIRE_W / NSA : FIRE_W / NSB) : isA ? FIRE_W / (32 - NSA - NLA) : FIRE_W / (32 - NSB - NLB);
            unsigned t2 = t1 + REC0_NS;
            int rec = isCA ? 2 : 0;
            int y = isCA ? 32 - ND : y0;
#pragma unroll 1
            for (int i = 0; i < nreq; i++) {
                const int row = y * 128;
                mbar_expect(bar_h + i * 16, 4096);
                mbar_expect(bar_h + i * 16 + 8, 4096);
                if (++y == 32) y = y0;
                if (i <= n1) {
                    unsigned t;
                    for (int it = 0; (int)((t = gt()) - t1) < 0 && it < 4096; it++) {}
                    t1 += dt;
                    if (rec && (int)(t - t2) >= 0) { mbar_arrive(sb + SB_BAR + --rec * 8); t2 += REC_NS - REC0_NS; }
                }
                tma2d(sb + i * 8192, map, cb * 32, row, bar_h + i * 16);
                tma2d(sb + i * 8192 + 4096, map, cb * 32, row + 64, bar_h + i * 16 + 8);
            }
            TR(3);
            while (rec) {
                for (int it = 0; (int)(gt() - t2) < 0 && it < 4096; it++) {}
                mbar_arrive(sb + SB_BAR + --rec * 8);
                t2 += REC_NS - REC0_NS;
            }
        }
        __syncwarp();
        uint2 o = make_uint2(0, 0);
        if (isC) {
            for (int it = 0;; it++) {
                o = ld_b64(snd);
                if (__all_sync(0xffffffffu, (o.x & 0xffu) == t8)) break;
                if (it > SPIN_MAX) __trap();
            }
        }
        TR(4);
        uint32_t* const dst = reinterpret_cast<uint32_t*>(P.out) + (lane >> 4) * 512 + (isA ? 0 : 256) + cb * 16 + (lane & 15);
        const float2* q = reinterpret_cast<const float2*>(red) + (lane >> 4) * 20 + (lane & 15);
        bar_sync(5, isCA ? 480 : 224);
        const float2 p0 = q[0], p1 = q[40], p2 = q[80], p3 = q[120], p4 = q[160], p5 = q[200], p6 = q[240], p7 = q[280];
        const float sx = (((p0.x + __uint_as_float(o.x)) + p1.x) + (p2.x + p3.x)) + ((p4.x + p5.x) + (p6.x + p7.x));
        const float sy = (((p0.y + __uint_as_float(o.y)) + p1.y) + (p2.y + p3.y)) + ((p4.y + p5.y) + (p6.y + p7.y));
        if (isC) *dst = packbf(sx, sy);
        else st_b64(snd, tagf(sx, t8), __float_as_uint(sy));
        TR(6);
        TROUT();
        return;
    }
    {
        constexpr int nw = 6;
        bar_sync(4, 448);
        const int yl = y1 - 1 - (y1 - 1 - y0 - (warp - 8)) % nw;
        if (isCA && yl >= y1 - 3) {
            const unsigned tag = lds32(sb + SB_CNT) + 1;
#pragma unroll 1
            for (int b = 0; b < 2; b++) fetch_frag(yl, b, tag, DPOLL);
            __syncwarp();
            TR(6);
        }
        float e[4][4];
#pragma unroll
        for (int i = 0; i < 4; i++) e[i][0] = e[i][1] = e[i][2] = e[i][3] = 0.f;
#pragma unroll 1
        for (int i = warp - 8 + ND * isCA; i < nreq; i += nw) {
            const uint32_t bp = sb + SC_FR + ((y0 + i - ND * isCA) * 32 + (lane & 7)) * 16;
            uint4 b[4];
#pragma unroll
            for (int j = 0; j < 4; j++) b[j] = lds128(bp + j * 128);
#pragma unroll
            for (int hf = 0; hf < 2; hf++) {
                uint32_t a[8][4];
                mbar_wait(bar_h + i * 16 + hf * 8, 0);
#pragma unroll
                for (int j = 0; j < 8; j++) ldsm4t(a[j], (wlane ^ ((j & 1) * 32)) + i * 8192 + hf * 4096 + (j >> 1) * 1024);
#pragma unroll
                for (int j = 0; j < 8; j++) {
                    const uint4& c = b[2 * hf + (j >> 2)];
                    mma16816(e[(j & 1) * 2 + ((j >> 1) & 1)], a[j], (j & 2) ? c.z : c.x, (j & 2) ? c.w : c.y);
                }
            }
        }
        float* rx = red + (warp - 8) * 80 + (tq & 1) * 40 + (tq >> 1) * 16 + g;
        float s4[4];
#pragma unroll
        for (int c = 0; c < 4; c++) s4[c] = (tq & 2) ? e[2][c] + e[3][c] : e[0][c] + e[1][c];
        rx[0] = (tq & 1) ? s4[1] : s4[0];
        rx[8] = (tq & 1) ? s4[3] : s4[2];
        bar_arrive(5, isCA ? 480 : 224);
        TROUT();
    }
}

typedef CUresult (*EncodeFn)(CUtensorMap*, CUtensorMapDataType, cuuint32_t, void*, const cuuint64_t*, const cuuint64_t*,
                             const cuuint32_t*, const cuuint32_t*, CUtensorMapInterleave, CUtensorMapSwizzle,
                             CUtensorMapL2promotion, CUtensorMapFloatOOBfill);

void make_map(EncodeFn enc, CUtensorMap* m, const void* base, uint64_t cols, uint64_t rows, uint32_t bc, uint32_t br,
              CUtensorMapL2promotion promo, CUtensorMapSwizzle sw = CU_TENSOR_MAP_SWIZZLE_128B) {
    cuuint64_t dims[2] = {cols, rows};
    cuuint64_t strides[1] = {cols * 2};
    cuuint32_t box[2] = {bc, br};
    cuuint32_t es[2] = {1, 1};
    enc(m, CU_TENSOR_MAP_DATA_TYPE_BFLOAT16, 2, const_cast<void*>(base), dims, strides, box, es,
        CU_TENSOR_MAP_INTERLEAVE_NONE, sw, promo, CU_TENSOR_MAP_FLOAT_OOB_FILL_NONE);
}

}

extern "C" void kernel_launch(void* const* d_in, const int* in_sizes, int n_in, void* d_out, int out_size) {
    (void)in_sizes; (void)n_in; (void)out_size;
    static EncodeFn enc = nullptr;
    static void* scr = nullptr;
    if (!enc) {
        void* fn = nullptr;
        cudaDriverEntryPointQueryResult qr;
        cudaGetDriverEntryPoint("cuTensorMapEncodeTiled", &fn, cudaEnableDefault, &qr);
        enc = (EncodeFn)fn;
        cudaGetSymbolAddress(&scr, g_scr);
        cudaFuncSetAttribute(fused_decode_kernel, cudaFuncAttributeMaxDynamicSharedMemorySize, SMEM_BYTES);
    }
    Maps m;
    make_map(enc, &m.kv[0], d_in[1], 64, 1048576, 64, 64, CU_TENSOR_MAP_L2_PROMOTION_NONE);
    make_map(enc, &m.kv[1], d_in[2], 64, 1048576, 64, 64, CU_TENSOR_MAP_L2_PROMOTION_NONE);
    make_map(enc, &m.qa, d_in[3], 4096, 512, 64, 64, CU_TENSOR_MAP_L2_PROMOTION_NONE);
    make_map(enc, &m.qb, d_in[7], 4096, 512, 64, 256, SPROMO);
    make_map(enc, &m.wo[0], d_in[10], 512, 4096, 32, 64, WPROMO, CU_TENSOR_MAP_SWIZZLE_64B);
    make_map(enc, &m.wo[1], d_in[4], 512, 4096, 32, 64, WPROMO, CU_TENSOR_MAP_SWIZZLE_64B);
    {
        cuuint64_t dims[4] = {64, 8, 8, 2048}, strides[3] = {1024, 128, 8192};
        cuuint32_t box[4] = {64, 8, 8, 8}, es[4] = {1, 1, 1, 1};
        enc(&m.c, CU_TENSOR_MAP_DATA_TYPE_BFLOAT16, 4, d_in[6], dims, strides, box, es, CU_TENSOR_MAP_INTERLEAVE_NONE,
            CU_TENSOR_MAP_SWIZZLE_128B, CU_TENSOR_MAP_L2_PROMOTION_NONE, CU_TENSOR_MAP_FLOAT_OOB_FILL_NONE);
    }
    make_map(enc, &m.uk, d_in[8], 4096, 512, 64, 256, SPROMO);
    make_map(enc, &m.uv, d_in[9], 4096, 512, 64, 256, SPROMO);
    Params p;
    p.scr = (Scratch*)scr;
    p.ax = (const uint32_t*)d_in[0];
    p.bx = (const uint32_t*)d_in[5];
    p.out = (__nv_bfloat16*)d_out;
    p.wq = (const char*)d_in[3];
    fused_decode_kernel<<<128, 480, SMEM_BYTES, cudaStreamPerThread>>>(p, m);
}
```

```cpp
#include <cuda_runtime.h>
#include <cuda_bf16.h>
#include <cuda.h>
#include <stdint.h>
#include <float.h>

#define LIM 12
#define LIM0 8
#define RAMP_S 256
#define RAMP_T0 300
#define BAL 20
#define SKEW 3
#define ROT 128
#define FIRE_T 240
#define FIRE_NS 3300
#define FIRE_W 1950
#define NLA 6
#define NLB 10
#define NSA 13
#define NSB 13
#define REC_NS 1700
#define JMAP 2
#define WPROMO CU_TENSOR_MAP_L2_PROMOTION_L2_128B
#define REC0_NS 100
#define DPOLL 300
#define PFM 1
#define QPOLL 300
#define BSTAG 500
#define SPROMO CU_TENSOR_MAP_L2_PROMOTION_NONE
#define XD0 1000
#define XDS 12
#define XPM 15
#define XPOS 1
#define NMW 6
#define PLACE 1
#define BSTART 3000
#define QSLEEP 1500
#define BPOLL 1000
#define CPOLL 700
#define FPOLL 300

namespace {

constexpr int NG = 2, CPG = 32, NW = 4;
constexpr int UPG = 8192;
constexpr int NSL = 12, SPW = NSL / NW;
constexpr unsigned TICK_INC = UPG - NSL * CPG + NW * CPG;
constexpr int SPIN_MAX = 1 << 22;
constexpr float LOG2E = 1.4426950408889634f;
constexpr float SCALE = 0.08838834764831845f;
constexpr uint64_t EVICT_FIRST = 0x12F0000000000000ull;

constexpr int SA_SLOT = NSL * 16384;
constexpr int SA_Q    = SA_SLOT + 8 * NW * 132 * 4;
constexpr int SA_FULL = SA_Q + 8192;
constexpr int SA_EMPTY = SA_FULL + NSL * 16;
constexpr int SA_GOV  = SA_EMPTY + NSL * 8;
constexpr int SA_MBAR = SA_GOV + NSL * 8;
constexpr int SA_QBAR = SA_MBAR + 128;
constexpr int SA_META = SA_QBAR + 24;
constexpr int SA_LIM  = SA_META + NSL * 4;
constexpr int SA_CNT  = SA_LIM + 16;
constexpr int SA_END  = SA_CNT + 64;
constexpr int PROW    = 2080;
constexpr int SB_STG  = 0;
constexpr int SB_QIMG = 131072;
constexpr int SB_P    = SB_QIMG + 32 * PROW;
constexpr int SB_AL   = SB_P + 8192;
constexpr int SB_X    = SB_AL + 256;
static_assert(SB_P % 1024 == 0, "swizzle atom");
constexpr int SB_QB   = SB_X + 4352;
constexpr int NT      = 40;
constexpr int SC_FR   = NT * 4096;
constexpr int SC_FP   = SC_FR + 16384;
constexpr int SC_RED  = SB_QB + 1024;
constexpr int SB_BAR  = SC_RED + 4480;
constexpr int SB_CNT  = SB_BAR + (12 + NT) * 8;
static_assert(SC_FP + 8448 <= SB_P && 2 * (32 - NSA) <= NT && 2 * (32 - NSB) <= NT && NSA <= 16 && NSB <= 16, "projection slots");
constexpr int SB_END  = SB_CNT + 64;
constexpr int SMEM_BYTES = (SA_END > SB_END ? SA_END : SB_END);
static_assert(SMEM_BYTES <= 232448, "shared memory");

struct Scratch {
    uint4    bpart[32 * 32 * (PROW / 16)];
    uint4    apart[64 * CPG * 32];
    uint4    qimg[2 * 4096];
    uint4    qpub[64 * 32];
    uint4    frag[2][64 * 32];
    uint2    snd[32 * 32];
    uint2    aml[64 * CPG * 4];
    unsigned epoch[128 * 8];
    unsigned ctr[1088];
    uint2    fire[544];
    unsigned qflag[1088], bflag[1088];
};
__device__ __align__(1024) Scratch g_scr;

#define TRARG
#define TRPASS
#define TR(k)
#define TROUT()

__device__ __forceinline__ uint32_t s2u(const void* p) { return (uint32_t)__cvta_generic_to_shared(p); }
__device__ __forceinline__ bool elect() {
    uint32_t ok;
    asm volatile("{\n.reg .pred p;\nelect.sync _|p, 0xffffffff;\nselp.u32 %0,1,0,p;\n}" : "=r"(ok));
    return ok;
}
__device__ __forceinline__ void mbar_init(uint32_t b, int c) {
    asm volatile("mbarrier.init.shared::cta.b64 [%0], %1;" ::"r"(b), "r"(c) : "memory");
}
__device__ __forceinline__ void mbar_init_fence() { asm volatile("fence.mbarrier_init.release.cluster;" ::: "memory"); }
__device__ __forceinline__ void mbar_expect(uint32_t b, uint32_t bytes) {
    asm volatile("mbarrier.arrive.expect_tx.shared::cta.b64 _, [%0], %1;" ::"r"(b), "r"(bytes) : "memory");
}
__device__ __forceinline__ void mbar_arrive(uint32_t b) {
    asm volatile("mbarrier.arrive.shared::cta.b64 _, [%0];" ::"r"(b) : "memory");
}
__device__ __forceinline__ bool mbar_test(uint32_t b, uint32_t ph) {
    uint32_t ok;
    asm volatile("{\n.reg .pred p;\nmbarrier.test_wait.parity.shared::cta.b64 p, [%1], %2;\nselp.u32 %0,1,0,p;\n}"
                 : "=r"(ok) : "r"(b), "r"(ph) : "memory");
    return ok;
}
__device__ __forceinline__ void mbar_wait(uint32_t b, uint32_t ph) {
    asm volatile("{\n.reg .pred p;\n.reg .u32 n;\nmov.u32 n, 0;\n"
                 "W: mbarrier.try_wait.parity.shared::cta.b64 p, [%0], %1;\n@p bra.uni D;\n"
                 "add.u32 n, n, 1;\nsetp.lt.u32 p, n, %2;\n@p bra.uni W;\ntrap;\nD:\n}"
                 ::"r"(b), "r"(ph), "n"(SPIN_MAX) : "memory");
}
__device__ __forceinline__ void tma2d(uint32_t dst, const CUtensorMap* map, int c0, int c1, uint32_t bar) {
    asm volatile("cp.async.bulk.tensor.2d.shared::cluster.global.mbarrier::complete_tx::bytes [%0], [%1, {%3, %4}], [%2];"
                 ::"r"(dst), "l"(map), "r"(bar), "r"(c0), "r"(c1) : "memory");
}
__device__ __forceinline__ void tma2d_ef(uint32_t dst, const CUtensorMap* map, int c0, int c1, uint32_t bar) {
    asm volatile("cp.async.bulk.tensor.2d.shared::cluster.global.mbarrier::complete_tx::bytes.L2::cache_hint [%0], [%1, {%3, %4}], [%2], %5;"
                 ::"r"(dst), "l"(map), "r"(bar), "r"(c0), "r"(c1), "l"(EVICT_FIRST) : "memory");
}
__device__ __forceinline__ void tma4d_ef(uint32_t dst, const CUtensorMap* map, int c3, uint32_t bar) {
    asm volatile("cp.async.bulk.tensor.4d.shared::cluster.global.mbarrier::complete_tx::bytes.L2::cache_hint [%0], [%1, {0, 0, 0, %3}], [%2], %4;"
                 ::"r"(dst), "l"(map), "r"(bar), "r"(c3), "l"(EVICT_FIRST) : "memory");
}
__device__ __forceinline__ void bulk_g2s(uint32_t dst, const void* src, uint32_t bytes, uint32_t bar) {
    asm volatile("cp.async.bulk.shared::cluster.global.mbarrier::complete_tx::bytes [%0], [%1], %2, [%3];"
                 ::"r"(dst), "l"(src), "r"(bytes), "r"(bar) : "memory");
}
__device__ __forceinline__ void bulk_s2g(void* dst, uint32_t src, uint32_t bytes) {
    asm volatile("cp.async.bulk.global.shared::cta.bulk_group [%0], [%1], %2;" ::"l"(dst), "r"(src), "r"(bytes) : "memory");
}
__device__ __forceinline__ void fence_async_all() { asm volatile("fence.proxy.async;" ::: "memory"); }
__device__ __forceinline__ void bar_sync(int id, int n) { asm volatile("bar.sync %0, %1;" ::"r"(id), "r"(n) : "memory"); }
__device__ __forceinline__ void bar_arrive(int id, int n) { asm volatile("bar.arrive %0, %1;" ::"r"(id), "r"(n) : "memory"); }
__device__ __forceinline__ unsigned ld_relaxed1(const void* p) {
    unsigned v;
    asm volatile("ld.relaxed.gpu.global.u32 %0, [%1];" : "=r"(v) : "l"(p) : "memory");
    return v;
}
__device__ __forceinline__ unsigned atom_inc(unsigned* p) {
    unsigned v;
    asm volatile("atom.relaxed.gpu.global.add.u32 %0, [%1], 1;" : "=r"(v) : "l"(p) : "memory");
    return v;
}
__device__ __forceinline__ uint4 ld_b128(const void* p) {
    uint4 v;
    asm volatile("{\n.reg .b128 t;\nld.relaxed.gpu.global.b128 t, [%4];\nmov.b128 {%0,%1,%2,%3}, t;\n}"
                 : "=r"(v.x), "=r"(v.y), "=r"(v.z), "=r"(v.w) : "l"(p) : "memory");
    return v;
}
__device__ __forceinline__ void st_b128(void* p, uint4 v) {
    asm volatile("{\n.reg .b128 t;\nmov.b128 t, {%1,%2,%3,%4};\nst.relaxed.gpu.global.b128 [%0], t;\n}"
                 ::"l"(p), "r"(v.x), "r"(v.y), "r"(v.z), "r"(v.w) : "memory");
}
__device__ __forceinline__ uint2 ld_b64(const void* p) {
    uint2 v;
    asm volatile("{\n.reg .b64 a;\nld.relaxed.gpu.global.b64 a, [%2];\nmov.b64 {%0,%1}, a;\n}" : "=r"(v.x), "=r"(v.y) : "l"(p) : "memory");
    return v;
}
__device__ __forceinline__ void st_b64(void* p, uint32_t a, uint32_t b) {
    asm volatile("{\n.reg .b64 t;\nmov.b64 t, {%1,%2};\nst.relaxed.gpu.global.b64 [%0], t;\n}" ::"l"(p), "r"(a), "r"(b) : "memory");
}
__device__ __forceinline__ unsigned ld_acquire(const unsigned* p) {
    unsigned v;
    asm volatile("ld.acquire.gpu.global.u32 %0, [%1];" : "=r"(v) : "l"(p) : "memory");
    return v;
}
__device__ __forceinline__ void st_release(unsigned* p, unsigned v) {
    asm volatile("st.release.gpu.global.u32 [%0], %1;" ::"l"(p), "r"(v) : "memory");
}
__device__ __forceinline__ void ldsm4(uint32_t (&r)[4], uint32_t a) {
    asm volatile("ldmatrix.sync.aligned.m8n8.x4.shared.b16 {%0,%1,%2,%3}, [%4];"
                 : "=r"(r[0]), "=r"(r[1]), "=r"(r[2]), "=r"(r[3]) : "r"(a) : "memory");
}
__device__ __forceinline__ void ldsm4t(uint32_t (&r)[4], uint32_t a) {
    asm volatile("ldmatrix.sync.aligned.m8n8.x4.trans.shared.b16 {%0,%1,%2,%3}, [%4];"
                 : "=r"(r[0]), "=r"(r[1]), "=r"(r[2]), "=r"(r[3]) : "r"(a) : "memory");
}
__device__ __forceinline__ uint4 lds128(uint32_t a) {
    uint4 v;
    asm volatile("ld.shared.v4.u32 {%0, %1, %2, %3}, [%4];" : "=r"(v.x), "=r"(v.y), "=r"(v.z), "=r"(v.w) : "r"(a) : "memory");
    return v;
}
__device__ __forceinline__ float2 lds64f(uint32_t a) {
    float2 v;
    asm volatile("ld.shared.v2.f32 {%0, %1}, [%2];" : "=f"(v.x), "=f"(v.y) : "r"(a) : "memory");
    return v;
}
__device__ __forceinline__ uint32_t lds32(uint32_t a) {
    uint32_t v;
    asm volatile("ld.shared.u32 %0, [%1];" : "=r"(v) : "r"(a) : "memory");
    return v;
}
__device__ __forceinline__ void sts32(uint32_t a, uint32_t v) { asm volatile("st.shared.u32 [%0], %1;" ::"r"(a), "r"(v) : "memory"); }
__device__ __forceinline__ void mma16816(float (&d)[4], const uint32_t (&a)[4], uint32_t b0, uint32_t b1) {
    asm volatile("mma.sync.aligned.m16n8k16.row.col.f32.bf16.bf16.f32 {%0,%1,%2,%3}, {%4,%5,%6,%7}, {%8,%9}, {%0,%1,%2,%3};"
                 : "+f"(d[0]), "+f"(d[1]), "+f"(d[2]), "+f"(d[3])
                 : "r"(a[0]), "r"(a[1]), "r"(a[2]), "r"(a[3]), "r"(b0), "r"(b1));
}
__device__ __forceinline__ uint32_t prmt0(uint32_t a, uint32_t sel) {
    uint32_t d;
    asm volatile("prmt.b32 %0, %1, 0, %2;" : "=r"(d) : "r"(a), "r"(sel));
    return d;
}
__device__ __forceinline__ unsigned gt() {
    unsigned t;
    asm volatile("mov.u32 %0, %globaltimer_lo;" : "=r"(t));
    return t;
}
__device__ __forceinline__ unsigned clk32() {
    unsigned c;
    asm volatile("mov.u32 %0, %clock;" : "=r"(c));
    return c;
}
__device__ __forceinline__ float ex2(float x) {
    float y;
    asm("ex2.approx.ftz.f32 %0, %1;" : "=f"(y) : "f"(x));
    return y;
}
__device__ __forceinline__ float bf16r(float x) { return __bfloat162float(__float2bfloat16_rn(x)); }
__device__ __forceinline__ uint32_t packbf(float lo, float hi) {
    uint32_t r;
    asm("cvt.rn.bf16x2.f32 %0, %1, %2;" : "=r"(r) : "f"(hi), "f"(lo));
    return r;
}
__device__ __forceinline__ float bflo(uint32_t v) { return __uint_as_float(v << 16); }
__device__ __forceinline__ float bfhi(uint32_t v) { return __uint_as_float(v & 0xffff0000u); }
__device__ __forceinline__ uint32_t tagf(float v, uint32_t t8) { return (__float_as_uint(v) & 0xffffff00u) | t8; }
__device__ __forceinline__ float shx(float v, int m) { return __shfl_xor_sync(0xffffffffu, v, m); }

__device__ __forceinline__ float warp_max(float v) {
    int i = __float_as_int(v);
    i = __reduce_max_sync(0xffffffffu, i ^ ((i >> 31) & 0x7fffffff));
    return __int_as_float(i ^ ((i >> 31) & 0x7fffffff));
}

__device__ __forceinline__ uint64_t gdesc(uint32_t addr, uint32_t lbo, uint32_t sbo) {
    return (uint64_t)((addr & 0x3ffff) >> 4) | ((uint64_t)(lbo >> 4) << 16) | ((uint64_t)(sbo >> 4) << 32) | (1ull << 62);
}
__device__ __forceinline__ void wg_fence() { asm volatile("wgmma.fence.sync.aligned;" ::: "memory"); }
__device__ __forceinline__ void wg_commit() { asm volatile("wgmma.commit_group.sync.aligned;" ::: "memory"); }
__device__ __forceinline__ void wg_wait0() { asm volatile("wgmma.wait_group.sync.aligned 0;" ::: "memory"); }
template <int N> __device__ __forceinline__ void reg_fence(float (&r)[N]) {
#pragma unroll
    for (int i = 0; i < N; i++) asm volatile("" : "+f"(r[i])::"memory");
}
#define F8(a, o) "+f"(a[o]), "+f"(a[o + 1]), "+f"(a[o + 2]), "+f"(a[o + 3]), "+f"(a[o + 4]), "+f"(a[o + 5]), "+f"(a[o + 6]), "+f"(a[o + 7])
#define F32(a, o) F8(a, o), F8(a, o + 8), F8(a, o + 16), F8(a, o + 24)
__device__ __forceinline__ void wgmma_n64_ss(float (&d)[32], uint64_t da, uint64_t db, int scale_d) {
    asm volatile(
        "{\n.reg .pred p;\nsetp.ne.b32 p, %34, 0;\n"
        "wgmma.mma_async.sync.aligned.m64n64k16.f32.bf16.bf16 "
        "{%0,%1,%2,%3,%4,%5,%6,%7,%8,%9,%10,%11,%12,%13,%14,%15,%16,%17,%18,%19,%20,%21,%22,%23,%24,%25,%26,%27,%28,%29,%30,%31},"
        " %32, %33, p, 1, 1, 0, 0;\n}"
        : F32(d, 0) : "l"(da), "l"(db), "r"(scale_d));
}
__device__ __forceinline__ void wgmma_n32_ts(float (&d)[16], uint64_t da, uint64_t db) {
    asm volatile(
        "{\n.reg .pred p;\nsetp.ne.b32 p, 1, 0;\n"
        "wgmma.mma_async.sync.aligned.m64n32k16.f32.bf16.bf16 "
        "{%0,%1,%2,%3,%4,%5,%6,%7,%8,%9,%10,%11,%12,%13,%14,%15}, %16, %17, p, 1, 1, 1, 0;\n}"
        : F8(d, 0), F8(d, 8) : "l"(da), "l"(db));
}

struct Params {
    Scratch* scr;
    const uint32_t *ax, *bx;
    const char* wq;
    __nv_bfloat16* out;
};
struct Maps { CUtensorMap kv[2], qa, qb, wo[2], c, uk, uv; };

__device__ __forceinline__ void wait_flags(const unsigned* flags, unsigned tag, int lane) {
    for (int i = 0; !__all_sync(0xffffffffu, ld_acquire(flags + lane) == tag); i++) {
        if (i > SPIN_MAX) __trap();
        __nanosleep(BPOLL);
    }
}
__device__ __forceinline__ void load_slice(uint32_t dst, const CUtensorMap* map, int r, uint32_t bar) {
    mbar_expect(bar, 131072);
#pragma unroll
    for (int x = 0; x < 4; x++) tma2d(dst + x * 32768, map, r * 128 + (x & 1) * 64, (x >> 1) * 256, bar);
}
__device__ __forceinline__ void gemv_slice(uint32_t sb, int warp, int lane) {
    const int g = lane >> 2, tq = lane & 3;
    float d[4][4];
#pragma unroll
    for (int i = 0; i < 4; i++) d[i][0] = d[i][1] = d[i][2] = d[i][3] = 0.f;
    const uint32_t wb = sb + SB_STG + (warp >> 2) * 32768 + ((lane & 7) + 8 * (lane >> 4)) * 128 +
                        (((2 * (warp & 3) + ((lane >> 3) & 1)) ^ (lane & 7)) << 4);
    const uint32_t xb = sb + SB_X + ((g & 3) * 264 + tq) * 4;
#pragma unroll 1
    for (int k8 = 0; k8 < 4; k8++) {
        uint32_t a[8][4], b[8][2];
#pragma unroll
        for (int ks = 0; ks < 8; ks++) {
            ldsm4t(a[ks], wb + (k8 >> 1) * 65536 + (k8 & 1) * 16384 + ks * 2048);
            b[ks][0] = lds32(xb + k8 * 256 + ks * 32);
            b[ks][1] = lds32(xb + k8 * 256 + ks * 32 + 16);
        }
#pragma unroll
        for (int ks = 0; ks < 8; ks++) mma16816(d[ks & 3], a[ks], b[ks][0], b[ks][1]);
    }
    const float y0 = ((d[0][0] + d[1][0]) + (d[2][0] + d[3][0])) + ((d[0][1] + d[1][1]) + (d[2][1] + d[3][1]));
    const float y1 = ((d[0][2] + d[1][2]) + (d[2][2] + d[3][2])) + ((d[0][3] + d[1][3]) + (d[2][3] + d[3][3]));
    if (tq < 2) {
        sts32(sb + SB_QB + (tq * 128 + warp * 16 + g) * 4, __float_as_uint(y0));
        sts32(sb + SB_QB + (tq * 128 + warp * 16 + 8 + g) * 4, __float_as_uint(y1));
    }
}
__device__ __forceinline__ uint32_t wo_lane(uint32_t sb, int lane) {
    return sb + ((lane & 7) + 8 * (lane >> 4)) * 64 + ((((lane >> 3) & 1) ^ ((lane >> 1) & 3)) << 4);
}

template <int NP, int NTHR> __device__ __forceinline__ float2 sum_parts(uint32_t q, float x, float y) {
    asm volatile("bar.sync 5, %0;" ::"n"(NTHR) : "memory");
    float2 p[NP];
#pragma unroll
    for (int i = 0; i < NP; i++) p[i] = lds64f(q + i * 320);
    p[0].x += x; p[0].y += y;
#pragma unroll
    for (int d = 1; d < NP; d *= 2)
#pragma unroll
        for (int i = 0; i + d < NP; i += 2 * d) { p[i].x += p[i + d].x; p[i].y += p[i + d].y; }
    return p[0];
}

__device__ __forceinline__ void latent_branch(const Params& P, const Maps& M, uint8_t* sm TRARG) {
    const uint32_t sb = s2u(sm);
    const int tid = threadIdx.x, lane = tid & 31, warp = tid >> 5, g = lane >> 2, tq = lane & 3, r = blockIdx.x >> 2;
    const uint32_t bar_w = sb + SB_BAR + 16, bar_x = sb + SB_BAR + 24;
    const unsigned tag = lds32(sb + SB_CNT) + 1;
    Scratch* const S = P.scr;
    const float* yb = reinterpret_cast<const float*>(sm + SB_QB);
    {
        float* xs = reinterpret_cast<float*>(sm + SB_X);
        const int crow0 = (r >> 4) * 8192 + (r & 15) * 64;
        {
            uint32_t* xh = reinterpret_cast<uint32_t*>(sm + SB_X) + tid;
            xh[0] = __ldg(P.bx + tid); xh[264] = 0; xh[528] = __ldg(P.bx + 256 + tid); xh[792] = 0;
            bar_sync(0, 256);
            mbar_wait(bar_w, 0);
            TR(0);
            gemv_slice(sb, warp, lane);
            bar_sync(0, 256);
            if (tid == 0) load_slice(sb + SB_STG, &M.uk, r, bar_w);
            uint32_t qb[8][2];
#pragma unroll
            for (int ks = 0; ks < 8; ks++) {
                const float2 a = *reinterpret_cast<const float2*>(yb + (g & 1) * 128 + ks * 16 + 2 * tq);
                const float2 b = *reinterpret_cast<const float2*>(yb + (g & 1) * 128 + ks * 16 + 8 + 2 * tq);
                qb[ks][0] = packbf(a.x, a.y);
                qb[ks][1] = packbf(b.x, b.y);
            }
            mbar_wait(bar_w, 1);
            const uint32_t wb = sb + SB_STG + (warp >> 2) * 65536 + ((warp & 3) * 64 + (lane & 15)) * 128;
#pragma unroll 1
            for (int mt = 0; mt < 4; mt++) {
                float d[4] = {0.f, 0.f, 0.f, 0.f};
#pragma unroll
                for (int ks = 0; ks < 8; ks++) {
                    uint32_t a[4];
                    ldsm4(a, wb + (ks >> 2) * 32768 + mt * 2048 + (((2 * (ks & 3) + (lane >> 4)) ^ (lane & 7)) << 4));
                    mma16816(d, a, qb[ks][0], qb[ks][1]);
                }
                if (tq == 0) {
                    const int c = warp * 64 + mt * 16 + g;
                    xs[c] = d[0]; xs[512 + c] = d[1]; xs[c + 8] = d[2]; xs[512 + c + 8] = d[3];
                }
            }
            bar_sync(0, 256);
            if (tid == 32) {
#pragma unroll
                for (int t = 0; t < 2; t++) {
                    mbar_expect(sb + SB_BAR + t * 8, 65536);
                    tma4d_ef(sb + SB_STG + t * 65536, &M.c, (crow0 >> 3) + t * 128, sb + SB_BAR + t * 8);
                }
            }
            const int b = tid >> 7, lo = (tid >> 6) & 1, ch = tid & 63;
            float v[8];
#pragma unroll
            for (int i = 0; i < 8; i++) {
                const float x = xs[b * 512 + ch * 8 + i];
                v[i] = lo ? x - bf16r(x) : x;
            }
            const int row = 16 * (r >> 3) + (r & 7) + 8 * lo;
            S->qimg[b * 4096 + (ch >> 3) * 512 + row * 8 + ((ch & 7) ^ (r & 7))] =
                make_uint4(packbf(v[0], v[1]), packbf(v[2], v[3]), packbf(v[4], v[5]), packbf(v[6], v[7]));
            bar_sync(0, 256);
            if (warp == 0) {
                if (lane == 0) { __threadfence(); st_release(S->qflag + r, tag); }
                wait_flags(S->qflag, tag, lane);
                if (lane == 0) {
                    fence_async_all();
                    mbar_expect(bar_x, 65536);
                    bulk_g2s(sb + SB_QIMG, S->qimg + (r >> 4) * 4096, 65536, bar_x);
                }
            }
            mbar_wait(bar_x, 0);
        }
        TR(1);
        {
            const int wg = warp >> 2;
            float acc[4][16];
#pragma unroll
            for (int i = 0; i < 64; i++) acc[i >> 4][i & 15] = 0.f;
            const int head = (warp & 3) * 8 + g;
            const uint32_t pa = sb + SB_P + wg * 4096;
            float* al = reinterpret_cast<float*>(sm + SB_AL) + wg * 32;
            float m = -FLT_MAX, l = 0.f;
#pragma unroll 1
            for (int t = 0; t < 8; t++) {
                const uint32_t stg = sb + SB_STG + (t & 1) * 65536;
                mbar_wait(sb + SB_BAR + (t & 1) * 8, (t >> 1) & 1);
                float s[32];
                uint32_t qa = sb + SB_QIMG;
                asm volatile("" : "+r"(qa));
                wg_fence();
#pragma unroll
                for (int k = 0; k < 32; k++) {
                    const uint32_t off = (k >> 2) * 8192 + (k & 3) * 32;
                    wgmma_n64_ss(s, gdesc(qa + off, 16, 1024), gdesc(stg + (k >> 2) * 1024 + (k & 3) * 32, 16, 8192), k > 0);
                }
                wg_commit();
                wg_wait0();
                reg_fence(s);
                float p[16], mx = m;
#pragma unroll
                for (int i = 0; i < 8; i++) {
                    p[2 * i] = bf16r(bf16r(s[4 * i] + s[4 * i + 2]) * SCALE);
                    p[2 * i + 1] = bf16r(bf16r(s[4 * i + 1] + s[4 * i + 3]) * SCALE);
                    mx = fmaxf(mx, fmaxf(p[2 * i], p[2 * i + 1]));
                }
                mx = fmaxf(mx, shx(mx, 1));
                mx = fmaxf(mx, shx(mx, 2));
                const float alpha = ex2((m - mx) * LOG2E);
                m = mx;
                float sum = 0.f;
#pragma unroll
                for (int i = 0; i < 8; i++) {
                    const float a = ex2((p[2 * i] - mx) * LOG2E), b = ex2((p[2 * i + 1] - mx) * LOG2E);
                    sum += a + b;
                    sts32(pa + head * 128 + ((i ^ g) << 4) + tq * 4, packbf(a, b));
                }
                l = fmaf(l, alpha, sum);
                if (tq == 0) al[head] = alpha;
                asm volatile("fence.proxy.async.shared::cta;" ::: "memory");
                bar_sync(1 + wg, 128);
#pragma unroll
                for (int j = 0; j < 4; j++) {
                    const float2 a = *reinterpret_cast<const float2*>(al + 8 * j + 2 * tq);
#pragma unroll
                    for (int i = 0; i < 4; i++) { acc[i][4 * j] *= a.x; acc[i][4 * j + 1] *= a.y; acc[i][4 * j + 2] *= a.x; acc[i][4 * j + 3] *= a.y; }
                }
#pragma unroll
                for (int i = 0; i < 4; i++) reg_fence(acc[i]);
                wg_fence();
#pragma unroll
                for (int kk = 0; kk < 4; kk++)
#pragma unroll
                    for (int i = 0; i < 4; i++)
                        wgmma_n32_ts(acc[i], gdesc(stg + (wg * 4 + i) * 1024 + kk * 16384, 1024, 8192), gdesc(pa + kk * 32, 16, 1024));
                wg_commit();
                wg_wait0();
#pragma unroll
                for (int i = 0; i < 4; i++) reg_fence(acc[i]);
                bar_sync(0, 256);
                if (tid == 0) {
                    if (t + 2 < 8) {
                        const uint32_t bar = sb + SB_BAR + (t & 1) * 8;
                        mbar_expect(bar, 65536);
                        tma4d_ef(stg, &M.c, (crow0 >> 3) + (t + 2) * 128, bar);
                    }
                    if (t == 7) load_slice(sb + SB_STG, &M.uv, r, bar_w);
                }
            }
            TR(2);
            float* dst = reinterpret_cast<float*>(sm + SB_QIMG + 2 * tq * PROW) + wg * 256 + (warp & 3) * 16 + g;
#pragma unroll
            for (int i = 0; i < 64; i++)
                dst[(((i >> 2) & 3) * 8 + (i & 1)) * (PROW / 4) + (i >> 4) * 64 + (i & 2) * 4] = acc[i >> 4][i & 15];
            l += shx(l, 1); l += shx(l, 2);
            if (wg == 0 && tq < 2) *reinterpret_cast<float4*>(sm + SB_QIMG + head * PROW + 2048 + tq * 16) = make_float4(m, l, 0.f, 0.f);
            asm volatile("fence.proxy.async.shared::cta;" ::: "memory");
            bar_sync(0, 256);
            if (warp == 0) {
                bulk_s2g(S->bpart + (lane * 32 + r) * (PROW / 16), sb + SB_QIMG + lane * PROW, PROW);
                asm volatile("cp.async.bulk.commit_group;" ::: "memory");
                asm volatile("cp.async.bulk.wait_group 0;" ::: "memory");
                fence_async_all();
                __threadfence();
                __syncwarp();
                if (lane == 0) st_release(S->bflag + r, tag);
                wait_flags(S->bflag, tag, lane);
                if (lane == 0) {
                    fence_async_all();
                    mbar_expect(bar_x, 32 * PROW);
                    bulk_g2s(sb + SB_QIMG, S->bpart + r * 32 * (PROW / 16), 32 * PROW, bar_x);
                }
            }
        }
        {
            const int b = tid >> 7, c4 = tid & 127;
            mbar_wait(bar_x, 1);
            TR(3);
            const float2 ml = *reinterpret_cast<const float2*>(sm + SB_QIMG + (b * 16 + (lane & 15)) * PROW + 2048);
            float MM = ml.x;
            MM = fmaxf(MM, shx(MM, 1)); MM = fmaxf(MM, shx(MM, 2)); MM = fmaxf(MM, shx(MM, 4)); MM = fmaxf(MM, shx(MM, 8));
            const float e = ex2((ml.x - MM) * LOG2E);
            float L = e * ml.y;
            L += shx(L, 1); L += shx(L, 2); L += shx(L, 4); L += shx(L, 8);
            const float wgt = e / L;
            float4 o = make_float4(0.f, 0.f, 0.f, 0.f);
#pragma unroll 4
            for (int i = 0; i < 16; i++) {
                const float w = __shfl_sync(0xffffffffu, wgt, i);
                const float4 v = *reinterpret_cast<const float4*>(sm + SB_QIMG + (b * 16 + i) * PROW + c4 * 16);
                o.x = fmaf(w, v.x, o.x); o.y = fmaf(w, v.y, o.y); o.z = fmaf(w, v.z, o.z); o.w = fmaf(w, v.w, o.w);
            }
            uint32_t* xh = reinterpret_cast<uint32_t*>(xs);
            const uint32_t h0 = packbf(o.x, o.y), h1 = packbf(o.z, o.w);
            *reinterpret_cast<uint2*>(xh + (2 * b) * 264 + c4 * 2) = make_uint2(h0, h1);
            *reinterpret_cast<uint2*>(xh + (2 * b + 1) * 264 + c4 * 2) =
                make_uint2(packbf(o.x - bflo(h0), o.y - bfhi(h0)), packbf(o.z - bflo(h1), o.w - bfhi(h1)));
            bar_sync(0, 256);
            mbar_wait(bar_w, 0);
            gemv_slice(sb, warp, lane);
            bar_sync(0, 256);
            if (tid < 64) {
                const float* y = yb + warp * 128 + 16 * g + 2 * tq;
                st_b128(S->frag[0] + (warp * 32 + r) * 32 + lane, make_uint4(packbf(y[0], y[1]), tag, packbf(y[8], y[9]), tag));
            }
        }
        TR(4);
    }
}

__global__ void __launch_bounds__(480, 1)
fused_decode_kernel(const Params P, const __grid_constant__ Maps M) {
    extern __shared__ __align__(1024) uint8_t sm[];
    const uint32_t sb = s2u(sm);
    const int tid = threadIdx.x, lane = tid & 31, bx = blockIdx.x;
    asm volatile("{\n.reg .pred p;\nsetp.lt.u32 p, %1, 256;\n@p prefetch.global.L2 [%0];\n}"
                 ::"l"(P.wq + (PFM ? (unsigned)(((bx & 1) * 256 + tid) * 8192 + (bx >> 1) * 128) : (unsigned)(bx * 32768 + tid * 128))), "r"(tid) : "memory");
    const int warp = __shfl_sync(0xffffffffu, tid >> 5, 0);
    const int g = lane >> 2, tq = lane & 3;
    Scratch* const S = P.scr;

    if (!(bx & 1)) {
        const int grp = (bx >> 1) & 1, crk = bx >> 2;
        const int rowbase = grp * (UPG * 64);
        auto issue = [&](int slot, unsigned tk, int v) {
            const int row = rowbase + (int)((tk & ~255u) | ((tk + grp * ROT) & 255u)) * 64;
            const uint32_t full = sb + SA_FULL + slot * 16 + v * 8;
            mbar_expect(full, 8192);
            tma2d_ef(sb + slot * 16384 + v * 8192, &M.kv[v], 0, row, full);
        };
        if (warp >= 8) {
            const int w = warp - 8;
            if (w >= NW) {
                if (w == NW && !(bx & XPM)) asm volatile("prefetch.global.L2 [%0];" ::"l"(((lane & 16) ? P.bx : P.ax) + (lane & 15) * 32) : "memory");
                return;
            }
            const bool one = elect();
            if (one) {
                mbar_init(sb + SA_FULL + w * 16, 1);
                mbar_init_fence();
                TR(3);
                sts32(sb + SA_META + w * 4, 0);
                if (w < SKEW) issue(w, w * CPG + crk, 0);
#pragma unroll
                for (int i = 0; i < SPW; i++) {
                    if (i) mbar_init(sb + SA_FULL + (w + i * NW) * 16, 1);
                    mbar_init(sb + SA_FULL + (w + i * NW) * 16 + 8, 1);
                    mbar_init(sb + SA_GOV + (w + i * NW) * 8, 1);
                    mbar_init(sb + SA_EMPTY + (w + i * NW) * 8, 2);
                    mbar_arrive(sb + SA_EMPTY + (w + i * NW) * 8);
                }
                if (w < SKEW) mbar_arrive(sb + SA_EMPTY + w * 8);
                sts32(sb + SA_LIM + w * 4, LIM);
                mbar_init_fence();
            }
            __syncwarp();
            bar_arrive(2, (NW + 1) * 32);
            bar_arrive(1, (2 * NW + 2) * 32);
            unsigned c = 0, tbase = 0;
            int slot = w;
            uint32_t eph = 0;
#pragma unroll 1
            for (int n = 0;; n++) {
                unsigned tk = (n * NW + w) * CPG + crk;
                if (n == SPW) {
                    mbar_wait(sb + SA_EMPTY + w * 8, 1);
                    tbase = NSL * CPG - lds32(sb + SA_CNT) * TICK_INC;
                }
                if (n >= SPW) {
                    const unsigned own = __shfl_sync(0xffffffffu, c, grp);
                    tk = own + tbase;
                    const int lag = (int)(__reduce_add_sync(0xffffffffu, c) - NG * own);
                    if (one) sts32(sb + SA_LIM + w * 4, lag > BAL * NG ? LIM + 1 : lag < -BAL * NG ? LIM - 1 : LIM);
                }
                mbar_wait(sb + SA_EMPTY + slot * 8, eph);
                if (tk >= UPG) {
                    if (one) { sts32(sb + SA_LIM + w * 4, 0); sts32(sb + SA_META + slot * 4, 32); mbar_arrive(sb + SA_FULL + slot * 16); }
                    return;
                }
                if (one && (n || w >= SKEW)) {
                    sts32(sb + SA_META + slot * 4, tk >> 8);
                    issue(slot, tk, 0);
                    if (tk == 1200) TR(6);
                    if (tk == UPG - FIRE_T) { st_b64(S->fire + grp, gt(), lds32(sb + SA_CNT) + 1); TR(4); }
                }
                if (n >= SPW - 1) {
                    if (lane == grp) c = atom_inc(S->ctr + lane);
                    else if (lane < NG) c = ld_relaxed1(S->ctr + lane);
                }
                mbar_wait(sb + SA_GOV + slot * 8, eph);
                if (one) issue(slot, tk, 1);
                TR(0);
                slot += NW;
                if (slot >= NSL) { slot -= NSL; eph ^= 1; }
                __syncwarp();
            }
        }
        if (warp == 0) {
            bool busy = lane < 2 * SKEW && !(lane & 1);
            uint32_t par = busy ? 0 : 1;
            int slot = SKEW;
            bool first = true;
            const unsigned c0 = clk32() + RAMP_T0;
            const int own = lane >= 2 * NSL ? -1 : ((lane >> 1) + (lane & 1) * SKEW) % NSL;
            const uint32_t fb = sb + SA_FULL + lane * 8, lw = sb + SA_LIM + ((lane >> 1) % NW) * 4;
            const uint32_t go = sb + ((lane & 1) ? SA_GOV : SA_EMPTY) + (lane >> 1) * 8;
            bar_sync(2, (NW + 1) * 32);
#pragma unroll 1
            for (int it = 0; it < SPIN_MAX; it++) {
                bool ok = true;
                if (busy) ok = mbar_test(fb, par);
                int lim = lds32(lw);
                if (first) lim = min(LIM0, SKEW + max((int)(clk32() - c0), 0) / RAMP_S);
                busy = busy && !ok && lim;
                const int n = __popc(__ballot_sync(0xffffffffu, busy));
                if (!__any_sync(0xffffffffu, lim)) return;
                const bool mine = own == slot && lim;
                if (!__any_sync(0xffffffffu, mine && (busy || n > lim - 2))) {
                    if (mine) { mbar_arrive(go); busy = true; par ^= 1; }
                    if (++slot == NSL) { slot = 0; first = false; }
                    it = 0;
                }
            }
            __trap();
        }
        {
            int w3 = warp;
            asm volatile("" : "+r"(w3));
            if (w3 == 3) return;
        }
        if (warp == 1) {
            const uint4* const qsrc = S->qpub + grp * 1024 + lane;
            uint2* const qdst = reinterpret_cast<uint2*>(sm + SA_Q) + lane;
            const unsigned epoch = ld_relaxed1(S->epoch + bx * 8);
            if (lane == 0) {
                mbar_init(sb + SA_QBAR, 32);
                mbar_init(sb + SA_QBAR + 8, 32);
                mbar_init(sb + SA_QBAR + 16, 32);
#pragma unroll
                for (int i = 0; i < 8; i++) { mbar_init(sb + SA_MBAR + i * 16, NW); mbar_init(sb + SA_MBAR + i * 16 + 8, 1); }
                mbar_init_fence();
                sts32(sb + SA_CNT, epoch);
            }
            __syncwarp();
            bar_arrive(1, (2 * NW + 2) * 32);
            if (lane == 0) S->epoch[bx * 8] = epoch + 1;
            __nanosleep(QSLEEP);
            for (int it = 0;; it++) {
                const uint4 u = ld_b128(qsrc);
                if (__all_sync(0xffffffffu, u.y == epoch + 1)) { qdst[0] = make_uint2(u.x, u.z); break; }
                if (it > SPIN_MAX) __trap();
            }
            mbar_arrive(sb + SA_QBAR);
#pragma unroll 1
            for (int h = 0, it = 0; h < 32; it++) {
                uint4 v[8];
                bool ok = true;
#pragma unroll
                for (int k = 0; k < 8; k++) v[k] = ld_b128(qsrc + (h + k) * 32);
#pragma unroll
                for (int k = 0; k < 8; k++) { ok = ok && v[k].y == epoch + 1; qdst[(h + k) * 32] = make_uint2(v[k].x, v[k].z); }
                if (__all_sync(0xffffffffu, ok)) {
                    if (!h) mbar_arrive(sb + SA_QBAR + 8);
                    h += 8;
                } else if (QPOLL) __nanosleep(QPOLL);
                if (it > SPIN_MAX) __trap();
            }
            mbar_arrive(sb + SA_QBAR + 16);
            return;
        }
        bar_sync(1, (2 * NW + 2) * 32);
        if (warp == 2) {
            const uint32_t t8 = (lds32(sb + SA_CNT) + 1) & 0xffu;
            uint4* dst = S->apart + (grp * 32 * CPG + crk) * 32 + lane;
            uint2* dml = S->aml + (grp * 32 * CPG + crk) * 4 + (lane & 3);
#pragma unroll 1
            for (int h = 0; h < 32; h++, dst += CPG * 32, dml += CPG * 4) {
                const float* s0 = reinterpret_cast<const float*>(sm + SA_SLOT) + (h & 7) * (NW * 132);
                mbar_wait(sb + SA_MBAR + (h & 7) * 16, (h >> 3) & 1);
                float2 ml[NW];
                float4 v[NW];
#pragma unroll
                for (int w = 0; w < NW; w++) {
                    ml[w] = *reinterpret_cast<const float2*>(s0 + w * 132 + 128);
                    v[w] = *reinterpret_cast<const float4*>(s0 + w * 132 + lane * 4);
                }
                const float MM = fmaxf(fmaxf(ml[0].x, ml[1].x), fmaxf(ml[2].x, ml[3].x));
                float e[NW];
#pragma unroll
                for (int w = 0; w < NW; w++) e[w] = ex2((ml[w].x - MM) * LOG2E);
                st_b128(dst, make_uint4(tagf(fmaf(e[0], v[0].x, e[1] * v[1].x) + fmaf(e[2], v[2].x, e[3] * v[3].x), t8),
                                        __float_as_uint(fmaf(e[0], v[0].y, e[1] * v[1].y) + fmaf(e[2], v[2].y, e[3] * v[3].y)),
                                        __float_as_uint(fmaf(e[0], v[0].z, e[1] * v[1].z) + fmaf(e[2], v[2].z, e[3] * v[3].z)),
                                        __float_as_uint(fmaf(e[0], v[0].w, e[1] * v[1].w) + fmaf(e[2], v[2].w, e[3] * v[3].w))));
                if (lane < 4) st_b64(dml, __float_as_uint(MM), tagf(fmaf(e[0], ml[0].y, e[1] * ml[1].y) + fmaf(e[2], ml[2].y, e[3] * ml[3].y), t8));
                TR(2);
                if (PLACE && (h == 27 || h == 28)) {
                    st_b128(dst + 3 * CPG * 32, make_uint4(t8 ^ 0x80u, 0, 0, 0));
                    if (lane < 4) st_b64(dml + 3 * CPG * 4, 0, t8 ^ 0x80u);
                }
                __syncwarp();
                if (lane == 0) mbar_arrive(sb + SA_MBAR + (h & 7) * 16 + 8);
            }
            TROUT();
            return;
        }
        const int cw = warp - 4;
        uint32_t koff[4], voff[4];
#pragma unroll
        for (int i = 0; i < 4; i++) {
            koff[i] = ((lane & 7) + 8 * ((lane >> 3) & 1)) * 128 + (((2 * i + (lane >> 4)) ^ (lane & 7)) << 4);
            voff[i] = ((lane & 7) + 8 * (lane >> 4)) * 128 + (((2 * i + ((lane >> 3) & 1)) ^ (lane & 7)) << 4);
        }
        uint32_t psel[4][2];
#pragma unroll
        for (int i = 0; i < 4; i++) {
            psel[i][0] = (g >> 1) != i ? 0x4444u : (g & 1) ? 0x1044u : 0x4410u;
            psel[i][1] = (g >> 1) != i ? 0x4444u : (g & 1) ? 0x3244u : 0x4432u;
        }
        uint32_t qf[4][2];
        auto load_q = [&](int pl) {
            const uint32_t q = sb + SA_Q + pl * 256 + ((g & 1) * 32 + tq) * 4;
#pragma unroll
            for (int ks = 0; ks < 4; ks++) { qf[ks][0] = lds32(q + ks * 32); qf[ks][1] = lds32(q + ks * 32 + 16); }
        };
        mbar_wait(sb + SA_QBAR, 0);
        TR(0);
        load_q(0);
        float acc[4][4], m = -FLT_MAX, l = 0.f, ls = 0.f;
#pragma unroll
        for (int i = 0; i < 4; i++) acc[i][0] = acc[i][1] = acc[i][2] = acc[i][3] = 0.f;
        int slot = cw, cur = 0;
        uint32_t ph = 0;
#pragma unroll 1
        for (;;) {
            mbar_wait(sb + SA_FULL + slot * 16, ph);
            const int pl = lds32(sb + SA_META + slot * 4);
            if (pl != cur) {
#pragma unroll 1
                do {
                    float* s0 = reinterpret_cast<float*>(sm + SA_SLOT) + ((cur & 7) * NW + cw) * 132;
                    float* sw = s0 + tq * 16 + (g >> 1) * 4 + (g & 1);
                    sw[0] = (acc[0][0] + acc[1][0]) + (acc[2][0] + acc[3][0]);
                    sw[2] = (acc[0][2] + acc[1][2]) + (acc[2][2] + acc[3][2]);
                    sw[64] = (acc[0][1] + acc[1][1]) + (acc[2][1] + acc[3][1]);
                    sw[66] = (acc[0][3] + acc[1][3]) + (acc[2][3] + acc[3][3]);
                    if (lane == 0) *reinterpret_cast<float2*>(s0 + 128) = make_float2(m, ls);
                    __syncwarp();
                    if (lane == 0) mbar_arrive(sb + SA_MBAR + (cur & 7) * 16);
                    if (++cur == 32) { TROUT(); return; }
#pragma unroll
                    for (int i = 0; i < 4; i++) acc[i][0] = acc[i][1] = acc[i][2] = acc[i][3] = 0.f;
                    m = -FLT_MAX; l = ls = 0.f;
                    mbar_wait(sb + SA_MBAR + (cur & 7) * 16 + 8, ((cur >> 3) & 1) ^ 1);
                    if (cur == 1 || cur == 8) mbar_wait(sb + SA_QBAR + 8 + (cur & 8), 0);
                } while (cur != pl);
                load_q(pl);
            }
            float s4[4][4];
            const uint32_t kb = sb + slot * 16384;
#pragma unroll
            for (int j = 0; j < 4; j++) {
                s4[j][0] = s4[j][1] = s4[j][2] = s4[j][3] = 0.f;
                const bool on = (g >> 1) == j;
#pragma unroll
                for (int ks = 0; ks < 4; ks++) {
                    uint32_t a[4];
                    ldsm4(a, kb + j * 2048 + koff[ks]);
                    mma16816(s4[j], a, on ? qf[ks][0] : 0u, on ? qf[ks][1] : 0u);
                }
            }
            float d[4];
#pragma unroll
            for (int r = 0; r < 4; r++) d[r] = (s4[0][r] + s4[1][r]) + (s4[2][r] + s4[3][r]);
            float sa = (g & 1) ? d[1] : d[0], sc = (g & 1) ? d[3] : d[2];
            sa += shx(sa, 4); sc += shx(sc, 4);
            uint32_t sp = packbf(sa, sc);
            sp = packbf(bflo(sp) * SCALE, bfhi(sp) * SCALE);
            sa = bflo(sp); sc = bfhi(sp);
            const float mx = warp_max(fmaxf(fmaxf(sa, sc), m));
            const float alpha = ex2((m - mx) * LOG2E);
            m = mx;
            const float pa = ex2((sa - mx) * LOG2E), pc = ex2((sc - mx) * LOG2E);
            const uint32_t pk = packbf(pa, pc);
            uint32_t pb[4][4][2];
#pragma unroll
            for (int j = 0; j < 4; j++) {
                const uint32_t pj = __shfl_sync(0xffffffffu, pk, 8 * tq + j);
#pragma unroll
                for (int i = 0; i < 4; i++) { pb[j][i][0] = prmt0(pj, psel[i][0]); pb[j][i][1] = prmt0(pj, psel[i][1]); }
            }
            l = fmaf(l, alpha, pa + pc);
            ls = l + shx(l, 8);
#pragma unroll
            for (int i = 0; i < 4; i++) { acc[i][0] *= alpha; acc[i][1] *= alpha; acc[i][2] *= alpha; acc[i][3] *= alpha; }
            mbar_wait(sb + SA_FULL + slot * 16 + 8, ph);
            TR(1);
            const uint32_t vb = kb + 8192;
#pragma unroll
            for (int i = 0; i < 4; i++)
#pragma unroll
                for (int j = 0; j < 4; j++) {
                    uint32_t a[4];
                    ldsm4t(a, vb + j * 2048 + voff[i]);
                    mma16816(acc[j], a, pb[j][i][0], pb[j][i][1]);
                }
            ls += shx(ls, 16); ls += shx(ls, 1); ls += shx(ls, 2);
            __syncwarp();
            if (lane == 0) mbar_arrive(sb + SA_EMPTY + slot * 8);
            slot += NW;
            if (slot >= NSL) { slot -= NSL; ph ^= 1; }
        }
    }

    const int r = bx >> 2, isC = (bx >> 1) & 1;
    const uint32_t bar_h = sb + SB_BAR + 32;
    if (warp == 8 && !isC) {
        const unsigned c0 = clk32();
        bar_sync(7, 64);
        while ((int)(clk32() - c0) < BSTART + (r & 7) * BSTAG) {}
        if (elect()) load_slice(sb + SB_STG, &M.qb, r, sb + SB_BAR + 16);
        __syncwarp();
    }
    if (warp < 8) {
    {
        const uint32_t bar_q = bar_h + (NT + warp) * 8, box = sb + SB_QIMG + warp * 8192;
        if (elect()) {
            mbar_init(bar_q, 1);
            mbar_init_fence();
            mbar_expect(bar_q, 8192 + 256);
            tma2d(box, &M.qa, (bx >> 1) * 64, warp * 64, bar_q);
        }
        __syncwarp();
        unsigned epoch = 0;
        if (warp < 2) epoch = ld_relaxed1(S->epoch + bx * 8);
        uint4* const qdst = S->qpub + ((lane >> 4) * 32 + r) * 32 + isC * 16 + (lane & 15);
        if (PLACE && warp == 0) st_b128(qdst, make_uint4(0, 0, 0, 0));
        if (elect()) {
            for (const unsigned c0 = clk32(); (int)(clk32() - c0) < XD0 + (bx >> 1) * XDS;) {}
            bulk_g2s(sb + SB_P + 4096 + warp * 288, P.ax + warp * 32, 128, bar_q);
            bulk_g2s(sb + SB_P + 4096 + warp * 288 + 144, P.ax + 256 + warp * 32, 128, bar_q);
        }
        if (tid == 32) {
#pragma unroll
            for (int i = 0; i < 4 + NT; i++) mbar_init(sb + SB_BAR + i * 8, 1);
            mbar_init_fence();
            sts32(sb + SB_CNT, epoch);
            sts32(sb + SB_CNT + 4, 0);
        }
        __syncwarp();
        if (warp == 1 && !isC) bar_arrive(7, 64);
        mbar_wait(bar_q, 0);
        TR(0);
        uint32_t b[8];
#pragma unroll
        for (int i = 0; i < 8; i++) b[i] = lds32(sb + SB_P + 4096 + warp * 288 + (g & 1) * 144 + tq * 4 + i * 16);
        float d[4][4];
        uint32_t a[4][4][4];
#pragma unroll
        for (int i = 0; i < 4; i++) {
            d[i][0] = d[i][1] = d[i][2] = d[i][3] = 0.f;
#pragma unroll
            for (int ks = 0; ks < 4; ks++)
                ldsm4t(a[i][ks], box + ks * 2048 + ((lane & 7) + 8 * (lane >> 4)) * 128 + (((2 * i + ((lane >> 3) & 1)) ^ (lane & 7)) << 4));
        }
#pragma unroll
        for (int ks = 0; ks < 4; ks++)
#pragma unroll
            for (int i = 0; i < 4; i++) mma16816(d[i], a[i][ks], b[2 * ks], b[2 * ks + 1]);
        float* qred = reinterpret_cast<float*>(sm + SB_P);
#pragma unroll
        for (int c = 0; c < 4; c++)
            qred[warp * 128 + (c & 1) * 64 + tq * 16 + (c >> 1) * 8 + g] = tq == 0 ? d[0][c] : tq == 1 ? d[1][c] : tq == 2 ? d[2][c] : d[3][c];
        bar_sync(0, 256);
        if (warp == 0) {
            float4 v[8];
#pragma unroll
            for (int w = 0; w < 8; w++) v[w] = *reinterpret_cast<const float4*>(qred + w * 128 + lane * 4);
#pragma unroll
            for (int o = 4; o; o >>= 1)
#pragma unroll
                for (int w = 0; w < o; w++) { v[w].x += v[w + o].x; v[w].y += v[w + o].y; v[w].z += v[w + o].z; v[w].w += v[w + o].w; }
            st_b128(qdst, make_uint4(packbf(v[0].x, v[0].y), epoch + 1, packbf(v[0].z, v[0].w), epoch + 1));
            if (lane == 0) S->epoch[bx * 8] = epoch + 1;
        }
        TR(1);
    }
    if (!isC) latent_branch(P, M, sm TRPASS);
    bar_arrive(6, 288);
    }

    constexpr int ND = 2;
    const int isA = (r >> JMAP) & 1, cb = ((r >> (JMAP + 1)) << JMAP) + (r & ((1 << JMAP) - 1)), nsnd = isA ? NSA : NSB, isCA = isC & isA;
    const int y0 = isC ? nsnd : 0, y1 = isC ? 32 - ND * isA : nsnd;
    const int nreq = isC ? 32 - nsnd : nsnd;
    const int nmw = isC && !isA ? NMW : 0;
    float* const red = reinterpret_cast<float*>(sm + SC_RED);
    const uint32_t wlane = wo_lane(sb, lane);
    auto fetch_frag = [&](int y, int b, unsigned tag, unsigned ns) {
        for (int it = 0;; it++) {
            const uint4 v = ld_b128(S->frag[0] + isA * 2048 + (b * 32 + y) * 32 + lane);
            if (__all_sync(0xffffffffu, v.y == tag)) {
                reinterpret_cast<uint2*>(sm + SC_FR)[(y * 32 + (g >> 1) * 8 + b * 4 + tq) * 2 + (g & 1)] = make_uint2(v.x, v.z);
                return;
            }
            if (it > SPIN_MAX) __trap();
            __nanosleep(ns);
        }
    };
    if (warp < 8) {
        const unsigned tag = lds32(sb + SB_CNT) + 1;
        const uint32_t t8 = tag & 0xffu;
        uint32_t bs[2], wf[4][4];
        float d[2][4];
        const uint32_t wa = (wlane ^ ((warp & 1) * 32)) + (warp & 2) * 2048;
        const int ks0 = (warp & 2) * 2;
        if (isC) __nanosleep(4000);
#pragma unroll 1
        for (int op = isCA ? 0 : 1;; op++) {
            const int step = isCA ? max(op - 1, 0) : 0, h = step ? 31 - ND + step : isA ? cb : 16 + cb;
            if (op != 1) {
                if (!isCA && (!isC || h >= 32 - ND)) break;
                const int rec = ((warp >> 2) * 32 + h) * CPG + (warp & 3) * 8;
                const uint2* mlp = S->aml + (rec + (lane & 7)) * 4;
                const uint4* src = S->apart + rec * 32 + lane;
                asm volatile("" : "+l"(mlp), "+l"(src));
                if (!step) {
                    for (int it = 0; !__all_sync(0xffffffffu, (ld_b64(mlp).y & 0xffu) == t8); it++) {
                        if (it > SPIN_MAX) __trap();
                        __nanosleep(h > 25 ? DPOLL : CPOLL);
                    }
                } else if (step < ND) {
                    mbar_wait(sb + SB_BAR + 8, 0);
                } else {
                    d[0][0] = d[0][1] = d[0][2] = d[0][3] = d[1][0] = d[1][1] = d[1][2] = d[1][3] = 0.f;
#pragma unroll
                    for (int k = 0; k < ND; k++) {
                        mbar_wait(bar_h + k * 16 + (warp & 2) * 4, 0);
#pragma unroll
                        for (int ks = 0; ks < 4; ks++) ldsm4t(wf[ks], wa + k * 8192 + ks * 1024);
                        if (k < ND - 1) {
#pragma unroll
                            for (int ks = 0; ks < 4; ks++) mma16816(d[ks & 1], wf[ks], g == ks0 + ks ? bs[0] : 0u, g == ks0 + ks ? bs[1] : 0u);
                        }
                    }
                    mbar_wait(sb + SB_BAR, 0);
                }
                TR(3);
                uint4 v[8];
                uint2 ml = ld_b64(mlp);
#pragma unroll
                for (int i = 0; i < 8; i++) v[i] = ld_b128(src + i * 32);
                for (int it = 0;; it++) {
                    unsigned x = ml.y ^ t8;
#pragma unroll
                    for (int i = 0; i < 8; i++) x |= v[i].x ^ t8;
                    if (!__any_sync(0xffffffffu, x & 0xffu)) break;
                    if (it > SPIN_MAX) __trap();
                    ml = ld_b64(mlp);
#pragma unroll
                    for (int i = 0; i < 8; i++)
                        if ((v[i].x & 0xffu) != t8) v[i] = ld_b128(src + i * 32);
                }
                TR(2);
                const float mw = warp_max(__uint_as_float(ml.x)), e = ex2((__uint_as_float(ml.x) - mw) * LOG2E);
                float L = e * __uint_as_float(ml.y), oa[4], ob[4];
                L += shx(L, 1);
#pragma unroll
                for (int i = 0; i < 8; i++) {
                    const float w = __shfl_sync(0xffffffffu, e, i);
                    float (&o)[4] = (i & 1) ? ob : oa;
                    o[0] = i < 2 ? w * __uint_as_float(v[i].x) : fmaf(w, __uint_as_float(v[i].x), o[0]);
                    o[1] = i < 2 ? w * __uint_as_float(v[i].y) : fmaf(w, __uint_as_float(v[i].y), o[1]);
                    o[2] = i < 2 ? w * __uint_as_float(v[i].z) : fmaf(w, __uint_as_float(v[i].z), o[2]);
                    o[3] = i < 2 ? w * __uint_as_float(v[i].w) : fmaf(w, __uint_as_float(v[i].w), o[3]);
                }
                float* fp = reinterpret_cast<float*>(sm + SC_FP) + ((step & 1) * 8 + (warp & 4)) * 132;
                *reinterpret_cast<float4*>(fp + (warp & 3) * 132 + lane * 4) = make_float4(oa[0] + ob[0], oa[1] + ob[1], oa[2] + ob[2], oa[3] + ob[3]);
                L += shx(L, 2);
                L += shx(L, 4);
                if (lane == 0) *reinterpret_cast<float2*>(fp + (warp & 3) * 132 + 128) = make_float2(mw, L);
                bar_sync(1 + (warp >> 2), 128);
                float2 q[4];
                float4 u[4];
#pragma unroll
                for (int w = 0; w < 4; w++) {
                    q[w] = *reinterpret_cast<const float2*>(fp + w * 132 + 128);
                    u[w] = *reinterpret_cast<const float4*>(fp + w * 132 + lane * 4);
                }
                const float MM = fmaxf(fmaxf(q[0].x, q[1].x), fmaxf(q[2].x, q[3].x));
                float f[4], inv;
#pragma unroll
                for (int w = 0; w < 4; w++) f[w] = ex2((q[w].x - MM) * LOG2E);
                asm("rcp.approx.ftz.f32 %0, %1;" : "=f"(inv) : "f"(fmaf(f[0], q[0].y, f[1] * q[1].y) + fmaf(f[2], q[2].y, f[3] * q[3].y)));
                const uint32_t b0 = packbf((fmaf(f[0], u[0].x, f[1] * u[1].x) + fmaf(f[2], u[2].x, f[3] * u[3].x)) * inv,
                                           (fmaf(f[0], u[0].y, f[1] * u[1].y) + fmaf(f[2], u[2].y, f[3] * u[3].y)) * inv);
                const uint32_t b1 = packbf((fmaf(f[0], u[0].z, f[1] * u[1].z) + fmaf(f[2], u[2].z, f[3] * u[3].z)) * inv,
                                           (fmaf(f[0], u[0].w, f[1] * u[1].w) + fmaf(f[2], u[2].w, f[3] * u[3].w)) * inv);
                if (step == ND) {
#pragma unroll
                    for (int ks = 0; ks < 4; ks++) mma16816(d[ks & 1], wf[ks], g == ks0 + ks ? b0 : 0u, g == ks0 + ks ? b1 : 0u);
                    const float x0 = (d[0][0] + d[0][1]) + (d[1][0] + d[1][1]), x1 = (d[0][2] + d[0][3]) + (d[1][2] + d[1][3]);
                    const float z = ((tq & 1) ? x1 : x0) + shx((tq & 1) ? x0 : x1, 1);
                    if ((tq & 2) == (warp & 2)) red[(6 + (tq >> 1)) * 80 + (warp >> 2) * 40 + (warp & 1) * 16 + (tq & 1) * 8 + g] = z;
                    bar_arrive(5, 480);
                    TR(5);
                    TROUT();
                    return;
                }
                bs[0] = b0; bs[1] = b1;
                if (!step && !(warp & 3)) st_b128(S->frag[1] + ((warp >> 2) * 32 + h) * 32 + lane, make_uint4(b0, tag, b1, 0));
                if (!isCA) break;
            } else {
#pragma unroll 1
                for (int y = y0 + ((warp - y0) & 3); y < y1 - 3 * isCA; y += 4) fetch_frag(y, warp >> 2, tag, CPOLL);
                TR(6);
                if (warp >= nmw) bar_arrive(4, 448);
            }
        }
        if (warp >= nmw) { TROUT(); return; }
    }
    if (warp == 14) {
        bar_sync(6, 288);
        const CUtensorMap* map = &M.wo[isA];
        const unsigned tag = lds32(sb + SB_CNT) + 1;
        const uint32_t t8 = tag & 0xffu;
        uint2* const snd = S->snd + r * 32 + lane;
        asm volatile("prefetch.tensormap [%0];" ::"l"(map) : "memory");
        if (PLACE && !isC) st_b64(snd, t8 ^ 0x80u, 0);
        for (int it = 0; ld_b128(S->frag[1] + 25 * 32).y != tag; it++) {
            if (it > SPIN_MAX) __trap();
            __nanosleep(2000);
        }
        uint2 f;
        for (int it = 0;; it++) {
            f = ld_b64(S->fire + (lane & 1));
            if (__all_sync(0xffffffffu, f.y == tag)) break;
            if (it > SPIN_MAX) __trap();
            __nanosleep(FPOLL);
        }
        const unsigned t0 = __shfl_sync(0xffffffffu, f.x, 0);
        unsigned t1 = t0 + (__reduce_add_sync(0xffffffffu, (int)(f.x - t0)) >> 5) + FIRE_NS;
        TR(2);
        if (elect()) {
            const int n1 = nreq - (isC ? (isA ? NLA : NLB) : 0);
            const int dt = !isC ? (isA ? FIRE_W / NSA : FIRE_W / NSB) : isA ? FIRE_W / (32 - NSA - NLA) : FIRE_W / (32 - NSB - NLB);
            unsigned t2 = t1 + REC0_NS;
            int rec = isCA ? 2 : 0;
            int y = isCA ? 32 - ND : y0;
#pragma unroll 1
            for (int i = 0; i < nreq; i++) {
                const int row = y * 128;
                mbar_expect(bar_h + i * 16, 4096);
                mbar_expect(bar_h + i * 16 + 8, 4096);
                if (++y == 32) y = y0;
                if (i <= n1) {
                    unsigned t;
                    for (int it = 0; (int)((t = gt()) - t1) < 0 && it < 4096; it++) {}
                    t1 += dt;
                    if (rec && (int)(t - t2) >= 0) { mbar_arrive(sb + SB_BAR + --rec * 8); t2 += REC_NS - REC0_NS; }
                }
                tma2d(sb + i * 8192, map, cb * 32, row, bar_h + i * 16);
                tma2d(sb + i * 8192 + 4096, map, cb * 32, row + 64, bar_h + i * 16 + 8);
            }
            TR(3);
            while (rec) {
                for (int it = 0; (int)(gt() - t2) < 0 && it < 4096; it++) {}
                mbar_arrive(sb + SB_BAR + --rec * 8);
                t2 += REC_NS - REC0_NS;
            }
        }
        __syncwarp();
        uint32_t* dst = reinterpret_cast<uint32_t*>(P.out) + (lane >> 4) * 512 + (isA ? 0 : 256) + cb * 16 + (lane & 15);
        uint32_t q = sb + SC_RED + ((lane >> 4) * 20 + (lane & 15)) * 8;
        asm volatile("" : "+l"(dst), "+r"(q));
        if (!isC) {
            const float2 s = sum_parts<6, 224>(q, 0.f, 0.f);
            st_b64(snd, tagf(s.x, t8), __float_as_uint(s.y));
        } else {
            uint2 o;
            for (int it = 0;; it++) {
                o = ld_b64(snd);
                if (__all_sync(0xffffffffu, (o.x & 0xffu) == t8)) break;
                if (it > SPIN_MAX) __trap();
            }
            TR(4);
            if (isA) {
                const float2 s = sum_parts<8, 480>(q, __uint_as_float(o.x), __uint_as_float(o.y));
                asm volatile("st.global.u32 [%0], %1;" ::"l"(dst), "r"(packbf(s.x, s.y)) : "memory");
            } else {
                const float2 s = sum_parts<6 + NMW, 224 + 32 * NMW>(q, __uint_as_float(o.x), __uint_as_float(o.y));
                asm volatile("st.global.b32 [%0], %1;" ::"l"(dst), "r"(packbf(s.x, s.y)) : "memory");
            }
        }
        TR(6);
        TROUT();
        return;
    }
    {
        const int nw = 6 + nmw, wi = warp < 8 ? warp + 6 : warp - 8, t0 = wi + 2 * ND * isCA;
        bar_sync(4, 448);
        if (isCA) {
            const int y = y0 - ND + ((2 * nreq - 1 - (2 * nreq - 1 - t0) % 6) >> 1);
            const unsigned tag = lds32(sb + SB_CNT) + 1;
#pragma unroll 1
            for (int b = 0; b < 2; b++) fetch_frag(y, b, tag, DPOLL);
            __syncwarp();
            TR(6);
        }
        uint32_t rx = sb + SC_RED + (wi * 80 + (tq & 1) * 40 + (tq >> 1) * 16 + g) * 4, nb = isCA ? 480 : 224 + nmw * 32;
        asm volatile("" : "+r"(rx), "+r"(nb));
        float e[4][4];
#pragma unroll
        for (int i = 0; i < 4; i++) e[i][0] = e[i][1] = e[i][2] = e[i][3] = 0.f;
        uint32_t bp = sb + SC_FR + ((2 * (y0 - ND * isCA) + t0) * 16 + (lane & 7)) * 16, wa = wlane + t0 * 4096, bar = bar_h + t0 * 8;
        uint4 b0 = lds128(bp), b1 = lds128(bp + 128);
        const uint32_t zero = lds32(sb + SB_CNT + 4);
#pragma unroll 1
        for (int t = t0;;) {
            uint32_t a[8][4];
            b0.x ^= zero; b1.x ^= zero;
            asm volatile("" : "+r"(b0.x), "+r"(b1.x));
            mbar_wait(bar, 0);
#pragma unroll
            for (int j = 0; j < 8; j++) ldsm4t(a[j], (wa ^ ((j & 1) * 32)) + (j >> 1) * 1024);
            bp += nw * 256;
            const uint4 n0 = lds128(bp), n1 = lds128(bp + 128);
#pragma unroll
            for (int j = 0; j < 8; j++) {
                const uint4& c = (j & 4) ? b1 : b0;
                mma16816(e[(j & 1) * 2 + ((j >> 1) & 1)], a[j], (j & 2) ? c.z : c.x, (j & 2) ? c.w : c.y);
            }
            t += nw;
            if (t >= 2 * nreq) break;
            wa += nw * 4096; bar += nw * 8;
            b0 = n0; b1 = n1;
        }
        float s4[4];
#pragma unroll
        for (int c = 0; c < 4; c++) s4[c] = (tq & 2) ? e[2][c] + e[3][c] : e[0][c] + e[1][c];
        sts32(rx, __float_as_uint((tq & 1) ? s4[1] : s4[0]));
        sts32(rx + 32, __float_as_uint((tq & 1) ? s4[3] : s4[2]));
        bar_arrive(5, nb);
        TROUT();
    }
}

typedef CUresult (*EncodeFn)(CUtensorMap*, CUtensorMapDataType, cuuint32_t, void*, const cuuint64_t*, const cuuint64_t*,
                             const cuuint32_t*, const cuuint32_t*, CUtensorMapInterleave, CUtensorMapSwizzle,
                             CUtensorMapL2promotion, CUtensorMapFloatOOBfill);

void make_map(EncodeFn enc, CUtensorMap* m, const void* base, uint64_t cols, uint64_t rows, uint32_t bc, uint32_t br,
              CUtensorMapL2promotion promo, CUtensorMapSwizzle sw = CU_TENSOR_MAP_SWIZZLE_128B) {
    cuuint64_t dims[2] = {cols, rows};
    cuuint64_t strides[1] = {cols * 2};
    cuuint32_t box[2] = {bc, br};
    cuuint32_t es[2] = {1, 1};
    enc(m, CU_TENSOR_MAP_DATA_TYPE_BFLOAT16, 2, const_cast<void*>(base), dims, strides, box, es,
        CU_TENSOR_MAP_INTERLEAVE_NONE, sw, promo, CU_TENSOR_MAP_FLOAT_OOB_FILL_NONE);
}

}

extern "C" void kernel_launch(void* const* d_in, const int* in_sizes, int n_in, void* d_out, int out_size) {
    (void)in_sizes; (void)n_in; (void)out_size;
    static EncodeFn enc = nullptr;
    static void* scr = nullptr;
    if (!enc) {
        void* fn = nullptr;
        cudaDriverEntryPointQueryResult qr;
        cudaGetDriverEntryPoint("cuTensorMapEncodeTiled", &fn, cudaEnableDefault, &qr);
        enc = (EncodeFn)fn;
        cudaGetSymbolAddress(&scr, g_scr);
        cudaFuncSetAttribute(fused_decode_kernel, cudaFuncAttributeMaxDynamicSharedMemorySize, SMEM_BYTES);
    }
    Maps m;
    make_map(enc, &m.kv[0], d_in[1], 64, 1048576, 64, 64, CU_TENSOR_MAP_L2_PROMOTION_NONE);
    make_map(enc, &m.kv[1], d_in[2], 64, 1048576, 64, 64, CU_TENSOR_MAP_L2_PROMOTION_NONE);
    make_map(enc, &m.qa, d_in[3], 4096, 512, 64, 64, CU_TENSOR_MAP_L2_PROMOTION_NONE);
    make_map(enc, &m.qb, d_in[7], 4096, 512, 64, 256, SPROMO);
    make_map(enc, &m.wo[0], d_in[10], 512, 4096, 32, 64, WPROMO, CU_TENSOR_MAP_SWIZZLE_64B);
    make_map(enc, &m.wo[1], d_in[4], 512, 4096, 32, 64, WPROMO, CU_TENSOR_MAP_SWIZZLE_64B);
    {
        cuuint64_t dims[4] = {64, 8, 8, 2048}, strides[3] = {1024, 128, 8192};
        cuuint32_t box[4] = {64, 8, 8, 8}, es[4] = {1, 1, 1, 1};
        enc(&m.c, CU_TENSOR_MAP_DATA_TYPE_BFLOAT16, 4, d_in[6], dims, strides, box, es, CU_TENSOR_MAP_INTERLEAVE_NONE,
            CU_TENSOR_MAP_SWIZZLE_128B, CU_TENSOR_MAP_L2_PROMOTION_NONE, CU_TENSOR_MAP_FLOAT_OOB_FILL_NONE);
    }
    make_map(enc, &m.uk, d_in[8], 4096, 512, 64, 256, SPROMO);
    make_map(enc, &m.uv, d_in[9], 4096, 512, 64, 256, SPROMO);
    Params p;
    p.scr = (Scratch*)scr;
    p.ax = (const uint32_t*)d_in[0];
    p.bx = (const uint32_t*)d_in[5];
    p.out = (__nv_bfloat16*)d_out;
    p.wq = (const char*)d_in[3];
    fused_decode_kernel<<<128, 480, SMEM_BYTES, cudaStreamPerThread>>>(p, m);
}
```

```cpp
#include <cuda_runtime.h>
#include <cuda_bf16.h>
#include <cuda.h>
#include <stdint.h>
#include <float.h>

#define LIM 12
#define LIM0 8
#define RAMP_S 256
#define RAMP_T0 300
#define BAL 20
#define SKEW 3
#define ROT 128
#define FIRE_T 240
#define FIRE_NS 3300
#define FIRE_W 1950
#define NLA 6
#define NLB 10
#define NSA 13
#define NSB 13
#define REC_NS 1700
#define JMAP 2
#define WPROMO CU_TENSOR_MAP_L2_PROMOTION_L2_128B
#define REC0_NS 100
#define DPOLL 300
#define PFM 1
#define QPOLL 300
#define BSTAG 500
#define SPROMO CU_TENSOR_MAP_L2_PROMOTION_NONE
#define XD0 1000
#define XDS 12
#define XPM 15
#define XPOS 1
#define NMW 6
#define EFW 3
#define PL2 7
#define FS ((PL2 & 4) ? 8 : 1)
#define PLACE 1
#define BSTART 3000
#define QSLEEP 1500
#define BPOLL 1000
#define CPOLL 700
#define FPOLL 300

namespace {

constexpr int NG = 2, CPG = 32, NW = 4;
constexpr int UPG = 8192;
constexpr int NSL = 12, SPW = NSL / NW;
constexpr int SPIN_MAX = 1 << 22;
constexpr float LOG2E = 1.4426950408889634f;
constexpr float SCALE = 0.08838834764831845f;
constexpr uint64_t EVICT_FIRST = 0x12F0000000000000ull;

constexpr int SA_SLOT = NSL * 16384;
constexpr int SA_Q    = SA_SLOT + 8 * NW * 132 * 4;
constexpr int SA_FULL = SA_Q + 8192;
constexpr int SA_EMPTY = SA_FULL + NSL * 16;
constexpr int SA_GOV  = SA_EMPTY + NSL * 8;
constexpr int SA_MBAR = SA_GOV + NSL * 8;
constexpr int SA_QBAR = SA_MBAR + 128;
constexpr int SA_META = SA_QBAR + 24;
constexpr int SA_LIM  = SA_META + NSL * 4;
constexpr int SA_CNT  = SA_LIM + 16;
constexpr int SA_END  = SA_CNT + 64;
constexpr int PROW    = 2080;
constexpr int SB_STG  = 0;
constexpr int SB_QIMG = 131072;
constexpr int SB_P    = SB_QIMG + 32 * PROW;
constexpr int SB_AL   = SB_P + 8192;
constexpr int SB_X    = SB_AL + 256;
static_assert(SB_P % 1024 == 0, "swizzle atom");
constexpr int SB_QB   = SB_X + 4352;
constexpr int NT      = 40;
constexpr int SC_FR   = NT * 4096;
constexpr int SC_FP   = SC_FR + 16384;
constexpr int SC_RED  = SB_QB + 1024;
constexpr int SB_BAR  = SC_RED + 4480;
constexpr int SB_CNT  = SB_BAR + (12 + NT) * 8;
static_assert(SC_FP + 8448 <= SB_P && 2 * (32 - NSA) <= NT && 2 * (32 - NSB) <= NT && NSA <= 16 && NSB <= 16, "projection slots");
constexpr int SB_END  = SB_CNT + 64;
constexpr int SMEM_BYTES = (SA_END > SB_END ? SA_END : SB_END);
static_assert(SMEM_BYTES <= 232448, "shared memory");

struct Scratch {
    uint4    bpart[32 * 32 * (PROW / 16)];
    uint4    apart[64 * CPG * 32];
    uint4    qimg[2 * 4096];
    uint4    qpub[64 * 32];
    uint4    frag[2][64 * 32];
    uint2    snd[32 * 32];
    uint2    aml[64 * CPG * 4];
    unsigned ctr[1088];
    uint2    fire[544];
    unsigned qflag[1088], bflag[1088];
};
__device__ __align__(1024) Scratch g_scr;

#define TRARG
#define TRPASS
#define TR(k)
#define TROUT()

__device__ __forceinline__ uint32_t s2u(const void* p) { return (uint32_t)__cvta_generic_to_shared(p); }
__device__ __forceinline__ bool elect() {
    uint32_t ok;
    asm volatile("{\n.reg .pred p;\nelect.sync _|p, 0xffffffff;\nselp.u32 %0,1,0,p;\n}" : "=r"(ok));
    return ok;
}
__device__ __forceinline__ void mbar_init(uint32_t b, int c) {
    asm volatile("mbarrier.init.shared::cta.b64 [%0], %1;" ::"r"(b), "r"(c) : "memory");
}
__device__ __forceinline__ void mbar_init_fence() { asm volatile("fence.mbarrier_init.release.cluster;" ::: "memory"); }
__device__ __forceinline__ void mbar_expect(uint32_t b, uint32_t bytes) {
    asm volatile("mbarrier.arrive.expect_tx.shared::cta.b64 _, [%0], %1;" ::"r"(b), "r"(bytes) : "memory");
}
__device__ __forceinline__ void mbar_arrive(uint32_t b) {
    asm volatile("mbarrier.arrive.shared::cta.b64 _, [%0];" ::"r"(b) : "memory");
}
__device__ __forceinline__ bool mbar_test(uint32_t b, uint32_t ph) {
    uint32_t ok;
    asm volatile("{\n.reg .pred p;\nmbarrier.test_wait.parity.shared::cta.b64 p, [%1], %2;\nselp.u32 %0,1,0,p;\n}"
                 : "=r"(ok) : "r"(b), "r"(ph) : "memory");
    return ok;
}
__device__ __forceinline__ void mbar_wait(uint32_t b, uint32_t ph) {
    asm volatile("{\n.reg .pred p;\n.reg .u32 n;\nmov.u32 n, 0;\n"
                 "W: mbarrier.try_wait.parity.shared::cta.b64 p, [%0], %1;\n@p bra.uni D;\n"
                 "add.u32 n, n, 1;\nsetp.lt.u32 p, n, %2;\n@p bra.uni W;\ntrap;\nD:\n}"
                 ::"r"(b), "r"(ph), "n"(SPIN_MAX) : "memory");
}
__device__ __forceinline__ void tma2d(uint32_t dst, const CUtensorMap* map, int c0, int c1, uint32_t bar) {
    asm volatile("cp.async.bulk.tensor.2d.shared::cluster.global.mbarrier::complete_tx::bytes [%0], [%1, {%3, %4}], [%2];"
                 ::"r"(dst), "l"(map), "r"(bar), "r"(c0), "r"(c1) : "memory");
}
__device__ __forceinline__ void tma2d_ef(uint32_t dst, const CUtensorMap* map, int c0, int c1, uint32_t bar) {
    asm volatile("cp.async.bulk.tensor.2d.shared::cluster.global.mbarrier::complete_tx::bytes.L2::cache_hint [%0], [%1, {%3, %4}], [%2], %5;"
                 ::"r"(dst), "l"(map), "r"(bar), "r"(c0), "r"(c1), "l"(EVICT_FIRST) : "memory");
}
__device__ __forceinline__ void tma4d_ef(uint32_t dst, const CUtensorMap* map, int c3, uint32_t bar) {
    asm volatile("cp.async.bulk.tensor.4d.shared::cluster.global.mbarrier::complete_tx::bytes.L2::cache_hint [%0], [%1, {0, 0, 0, %3}], [%2], %4;"
                 ::"r"(dst), "l"(map), "r"(bar), "r"(c3), "l"(EVICT_FIRST) : "memory");
}
__device__ __forceinline__ void bulk_g2s(uint32_t dst, const void* src, uint32_t bytes, uint32_t bar) {
    asm volatile("cp.async.bulk.shared::cluster.global.mbarrier::complete_tx::bytes [%0], [%1], %2, [%3];"
                 ::"r"(dst), "l"(src), "r"(bytes), "r"(bar) : "memory");
}
__device__ __forceinline__ void bulk_s2g(void* dst, uint32_t src, uint32_t bytes) {
    asm volatile("cp.async.bulk.global.shared::cta.bulk_group [%0], [%1], %2;" ::"l"(dst), "r"(src), "r"(bytes) : "memory");
}
__device__ __forceinline__ void fence_async_all() { asm volatile("fence.proxy.async;" ::: "memory"); }
__device__ __forceinline__ void bar_sync(int id, int n) { asm volatile("bar.sync %0, %1;" ::"r"(id), "r"(n) : "memory"); }
__device__ __forceinline__ void bar_arrive(int id, int n) { asm volatile("bar.arrive %0, %1;" ::"r"(id), "r"(n) : "memory"); }
__device__ __forceinline__ unsigned ld_relaxed1(const void* p) {
    unsigned v;
    asm volatile("ld.relaxed.gpu.global.u32 %0, [%1];" : "=r"(v) : "l"(p) : "memory");
    return v;
}
__device__ __forceinline__ unsigned atom_inc(unsigned* p) {
    unsigned v;
    asm volatile("atom.relaxed.gpu.global.add.u32 %0, [%1], 1;" : "=r"(v) : "l"(p) : "memory");
    return v;
}
__device__ __forceinline__ uint4 ld_b128(const void* p) {
    uint4 v;
    asm volatile("{\n.reg .b128 t;\nld.relaxed.gpu.global.b128 t, [%4];\nmov.b128 {%0,%1,%2,%3}, t;\n}"
                 : "=r"(v.x), "=r"(v.y), "=r"(v.z), "=r"(v.w) : "l"(p) : "memory");
    return v;
}
__device__ __forceinline__ void st_b128(void* p, uint4 v) {
    asm volatile("{\n.reg .b128 t;\nmov.b128 t, {%1,%2,%3,%4};\nst.relaxed.gpu.global.b128 [%0], t;\n}"
                 ::"l"(p), "r"(v.x), "r"(v.y), "r"(v.z), "r"(v.w) : "memory");
}
__device__ __forceinline__ uint2 ld_b64(const void* p) {
    uint2 v;
    asm volatile("{\n.reg .b64 a;\nld.relaxed.gpu.global.b64 a, [%2];\nmov.b64 {%0,%1}, a;\n}" : "=r"(v.x), "=r"(v.y) : "l"(p) : "memory");
    return v;
}
__device__ __forceinline__ void st_b64(void* p, uint32_t a, uint32_t b) {
    asm volatile("{\n.reg .b64 t;\nmov.b64 t, {%1,%2};\nst.relaxed.gpu.global.b64 [%0], t;\n}" ::"l"(p), "r"(a), "r"(b) : "memory");
}
__device__ __forceinline__ unsigned ld_acquire(const unsigned* p) {
    unsigned v;
    asm volatile("ld.acquire.gpu.global.u32 %0, [%1];" : "=r"(v) : "l"(p) : "memory");
    return v;
}
__device__ __forceinline__ void st_release(unsigned* p, unsigned v) {
    asm volatile("st.release.gpu.global.u32 [%0], %1;" ::"l"(p), "r"(v) : "memory");
}
__device__ __forceinline__ void ldsm4(uint32_t (&r)[4], uint32_t a) {
    asm volatile("ldmatrix.sync.aligned.m8n8.x4.shared.b16 {%0,%1,%2,%3}, [%4];"
                 : "=r"(r[0]), "=r"(r[1]), "=r"(r[2]), "=r"(r[3]) : "r"(a) : "memory");
}
__device__ __forceinline__ void ldsm4t(uint32_t (&r)[4], uint32_t a) {
    asm volatile("ldmatrix.sync.aligned.m8n8.x4.trans.shared.b16 {%0,%1,%2,%3}, [%4];"
                 : "=r"(r[0]), "=r"(r[1]), "=r"(r[2]), "=r"(r[3]) : "r"(a) : "memory");
}
__device__ __forceinline__ uint4 lds128(uint32_t a) {
    uint4 v;
    asm volatile("ld.shared.v4.u32 {%0, %1, %2, %3}, [%4];" : "=r"(v.x), "=r"(v.y), "=r"(v.z), "=r"(v.w) : "r"(a) : "memory");
    return v;
}
__device__ __forceinline__ float2 lds64f(uint32_t a) {
    float2 v;
    asm volatile("ld.shared.v2.f32 {%0, %1}, [%2];" : "=f"(v.x), "=f"(v.y) : "r"(a) : "memory");
    return v;
}
__device__ __forceinline__ uint32_t lds32(uint32_t a) {
    uint32_t v;
    asm volatile("ld.shared.u32 %0, [%1];" : "=r"(v) : "r"(a) : "memory");
    return v;
}
__device__ __forceinline__ void sts32(uint32_t a, uint32_t v) { asm volatile("st.shared.u32 [%0], %1;" ::"r"(a), "r"(v) : "memory"); }
__device__ __forceinline__ void mma16816(float (&d)[4], const uint32_t (&a)[4], uint32_t b0, uint32_t b1) {
    asm volatile("mma.sync.aligned.m16n8k16.row.col.f32.bf16.bf16.f32 {%0,%1,%2,%3}, {%4,%5,%6,%7}, {%8,%9}, {%0,%1,%2,%3};"
                 : "+f"(d[0]), "+f"(d[1]), "+f"(d[2]), "+f"(d[3])
                 : "r"(a[0]), "r"(a[1]), "r"(a[2]), "r"(a[3]), "r"(b0), "r"(b1));
}
__device__ __forceinline__ uint32_t prmt0(uint32_t a, uint32_t sel) {
    uint32_t d;
    asm volatile("prmt.b32 %0, %1, 0, %2;" : "=r"(d) : "r"(a), "r"(sel));
    return d;
}
__device__ __forceinline__ unsigned gt() {
    unsigned t;
    asm volatile("mov.u32 %0, %globaltimer_lo;" : "=r"(t));
    return t;
}
__device__ __forceinline__ unsigned clk32() {
    unsigned c;
    asm volatile("mov.u32 %0, %clock;" : "=r"(c));
    return c;
}
__device__ __forceinline__ float ex2(float x) {
    float y;
    asm("ex2.approx.ftz.f32 %0, %1;" : "=f"(y) : "f"(x));
    return y;
}
__device__ __forceinline__ float bf16r(float x) { return __bfloat162float(__float2bfloat16_rn(x)); }
__device__ __forceinline__ uint32_t packbf(float lo, float hi) {
    uint32_t r;
    asm("cvt.rn.bf16x2.f32 %0, %1, %2;" : "=r"(r) : "f"(hi), "f"(lo));
    return r;
}
__device__ __forceinline__ float bflo(uint32_t v) { return __uint_as_float(v << 16); }
__device__ __forceinline__ float bfhi(uint32_t v) { return __uint_as_float(v & 0xffff0000u); }
__device__ __forceinline__ uint32_t tagf(float v, uint32_t t8) { return (__float_as_uint(v) & 0xffffff00u) | t8; }
__device__ __forceinline__ float shx(float v, int m) { return __shfl_xor_sync(0xffffffffu, v, m); }

__device__ __forceinline__ float warp_max(float v) {
    int i = __float_as_int(v);
    i = __reduce_max_sync(0xffffffffu, i ^ ((i >> 31) & 0x7fffffff));
    return __int_as_float(i ^ ((i >> 31) & 0x7fffffff));
}

__device__ __forceinline__ uint64_t gdesc(uint32_t addr, uint32_t lbo, uint32_t sbo) {
    return (uint64_t)((addr & 0x3ffff) >> 4) | ((uint64_t)(lbo >> 4) << 16) | ((uint64_t)(sbo >> 4) << 32) | (1ull << 62);
}
__device__ __forceinline__ void wg_fence() { asm volatile("wgmma.fence.sync.aligned;" ::: "memory"); }
__device__ __forceinline__ void wg_commit() { asm volatile("wgmma.commit_group.sync.aligned;" ::: "memory"); }
__device__ __forceinline__ void wg_wait0() { asm volatile("wgmma.wait_group.sync.aligned 0;" ::: "memory"); }
template <int N> __device__ __forceinline__ void reg_fence(float (&r)[N]) {
#pragma unroll
    for (int i = 0; i < N; i++) asm volatile("" : "+f"(r[i])::"memory");
}
#define F8(a, o) "+f"(a[o]), "+f"(a[o + 1]), "+f"(a[o + 2]), "+f"(a[o + 3]), "+f"(a[o + 4]), "+f"(a[o + 5]), "+f"(a[o + 6]), "+f"(a[o + 7])
#define F32(a, o) F8(a, o), F8(a, o + 8), F8(a, o + 16), F8(a, o + 24)
__device__ __forceinline__ void wgmma_n64_ss(float (&d)[32], uint64_t da, uint64_t db, int scale_d) {
    asm volatile(
        "{\n.reg .pred p;\nsetp.ne.b32 p, %34, 0;\n"
        "wgmma.mma_async.sync.aligned.m64n64k16.f32.bf16.bf16 "
        "{%0,%1,%2,%3,%4,%5,%6,%7,%8,%9,%10,%11,%12,%13,%14,%15,%16,%17,%18,%19,%20,%21,%22,%23,%24,%25,%26,%27,%28,%29,%30,%31},"
        " %32, %33, p, 1, 1, 0, 0;\n}"
        : F32(d, 0) : "l"(da), "l"(db), "r"(scale_d));
}
__device__ __forceinline__ void wgmma_n32_ts(float (&d)[16], uint64_t da, uint64_t db) {
    asm volatile(
        "{\n.reg .pred p;\nsetp.ne.b32 p, 1, 0;\n"
        "wgmma.mma_async.sync.aligned.m64n32k16.f32.bf16.bf16 "
        "{%0,%1,%2,%3,%4,%5,%6,%7,%8,%9,%10,%11,%12,%13,%14,%15}, %16, %17, p, 1, 1, 1, 0;\n}"
        : F8(d, 0), F8(d, 8) : "l"(da), "l"(db));
}

struct Params {
    Scratch* scr;
    const uint32_t *ax, *bx;
    const char* wq;
    __nv_bfloat16* out;
};
struct Maps { CUtensorMap kv[2], qa, qb, wo[2], c, uk, uv; };

__device__ __forceinline__ void wait_flags(const unsigned* flags, unsigned tag, int lane) {
    for (int i = 0; !__all_sync(0xffffffffu, ld_acquire(flags + lane * FS) == tag); i++) {
        if (i > SPIN_MAX) __trap();
        __nanosleep(BPOLL);
    }
}
__device__ __forceinline__ void load_slice(uint32_t dst, const CUtensorMap* map, int r, uint32_t bar) {
    mbar_expect(bar, 131072);
#pragma unroll
    for (int x = 0; x < 4; x++) {
        if (EFW & 1) tma2d_ef(dst + x * 32768, map, r * 128 + (x & 1) * 64, (x >> 1) * 256, bar);
        else tma2d(dst + x * 32768, map, r * 128 + (x & 1) * 64, (x >> 1) * 256, bar);
    }
}
__device__ __forceinline__ void gemv_slice(uint32_t sb, int warp, int lane) {
    const int g = lane >> 2, tq = lane & 3;
    float d[4][4];
#pragma unroll
    for (int i = 0; i < 4; i++) d[i][0] = d[i][1] = d[i][2] = d[i][3] = 0.f;
    const uint32_t wb = sb + SB_STG + (warp >> 2) * 32768 + ((lane & 7) + 8 * (lane >> 4)) * 128 +
                        (((2 * (warp & 3) + ((lane >> 3) & 1)) ^ (lane & 7)) << 4);
    const uint32_t xb = sb + SB_X + ((g & 3) * 264 + tq) * 4;
#pragma unroll 1
    for (int k8 = 0; k8 < 4; k8++) {
        uint32_t a[8][4], b[8][2];
#pragma unroll
        for (int ks = 0; ks < 8; ks++) {
            ldsm4t(a[ks], wb + (k8 >> 1) * 65536 + (k8 & 1) * 16384 + ks * 2048);
            b[ks][0] = lds32(xb + k8 * 256 + ks * 32);
            b[ks][1] = lds32(xb + k8 * 256 + ks * 32 + 16);
        }
#pragma unroll
        for (int ks = 0; ks < 8; ks++) mma16816(d[ks & 3], a[ks], b[ks][0], b[ks][1]);
    }
    const float y0 = ((d[0][0] + d[1][0]) + (d[2][0] + d[3][0])) + ((d[0][1] + d[1][1]) + (d[2][1] + d[3][1]));
    const float y1 = ((d[0][2] + d[1][2]) + (d[2][2] + d[3][2])) + ((d[0][3] + d[1][3]) + (d[2][3] + d[3][3]));
    if (tq < 2) {
        sts32(sb + SB_QB + (tq * 128 + warp * 16 + g) * 4, __float_as_uint(y0));
        sts32(sb + SB_QB + (tq * 128 + warp * 16 + 8 + g) * 4, __float_as_uint(y1));
    }
}
__device__ __forceinline__ uint32_t wo_lane(uint32_t sb, int lane) {
    return sb + ((lane & 7) + 8 * (lane >> 4)) * 64 + ((((lane >> 3) & 1) ^ ((lane >> 1) & 3)) << 4);
}

template <int NP, int NTHR> __device__ __forceinline__ float2 sum_parts(uint32_t q, float x, float y) {
    asm volatile("bar.sync 5, %0;" ::"n"(NTHR) : "memory");
    float2 p[NP];
#pragma unroll
    for (int i = 0; i < NP; i++) p[i] = lds64f(q + i * 320);
    p[0].x += x; p[0].y += y;
#pragma unroll
    for (int d = 1; d < NP; d *= 2)
#pragma unroll
        for (int i = 0; i + d < NP; i += 2 * d) { p[i].x += p[i + d].x; p[i].y += p[i + d].y; }
    return p[0];
}

__device__ __forceinline__ void latent_branch(const Params& P, const Maps& M, uint8_t* sm TRARG) {
    const uint32_t sb = s2u(sm);
    const int tid = threadIdx.x, lane = tid & 31, warp = tid >> 5, g = lane >> 2, tq = lane & 3, r = blockIdx.x >> 2;
    const uint32_t bar_w = sb + SB_BAR + 16, bar_x = sb + SB_BAR + 24;
    const unsigned tag = lds32(sb + SB_CNT) + 1;
    Scratch* const S = P.scr;
    const float* yb = reinterpret_cast<const float*>(sm + SB_QB);
    {
        float* xs = reinterpret_cast<float*>(sm + SB_X);
        const int crow0 = (r >> 4) * 8192 + (r & 15) * 64;
        {
            uint32_t* xh = reinterpret_cast<uint32_t*>(sm + SB_X) + tid;
            xh[0] = __ldg(P.bx + tid); xh[264] = 0; xh[528] = __ldg(P.bx + 256 + tid); xh[792] = 0;
            bar_sync(0, 256);
            mbar_wait(bar_w, 0);
            TR(0);
            gemv_slice(sb, warp, lane);
            bar_sync(0, 256);
            if (tid == 0) load_slice(sb + SB_STG, &M.uk, r, bar_w);
            uint32_t qb[8][2];
#pragma unroll
            for (int ks = 0; ks < 8; ks++) {
                const float2 a = *reinterpret_cast<const float2*>(yb + (g & 1) * 128 + ks * 16 + 2 * tq);
                const float2 b = *reinterpret_cast<const float2*>(yb + (g & 1) * 128 + ks * 16 + 8 + 2 * tq);
                qb[ks][0] = packbf(a.x, a.y);
                qb[ks][1] = packbf(b.x, b.y);
            }
            mbar_wait(bar_w, 1);
            const uint32_t wb = sb + SB_STG + (warp >> 2) * 65536 + ((warp & 3) * 64 + (lane & 15)) * 128;
#pragma unroll 1
            for (int mt = 0; mt < 4; mt++) {
                float d[4] = {0.f, 0.f, 0.f, 0.f};
#pragma unroll
                for (int ks = 0; ks < 8; ks++) {
                    uint32_t a[4];
                    ldsm4(a, wb + (ks >> 2) * 32768 + mt * 2048 + (((2 * (ks & 3) + (lane >> 4)) ^ (lane & 7)) << 4));
                    mma16816(d, a, qb[ks][0], qb[ks][1]);
                }
                if (tq == 0) {
                    const int c = warp * 64 + mt * 16 + g;
                    xs[c] = d[0]; xs[512 + c] = d[1]; xs[c + 8] = d[2]; xs[512 + c + 8] = d[3];
                }
            }
            bar_sync(0, 256);
            if (tid == 32) {
#pragma unroll
                for (int t = 0; t < 2; t++) {
                    mbar_expect(sb + SB_BAR + t * 8, 65536);
                    tma4d_ef(sb + SB_STG + t * 65536, &M.c, (crow0 >> 3) + t * 128, sb + SB_BAR + t * 8);
                }
            }
            const int b = tid >> 7, lo = (tid >> 6) & 1, ch = tid & 63;
            float v[8];
#pragma unroll
            for (int i = 0; i < 8; i++) {
                const float x = xs[b * 512 + ch * 8 + i];
                v[i] = lo ? x - bf16r(x) : x;
            }
            const int row = 16 * (r >> 3) + (r & 7) + 8 * lo;
            S->qimg[b * 4096 + (ch >> 3) * 512 + row * 8 + ((ch & 7) ^ (r & 7))] =
                make_uint4(packbf(v[0], v[1]), packbf(v[2], v[3]), packbf(v[4], v[5]), packbf(v[6], v[7]));
            bar_sync(0, 256);
            if (warp == 0) {
                if (lane == 0) { __threadfence(); st_release(S->qflag + r * FS, tag); }
                wait_flags(S->qflag, tag, lane);
                if (lane == 0) {
                    fence_async_all();
                    mbar_expect(bar_x, 65536);
                    bulk_g2s(sb + SB_QIMG, S->qimg + (r >> 4) * 4096, 65536, bar_x);
                }
            }
            mbar_wait(bar_x, 0);
        }
        TR(1);
        {
            const int wg = warp >> 2;
            float acc[4][16];
#pragma unroll
            for (int i = 0; i < 64; i++) acc[i >> 4][i & 15] = 0.f;
            const int head = (warp & 3) * 8 + g;
            const uint32_t pa = sb + SB_P + wg * 4096;
            float* al = reinterpret_cast<float*>(sm + SB_AL) + wg * 32;
            float m = -FLT_MAX, l = 0.f;
#pragma unroll 1
            for (int t = 0; t < 8; t++) {
                const uint32_t stg = sb + SB_STG + (t & 1) * 65536;
                mbar_wait(sb + SB_BAR + (t & 1) * 8, (t >> 1) & 1);
                float s[32];
                uint32_t qa = sb + SB_QIMG;
                asm volatile("" : "+r"(qa));
                wg_fence();
#pragma unroll
                for (int k = 0; k < 32; k++) {
                    const uint32_t off = (k >> 2) * 8192 + (k & 3) * 32;
                    wgmma_n64_ss(s, gdesc(qa + off, 16, 1024), gdesc(stg + (k >> 2) * 1024 + (k & 3) * 32, 16, 8192), k > 0);
                }
                wg_commit();
                wg_wait0();
                reg_fence(s);
                float p[16], mx = m;
#pragma unroll
                for (int i = 0; i < 8; i++) {
                    p[2 * i] = bf16r(bf16r(s[4 * i] + s[4 * i + 2]) * SCALE);
                    p[2 * i + 1] = bf16r(bf16r(s[4 * i + 1] + s[4 * i + 3]) * SCALE);
                    mx = fmaxf(mx, fmaxf(p[2 * i], p[2 * i + 1]));
                }
                mx = fmaxf(mx, shx(mx, 1));
                mx = fmaxf(mx, shx(mx, 2));
                const float alpha = ex2((m - mx) * LOG2E);
                m = mx;
                float sum = 0.f;
#pragma unroll
                for (int i = 0; i < 8; i++) {
                    const float a = ex2((p[2 * i] - mx) * LOG2E), b = ex2((p[2 * i + 1] - mx) * LOG2E);
                    sum += a + b;
                    sts32(pa + head * 128 + ((i ^ g) << 4) + tq * 4, packbf(a, b));
                }
                l = fmaf(l, alpha, sum);
                if (tq == 0) al[head] = alpha;
                asm volatile("fence.proxy.async.shared::cta;" ::: "memory");
                bar_sync(1 + wg, 128);
#pragma unroll
                for (int j = 0; j < 4; j++) {
                    const float2 a = *reinterpret_cast<const float2*>(al + 8 * j + 2 * tq);
#pragma unroll
                    for (int i = 0; i < 4; i++) { acc[i][4 * j] *= a.x; acc[i][4 * j + 1] *= a.y; acc[i][4 * j + 2] *= a.x; acc[i][4 * j + 3] *= a.y; }
                }
#pragma unroll
                for (int i = 0; i < 4; i++) reg_fence(acc[i]);
                wg_fence();
#pragma unroll
                for (int kk = 0; kk < 4; kk++)
#pragma unroll
                    for (int i = 0; i < 4; i++)
                        wgmma_n32_ts(acc[i], gdesc(stg + (wg * 4 + i) * 1024 + kk * 16384, 1024, 8192), gdesc(pa + kk * 32, 16, 1024));
                wg_commit();
                wg_wait0();
#pragma unroll
                for (int i = 0; i < 4; i++) reg_fence(acc[i]);
                bar_sync(0, 256);
                if (tid == 0) {
                    if (t + 2 < 8) {
                        const uint32_t bar = sb + SB_BAR + (t & 1) * 8;
                        mbar_expect(bar, 65536);
                        tma4d_ef(stg, &M.c, (crow0 >> 3) + (t + 2) * 128, bar);
                    }
                    if (t == 7) load_slice(sb + SB_STG, &M.uv, r, bar_w);
                }
            }
            TR(2);
            float* dst = reinterpret_cast<float*>(sm + SB_QIMG + 2 * tq * PROW) + wg * 256 + (warp & 3) * 16 + g;
#pragma unroll
            for (int i = 0; i < 64; i++)
                dst[(((i >> 2) & 3) * 8 + (i & 1)) * (PROW / 4) + (i >> 4) * 64 + (i & 2) * 4] = acc[i >> 4][i & 15];
            l += shx(l, 1); l += shx(l, 2);
            if (wg == 0 && tq < 2) *reinterpret_cast<float4*>(sm + SB_QIMG + head * PROW + 2048 + tq * 16) = make_float4(m, l, 0.f, 0.f);
            asm volatile("fence.proxy.async.shared::cta;" ::: "memory");
            bar_sync(0, 256);
            if (warp == 0) {
                bulk_s2g(S->bpart + (lane * 32 + r) * (PROW / 16), sb + SB_QIMG + lane * PROW, PROW);
                asm volatile("cp.async.bulk.commit_group;" ::: "memory");
                asm volatile("cp.async.bulk.wait_group 0;" ::: "memory");
                fence_async_all();
                __threadfence();
                __syncwarp();
                if (lane == 0) st_release(S->bflag + r * FS, tag);
                wait_flags(S->bflag, tag, lane);
                if (lane == 0) {
                    fence_async_all();
                    mbar_expect(bar_x, 32 * PROW);
                    bulk_g2s(sb + SB_QIMG, S->bpart + r * 32 * (PROW / 16), 32 * PROW, bar_x);
                }
            }
        }
        {
            const int b = tid >> 7, c4 = tid & 127;
            mbar_wait(bar_x, 1);
            TR(3);
            const float2 ml = *reinterpret_cast<const float2*>(sm + SB_QIMG + (b * 16 + (lane & 15)) * PROW + 2048);
            float MM = ml.x;
            MM = fmaxf(MM, shx(MM, 1)); MM = fmaxf(MM, shx(MM, 2)); MM = fmaxf(MM, shx(MM, 4)); MM = fmaxf(MM, shx(MM, 8));
            const float e = ex2((ml.x - MM) * LOG2E);
            float L = e * ml.y;
            L += shx(L, 1); L += shx(L, 2); L += shx(L, 4); L += shx(L, 8);
            const float wgt = e / L;
            float4 o = make_float4(0.f, 0.f, 0.f, 0.f);
#pragma unroll 4
            for (int i = 0; i < 16; i++) {
                const float w = __shfl_sync(0xffffffffu, wgt, i);
                const float4 v = *reinterpret_cast<const float4*>(sm + SB_QIMG + (b * 16 + i) * PROW + c4 * 16);
                o.x = fmaf(w, v.x, o.x); o.y = fmaf(w, v.y, o.y); o.z = fmaf(w, v.z, o.z); o.w = fmaf(w, v.w, o.w);
            }
            uint32_t* xh = reinterpret_cast<uint32_t*>(xs);
            const uint32_t h0 = packbf(o.x, o.y), h1 = packbf(o.z, o.w);
            *reinterpret_cast<uint2*>(xh + (2 * b) * 264 + c4 * 2) = make_uint2(h0, h1);
            *reinterpret_cast<uint2*>(xh + (2 * b + 1) * 264 + c4 * 2) =
                make_uint2(packbf(o.x - bflo(h0), o.y - bfhi(h0)), packbf(o.z - bflo(h1), o.w - bfhi(h1)));
            bar_sync(0, 256);
            mbar_wait(bar_w, 0);
            gemv_slice(sb, warp, lane);
            bar_sync(0, 256);
            if (tid < 64) {
                const float* y = yb + warp * 128 + 16 * g + 2 * tq;
                st_b128(S->frag[0] + (warp * 32 + r) * 32 + lane, make_uint4(packbf(y[0], y[1]), tag, packbf(y[8], y[9]), tag));
            }
        }
        TR(4);
    }
}

__global__ void __launch_bounds__(480, 1)
fused_decode_kernel(const Params P, const __grid_constant__ Maps M) {
    extern __shared__ __align__(1024) uint8_t sm[];
    const uint32_t sb = s2u(sm);
    const int tid = threadIdx.x, lane = tid & 31, bx = blockIdx.x;
    asm volatile("{\n.reg .pred p;\nsetp.lt.u32 p, %1, 256;\n@p prefetch.global.L2 [%0];\n}"
                 ::"l"(P.wq + (PFM ? (unsigned)(((bx & 1) * 256 + tid) * 8192 + (bx >> 1) * 128) : (unsigned)(bx * 32768 + tid * 128))), "r"(tid) : "memory");
    const int warp = __shfl_sync(0xffffffffu, tid >> 5, 0);
    const int g = lane >> 2, tq = lane & 3;
    Scratch* const S = P.scr;

    if (!(bx & 1)) {
        const int grp = (bx >> 1) & 1, crk = bx >> 2;
        const int rowbase = grp * (UPG * 64);
        auto issue = [&](int slot, unsigned tk, int v) {
            const int row = rowbase + (int)((tk & ~255u) | ((tk + grp * ROT) & 255u)) * 64;
            const uint32_t full = sb + SA_FULL + slot * 16 + v * 8;
            mbar_expect(full, 8192);
            tma2d_ef(sb + slot * 16384 + v * 8192, &M.kv[v], 0, row, full);
        };
        if (warp >= 8) {
            const int w = warp - 8;
            if (w >= NW) {
                if (w == NW && !(bx & XPM)) asm volatile("prefetch.global.L2 [%0];" ::"l"(((lane & 16) ? P.bx : P.ax) + (lane & 15) * 32) : "memory");
                return;
            }
            const bool one = elect();
            if (one) {
                mbar_init(sb + SA_FULL + w * 16, 1);
                mbar_init_fence();
                TR(3);
                sts32(sb + SA_META + w * 4, 0);
                if (w < SKEW) issue(w, w * CPG + crk, 0);
#pragma unroll
                for (int i = 0; i < SPW; i++) {
                    if (i) mbar_init(sb + SA_FULL + (w + i * NW) * 16, 1);
                    mbar_init(sb + SA_FULL + (w + i * NW) * 16 + 8, 1);
                    mbar_init(sb + SA_GOV + (w + i * NW) * 8, 1);
                    mbar_init(sb + SA_EMPTY + (w + i * NW) * 8, 2);
                    mbar_arrive(sb + SA_EMPTY + (w + i * NW) * 8);
                }
                if (w < SKEW) mbar_arrive(sb + SA_EMPTY + w * 8);
                sts32(sb + SA_LIM + w * 4, LIM);
                mbar_init_fence();
            }
            __syncwarp();
            bar_arrive(2, (NW + 1) * 32);
            bar_arrive(1, (2 * NW + 2) * 32);
            unsigned c = 0;
            int slot = w;
            uint32_t eph = 0;
#pragma unroll 1
            for (int n = 0;; n++) {
                unsigned tk = (n * NW + w) * CPG + crk, own = 0;
                if (n >= SPW) {
                    own = __shfl_sync(0xffffffffu, c, grp);
                    tk = own % UPG + NSL * CPG;
                    const int lag = (int)(__reduce_add_sync(0xffffffffu, c) - NG * own);
                    if (one) sts32(sb + SA_LIM + w * 4, lag > BAL * NG ? LIM + 1 : lag < -BAL * NG ? LIM - 1 : LIM);
                }
                mbar_wait(sb + SA_EMPTY + slot * 8, eph);
                if (tk >= UPG) {
                    if (one) {
                        sts32(sb + SA_LIM + w * 4, 0);
                        sts32(sb + SA_META + slot * 4, 32);
                        mbar_arrive(sb + SA_FULL + slot * 16);
                        asm volatile("red.relaxed.gpu.global.add.u32 [%0], %1;" ::"l"(S->ctr + grp), "n"(SPW - 1) : "memory");
                    }
                    return;
                }
                if (one && (n || w >= SKEW)) {
                    sts32(sb + SA_META + slot * 4, tk >> 8);
                    issue(slot, tk, 0);
                    if (tk == 1200) TR(6);
                    if (tk == UPG - FIRE_T) { st_b64(S->fire + grp, gt(), own / UPG + 1); TR(4); }
                }
                if (n >= SPW - 1) {
                    if (lane == grp) c = atom_inc(S->ctr + lane);
                    else if (lane < NG) c = ld_relaxed1(S->ctr + lane);
                }
                mbar_wait(sb + SA_GOV + slot * 8, eph);
                if (one) issue(slot, tk, 1);
                TR(0);
                slot += NW;
                if (slot >= NSL) { slot -= NSL; eph ^= 1; }
                __syncwarp();
            }
        }
        if (warp == 0) {
            bool busy = lane < 2 * SKEW && !(lane & 1);
            uint32_t par = busy ? 0 : 1;
            int slot = SKEW;
            bool first = true;
            const unsigned c0 = clk32() + RAMP_T0;
            const int own = lane >= 2 * NSL ? -1 : ((lane >> 1) + (lane & 1) * SKEW) % NSL;
            const uint32_t fb = sb + SA_FULL + lane * 8, lw = sb + SA_LIM + ((lane >> 1) % NW) * 4;
            const uint32_t go = sb + ((lane & 1) ? SA_GOV : SA_EMPTY) + (lane >> 1) * 8;
            bar_sync(2, (NW + 1) * 32);
#pragma unroll 1
            for (int it = 0; it < SPIN_MAX; it++) {
                bool ok = true;
                if (busy) ok = mbar_test(fb, par);
                int lim = lds32(lw);
                if (first) lim = min(LIM0, SKEW + max((int)(clk32() - c0), 0) / RAMP_S);
                busy = busy && !ok && lim;
                const int n = __popc(__ballot_sync(0xffffffffu, busy));
                if (!__any_sync(0xffffffffu, lim)) return;
                const bool mine = own == slot && lim;
                if (!__any_sync(0xffffffffu, mine && (busy || n > lim - 2))) {
                    if (mine) { mbar_arrive(go); busy = true; par ^= 1; }
                    if (++slot == NSL) { slot = 0; first = false; }
                    it = 0;
                }
            }
            __trap();
        }
        {
            int w3 = warp;
            asm volatile("" : "+r"(w3));
            if (w3 == 3) return;
        }
        if (warp == 1) {
            const uint4* const qsrc = S->qpub + grp * 1024 + lane;
            uint2* const qdst = reinterpret_cast<uint2*>(sm + SA_Q) + lane;
            const unsigned epoch = ld_relaxed1(S->ctr + grp) / UPG;
            if (lane == 0) {
                mbar_init(sb + SA_QBAR, 32);
                mbar_init(sb + SA_QBAR + 8, 32);
                mbar_init(sb + SA_QBAR + 16, 32);
#pragma unroll
                for (int i = 0; i < 8; i++) { mbar_init(sb + SA_MBAR + i * 16, NW); mbar_init(sb + SA_MBAR + i * 16 + 8, 1); }
                mbar_init_fence();
                sts32(sb + SA_CNT, epoch);
            }
            __syncwarp();
            bar_arrive(1, (2 * NW + 2) * 32);
            __nanosleep(QSLEEP);
            for (int it = 0;; it++) {
                const uint4 u = ld_b128(qsrc);
                if (__all_sync(0xffffffffu, u.y == epoch + 1)) { qdst[0] = make_uint2(u.x, u.z); break; }
                if (it > SPIN_MAX) __trap();
            }
            mbar_arrive(sb + SA_QBAR);
#pragma unroll 1
            for (int h = 0, it = 0; h < 32; it++) {
                uint4 v[8];
                bool ok = true;
#pragma unroll
                for (int k = 0; k < 8; k++) v[k] = ld_b128(qsrc + (h + k) * 32);
#pragma unroll
                for (int k = 0; k < 8; k++) { ok = ok && v[k].y == epoch + 1; qdst[(h + k) * 32] = make_uint2(v[k].x, v[k].z); }
                if (__all_sync(0xffffffffu, ok)) {
                    if (!h) mbar_arrive(sb + SA_QBAR + 8);
                    h += 8;
                } else if (QPOLL) __nanosleep(QPOLL);
                if (it > SPIN_MAX) __trap();
            }
            mbar_arrive(sb + SA_QBAR + 16);
            return;
        }
        bar_sync(1, (2 * NW + 2) * 32);
        if (warp == 2) {
            const uint32_t t8 = (lds32(sb + SA_CNT) + 1) & 0xffu;
            uint4* dst = S->apart + (grp * 32 * CPG + crk) * 32 + lane;
            uint2* dml = S->aml + (grp * 32 * CPG + crk) * 4 + (lane & 3);
            if (PL2 & 1) {
#pragma unroll
                for (int k = 0; k < 4; k++) st_b64(dml + (k * 8 + (lane >> 2)) * (CPG * 4), 0, t8 ^ 0x80u);
                __syncwarp();
            }
#pragma unroll 1
            for (int h = 0; h < 32; h++, dst += CPG * 32, dml += CPG * 4) {
                const float* s0 = reinterpret_cast<const float*>(sm + SA_SLOT) + (h & 7) * (NW * 132);
                mbar_wait(sb + SA_MBAR + (h & 7) * 16, (h >> 3) & 1);
                float2 ml[NW];
                float4 v[NW];
#pragma unroll
                for (int w = 0; w < NW; w++) {
                    ml[w] = *reinterpret_cast<const float2*>(s0 + w * 132 + 128);
                    v[w] = *reinterpret_cast<const float4*>(s0 + w * 132 + lane * 4);
                }
                const float MM = fmaxf(fmaxf(ml[0].x, ml[1].x), fmaxf(ml[2].x, ml[3].x));
                float e[NW];
#pragma unroll
                for (int w = 0; w < NW; w++) e[w] = ex2((ml[w].x - MM) * LOG2E);
                st_b128(dst, make_uint4(tagf(fmaf(e[0], v[0].x, e[1] * v[1].x) + fmaf(e[2], v[2].x, e[3] * v[3].x), t8),
                                        __float_as_uint(fmaf(e[0], v[0].y, e[1] * v[1].y) + fmaf(e[2], v[2].y, e[3] * v[3].y)),
                                        __float_as_uint(fmaf(e[0], v[0].z, e[1] * v[1].z) + fmaf(e[2], v[2].z, e[3] * v[3].z)),
                                        __float_as_uint(fmaf(e[0], v[0].w, e[1] * v[1].w) + fmaf(e[2], v[2].w, e[3] * v[3].w))));
                if (lane < 4) st_b64(dml, __float_as_uint(MM), tagf(fmaf(e[0], ml[0].y, e[1] * ml[1].y) + fmaf(e[2], ml[2].y, e[3] * ml[3].y), t8));
                TR(2);
                if (PLACE && (h == 27 || h == 28)) {
                    st_b128(dst + 3 * CPG * 32, make_uint4(t8 ^ 0x80u, 0, 0, 0));
                    if (!(PL2 & 1) && lane < 4) st_b64(dml + 3 * CPG * 4, 0, t8 ^ 0x80u);
                }
                __syncwarp();
                if (lane == 0) mbar_arrive(sb + SA_MBAR + (h & 7) * 16 + 8);
            }
            TROUT();
            return;
        }
        const int cw = warp - 4;
        uint32_t koff[4], voff[4];
#pragma unroll
        for (int i = 0; i < 4; i++) {
            koff[i] = ((lane & 7) + 8 * ((lane >> 3) & 1)) * 128 + (((2 * i + (lane >> 4)) ^ (lane & 7)) << 4);
            voff[i] = ((lane & 7) + 8 * (lane >> 4)) * 128 + (((2 * i + ((lane >> 3) & 1)) ^ (lane & 7)) << 4);
        }
        uint32_t psel[4][2];
#pragma unroll
        for (int i = 0; i < 4; i++) {
            psel[i][0] = (g >> 1) != i ? 0x4444u : (g & 1) ? 0x1044u : 0x4410u;
            psel[i][1] = (g >> 1) != i ? 0x4444u : (g & 1) ? 0x3244u : 0x4432u;
        }
        uint32_t qf[4][2];
        auto load_q = [&](int pl) {
            const uint32_t q = sb + SA_Q + pl * 256 + ((g & 1) * 32 + tq) * 4;
#pragma unroll
            for (int ks = 0; ks < 4; ks++) { qf[ks][0] = lds32(q + ks * 32); qf[ks][1] = lds32(q + ks * 32 + 16); }
        };
        mbar_wait(sb + SA_QBAR, 0);
        TR(0);
        load_q(0);
        float acc[4][4], m = -FLT_MAX, l = 0.f, ls = 0.f;
#pragma unroll
        for (int i = 0; i < 4; i++) acc[i][0] = acc[i][1] = acc[i][2] = acc[i][3] = 0.f;
        int slot = cw, cur = 0;
        uint32_t ph = 0;
#pragma unroll 1
        for (;;) {
            mbar_wait(sb + SA_FULL + slot * 16, ph);
            const int pl = lds32(sb + SA_META + slot * 4);
            if (pl != cur) {
#pragma unroll 1
                do {
                    float* s0 = reinterpret_cast<float*>(sm + SA_SLOT) + ((cur & 7) * NW + cw) * 132;
                    float* sw = s0 + tq * 16 + (g >> 1) * 4 + (g & 1);
                    sw[0] = (acc[0][0] + acc[1][0]) + (acc[2][0] + acc[3][0]);
                    sw[2] = (acc[0][2] + acc[1][2]) + (acc[2][2] + acc[3][2]);
                    sw[64] = (acc[0][1] + acc[1][1]) + (acc[2][1] + acc[3][1]);
                    sw[66] = (acc[0][3] + acc[1][3]) + (acc[2][3] + acc[3][3]);
                    if (lane == 0) *reinterpret_cast<float2*>(s0 + 128) = make_float2(m, ls);
                    __syncwarp();
                    if (lane == 0) mbar_arrive(sb + SA_MBAR + (cur & 7) * 16);
                    if (++cur == 32) { TROUT(); return; }
#pragma unroll
                    for (int i = 0; i < 4; i++) acc[i][0] = acc[i][1] = acc[i][2] = acc[i][3] = 0.f;
                    m = -FLT_MAX; l = ls = 0.f;
                    mbar_wait(sb + SA_MBAR + (cur & 7) * 16 + 8, ((cur >> 3) & 1) ^ 1);
                    if (cur == 1 || cur == 8) mbar_wait(sb + SA_QBAR + 8 + (cur & 8), 0);
                } while (cur != pl);
                load_q(pl);
            }
            float s4[4][4];
            const uint32_t kb = sb + slot * 16384;
#pragma unroll
            for (int j = 0; j < 4; j++) {
                s4[j][0] = s4[j][1] = s4[j][2] = s4[j][3] = 0.f;
                const bool on = (g >> 1) == j;
#pragma unroll
                for (int ks = 0; ks < 4; ks++) {
                    uint32_t a[4];
                    ldsm4(a, kb + j * 2048 + koff[ks]);
                    mma16816(s4[j], a, on ? qf[ks][0] : 0u, on ? qf[ks][1] : 0u);
                }
            }
            float d[4];
#pragma unroll
            for (int r = 0; r < 4; r++) d[r] = (s4[0][r] + s4[1][r]) + (s4[2][r] + s4[3][r]);
            float sa = (g & 1) ? d[1] : d[0], sc = (g & 1) ? d[3] : d[2];
            sa += shx(sa, 4); sc += shx(sc, 4);
            uint32_t sp = packbf(sa, sc);
            sp = packbf(bflo(sp) * SCALE, bfhi(sp) * SCALE);
            sa = bflo(sp); sc = bfhi(sp);
            const float mx = warp_max(fmaxf(fmaxf(sa, sc), m));
            const float alpha = ex2((m - mx) * LOG2E);
            m = mx;
            const float pa = ex2((sa - mx) * LOG2E), pc = ex2((sc - mx) * LOG2E);
            const uint32_t pk = packbf(pa, pc);
            uint32_t pb[4][4][2];
#pragma unroll
            for (int j = 0; j < 4; j++) {
                const uint32_t pj = __shfl_sync(0xffffffffu, pk, 8 * tq + j);
#pragma unroll
                for (int i = 0; i < 4; i++) { pb[j][i][0] = prmt0(pj, psel[i][0]); pb[j][i][1] = prmt0(pj, psel[i][1]); }
            }
            l = fmaf(l, alpha, pa + pc);
            ls = l + shx(l, 8);
#pragma unroll
            for (int i = 0; i < 4; i++) { acc[i][0] *= alpha; acc[i][1] *= alpha; acc[i][2] *= alpha; acc[i][3] *= alpha; }
            mbar_wait(sb + SA_FULL + slot * 16 + 8, ph);
            TR(1);
            const uint32_t vb = kb + 8192;
#pragma unroll
            for (int i = 0; i < 4; i++)
#pragma unroll
                for (int j = 0; j < 4; j++) {
                    uint32_t a[4];
                    ldsm4t(a, vb + j * 2048 + voff[i]);
                    mma16816(acc[j], a, pb[j][i][0], pb[j][i][1]);
                }
            ls += shx(ls, 16); ls += shx(ls, 1); ls += shx(ls, 2);
            __syncwarp();
            if (lane == 0) mbar_arrive(sb + SA_EMPTY + slot * 8);
            slot += NW;
            if (slot >= NSL) { slot -= NSL; ph ^= 1; }
        }
    }

    const int r = bx >> 2, isC = (bx >> 1) & 1;
    const uint32_t bar_h = sb + SB_BAR + 32;
    if (warp == 8 && !isC) {
        const unsigned c0 = clk32();
        bar_sync(7, 64);
        while ((int)(clk32() - c0) < BSTART + (r & 7) * BSTAG) {}
        if (elect()) load_slice(sb + SB_STG, &M.qb, r, sb + SB_BAR + 16);
        __syncwarp();
    }
    if (warp < 8) {
    {
        const uint32_t bar_q = bar_h + (NT + warp) * 8, box = sb + SB_QIMG + warp * 8192;
        if (elect()) {
            mbar_init(bar_q, 1);
            mbar_init_fence();
            mbar_expect(bar_q, 8192 + 256);
            if (EFW & 2) tma2d_ef(box, &M.qa, (bx >> 1) * 64, warp * 64, bar_q);
            else tma2d(box, &M.qa, (bx >> 1) * 64, warp * 64, bar_q);
        }
        __syncwarp();
        unsigned epoch = 0;
        if (warp < 2) epoch = ld_relaxed1(S->ctr) / UPG;
        uint4* const qdst = S->qpub + ((lane >> 4) * 32 + r) * 32 + isC * 16 + (lane & 15);
        if (PLACE && warp == 0) st_b128(qdst, make_uint4(0, 0, 0, 0));
        if (elect()) {
            for (const unsigned c0 = clk32(); (int)(clk32() - c0) < XD0 + (bx >> 1) * XDS;) {}
            bulk_g2s(sb + SB_P + 4096 + warp * 288, P.ax + warp * 32, 128, bar_q);
            bulk_g2s(sb + SB_P + 4096 + warp * 288 + 144, P.ax + 256 + warp * 32, 128, bar_q);
        }
        if (tid == 32) {
#pragma unroll
            for (int i = 0; i < 4 + NT; i++) mbar_init(sb + SB_BAR + i * 8, 1);
            mbar_init_fence();
            sts32(sb + SB_CNT, epoch);
            sts32(sb + SB_CNT + 4, 0);
        }
        __syncwarp();
        if (warp == 1 && !isC) bar_arrive(7, 64);
        mbar_wait(bar_q, 0);
        TR(0);
        uint32_t b[8];
#pragma unroll
        for (int i = 0; i < 8; i++) b[i] = lds32(sb + SB_P + 4096 + warp * 288 + (g & 1) * 144 + tq * 4 + i * 16);
        float d[4][4];
        uint32_t a[4][4][4];
#pragma unroll
        for (int i = 0; i < 4; i++) {
            d[i][0] = d[i][1] = d[i][2] = d[i][3] = 0.f;
#pragma unroll
            for (int ks = 0; ks < 4; ks++)
                ldsm4t(a[i][ks], box + ks * 2048 + ((lane & 7) + 8 * (lane >> 4)) * 128 + (((2 * i + ((lane >> 3) & 1)) ^ (lane & 7)) << 4));
        }
#pragma unroll
        for (int ks = 0; ks < 4; ks++)
#pragma unroll
            for (int i = 0; i < 4; i++) mma16816(d[i], a[i][ks], b[2 * ks], b[2 * ks + 1]);
        float* qred = reinterpret_cast<float*>(sm + SB_P);
#pragma unroll
        for (int c = 0; c < 4; c++)
            qred[warp * 128 + (c & 1) * 64 + tq * 16 + (c >> 1) * 8 + g] = tq == 0 ? d[0][c] : tq == 1 ? d[1][c] : tq == 2 ? d[2][c] : d[3][c];
        bar_sync(0, 256);
        if (warp == 0) {
            float4 v[8];
#pragma unroll
            for (int w = 0; w < 8; w++) v[w] = *reinterpret_cast<const float4*>(qred + w * 128 + lane * 4);
#pragma unroll
            for (int o = 4; o; o >>= 1)
#pragma unroll
                for (int w = 0; w < o; w++) { v[w].x += v[w + o].x; v[w].y += v[w + o].y; v[w].z += v[w + o].z; v[w].w += v[w + o].w; }
            st_b128(qdst, make_uint4(packbf(v[0].x, v[0].y), epoch + 1, packbf(v[0].z, v[0].w), epoch + 1));
        }
        if ((PL2 & 4) && !isC && tid < 4) st_b128(((tid & 2) ? S->bflag : S->qflag) + r * 8 + (tid & 1) * 4, make_uint4(0, 0, 0, 0));
        if ((PL2 & 2) && !isC && warp < 2) st_b128(S->frag[0] + (warp * 32 + r) * 32 + lane, make_uint4(0, 0, 0, 0));
        if ((PL2 & 2) && isC && !(warp & 3))
            st_b128(S->frag[1] + ((warp >> 2) * 32 + (((r >> JMAP) & 1) ? 0 : 16) + ((r >> (JMAP + 1)) << JMAP) + (r & ((1 << JMAP) - 1))) * 32 + lane, make_uint4(0, 0, 0, 0));
        TR(1);
    }
    if (!isC) latent_branch(P, M, sm TRPASS);
    bar_arrive(6, 288);
    }

    constexpr int ND = 2;
    const int isA = (r >> JMAP) & 1, cb = ((r >> (JMAP + 1)) << JMAP) + (r & ((1 << JMAP) - 1)), nsnd = isA ? NSA : NSB, isCA = isC & isA;
    const int y0 = isC ? nsnd : 0, y1 = isC ? 32 - ND * isA : nsnd;
    const int nreq = isC ? 32 - nsnd : nsnd;
    const int nmw = isC && !isA ? NMW : 0;
    float* const red = reinterpret_cast<float*>(sm + SC_RED);
    const uint32_t wlane = wo_lane(sb, lane);
    auto fetch_frag = [&](int y, int b, unsigned tag, unsigned ns) {
        for (int it = 0;; it++) {
            const uint4 v = ld_b128(S->frag[0] + isA * 2048 + (b * 32 + y) * 32 + lane);
            if (__all_sync(0xffffffffu, v.y == tag)) {
                reinterpret_cast<uint2*>(sm + SC_FR)[(y * 32 + (g >> 1) * 8 + b * 4 + tq) * 2 + (g & 1)] = make_uint2(v.x, v.z);
                return;
            }
            if (it > SPIN_MAX) __trap();
            __nanosleep(ns);
        }
    };
    if (warp < 8) {
        const unsigned tag = lds32(sb + SB_CNT) + 1;
        const uint32_t t8 = tag & 0xffu;
        uint32_t bs[2], wf[4][4];
        float d[2][4];
        const uint32_t wa = (wlane ^ ((warp & 1) * 32)) + (warp & 2) * 2048;
        const int ks0 = (warp & 2) * 2;
        if (isC) __nanosleep(4000);
#pragma unroll 1
        for (int op = isCA ? 0 : 1;; op++) {
            const int step = isCA ? max(op - 1, 0) : 0, h = step ? 31 - ND + step : isA ? cb : 16 + cb;
            if (op != 1) {
                if (!isCA && (!isC || h >= 32 - ND)) break;
                const int rec = ((warp >> 2) * 32 + h) * CPG + (warp & 3) * 8;
                const uint2* mlp = S->aml + (rec + (lane & 7)) * 4;
                const uint4* src = S->apart + rec * 32 + lane;
                asm volatile("" : "+l"(mlp), "+l"(src));
                if (!step) {
                    for (int it = 0; !__all_sync(0xffffffffu, (ld_b64(mlp).y & 0xffu) == t8); it++) {
                        if (it > SPIN_MAX) __trap();
                        __nanosleep(h > 25 ? DPOLL : CPOLL);
                    }
                } else if (step < ND) {
                    mbar_wait(sb + SB_BAR + 8, 0);
                } else {
                    d[0][0] = d[0][1] = d[0][2] = d[0][3] = d[1][0] = d[1][1] = d[1][2] = d[1][3] = 0.f;
#pragma unroll
                    for (int k = 0; k < ND; k++) {
                        mbar_wait(bar_h + k * 16 + (warp & 2) * 4, 0);
#pragma unroll
                        for (int ks = 0; ks < 4; ks++) ldsm4t(wf[ks], wa + k * 8192 + ks * 1024);
                        if (k < ND - 1) {
#pragma unroll
                            for (int ks = 0; ks < 4; ks++) mma16816(d[ks & 1], wf[ks], g == ks0 + ks ? bs[0] : 0u, g == ks0 + ks ? bs[1] : 0u);
                        }
                    }
                    mbar_wait(sb + SB_BAR, 0);
                }
                TR(3);
                uint4 v[8];
                uint2 ml = ld_b64(mlp);
#pragma unroll
                for (int i = 0; i < 8; i++) v[i] = ld_b128(src + i * 32);
                for (int it = 0;; it++) {
                    unsigned x = ml.y ^ t8;
#pragma unroll
                    for (int i = 0; i < 8; i++) x |= v[i].x ^ t8;
                    if (!__any_sync(0xffffffffu, x & 0xffu)) break;
                    if (it > SPIN_MAX) __trap();
                    ml = ld_b64(mlp);
#pragma unroll
                    for (int i = 0; i < 8; i++)
                        if ((v[i].x & 0xffu) != t8) v[i] = ld_b128(src + i * 32);
                }
                TR(2);
                const float mw = warp_max(__uint_as_float(ml.x)), e = ex2((__uint_as_float(ml.x) - mw) * LOG2E);
                float L = e * __uint_as_float(ml.y), oa[4], ob[4];
                L += shx(L, 1);
#pragma unroll
                for (int i = 0; i < 8; i++) {
                    const float w = __shfl_sync(0xffffffffu, e, i);
                    float (&o)[4] = (i & 1) ? ob : oa;
                    o[0] = i < 2 ? w * __uint_as_float(v[i].x) : fmaf(w, __uint_as_float(v[i].x), o[0]);
                    o[1] = i < 2 ? w * __uint_as_float(v[i].y) : fmaf(w, __uint_as_float(v[i].y), o[1]);
                    o[2] = i < 2 ? w * __uint_as_float(v[i].z) : fmaf(w, __uint_as_float(v[i].z), o[2]);
                    o[3] = i < 2 ? w * __uint_as_float(v[i].w) : fmaf(w, __uint_as_float(v[i].w), o[3]);
                }
                float* fp = reinterpret_cast<float*>(sm + SC_FP) + ((step & 1) * 8 + (warp & 4)) * 132;
                *reinterpret_cast<float4*>(fp + (warp & 3) * 132 + lane * 4) = make_float4(oa[0] + ob[0], oa[1] + ob[1], oa[2] + ob[2], oa[3] + ob[3]);
                L += shx(L, 2);
                L += shx(L, 4);
                if (lane == 0) *reinterpret_cast<float2*>(fp + (warp & 3) * 132 + 128) = make_float2(mw, L);
                bar_sync(1 + (warp >> 2), 128);
                float2 q[4];
                float4 u[4];
#pragma unroll
                for (int w = 0; w < 4; w++) {
                    q[w] = *reinterpret_cast<const float2*>(fp + w * 132 + 128);
                    u[w] = *reinterpret_cast<const float4*>(fp + w * 132 + lane * 4);
                }
                const float MM = fmaxf(fmaxf(q[0].x, q[1].x), fmaxf(q[2].x, q[3].x));
                float f[4], inv;
#pragma unroll
                for (int w = 0; w < 4; w++) f[w] = ex2((q[w].x - MM) * LOG2E);
                asm("rcp.approx.ftz.f32 %0, %1;" : "=f"(inv) : "f"(fmaf(f[0], q[0].y, f[1] * q[1].y) + fmaf(f[2], q[2].y, f[3] * q[3].y)));
                const uint32_t b0 = packbf((fmaf(f[0], u[0].x, f[1] * u[1].x) + fmaf(f[2], u[2].x, f[3] * u[3].x)) * inv,
                                           (fmaf(f[0], u[0].y, f[1] * u[1].y) + fmaf(f[2], u[2].y, f[3] * u[3].y)) * inv);
                const uint32_t b1 = packbf((fmaf(f[0], u[0].z, f[1] * u[1].z) + fmaf(f[2], u[2].z, f[3] * u[3].z)) * inv,
                                           (fmaf(f[0], u[0].w, f[1] * u[1].w) + fmaf(f[2], u[2].w, f[3] * u[3].w)) * inv);
                if (step == ND) {
#pragma unroll
                    for (int ks = 0; ks < 4; ks++) mma16816(d[ks & 1], wf[ks], g == ks0 + ks ? b0 : 0u, g == ks0 + ks ? b1 : 0u);
                    const float x0 = (d[0][0] + d[0][1]) + (d[1][0] + d[1][1]), x1 = (d[0][2] + d[0][3]) + (d[1][2] + d[1][3]);
                    const float z = ((tq & 1) ? x1 : x0) + shx((tq & 1) ? x0 : x1, 1);
                    if ((tq & 2) == (warp & 2)) red[(6 + (tq >> 1)) * 80 + (warp >> 2) * 40 + (warp & 1) * 16 + (tq & 1) * 8 + g] = z;
                    bar_arrive(5, 480);
                    TR(5);
                    TROUT();
                    return;
                }
                bs[0] = b0; bs[1] = b1;
                if (!step && !(warp & 3)) st_b128(S->frag[1] + ((warp >> 2) * 32 + h) * 32 + lane, make_uint4(b0, tag, b1, 0));
                if (!isCA) break;
            } else {
#pragma unroll 1
                for (int y = y0 + ((warp - y0) & 3); y < y1 - 3 * isCA; y += 4) fetch_frag(y, warp >> 2, tag, CPOLL);
                TR(6);
                if (warp >= nmw) bar_arrive(4, 448);
            }
        }
        if (warp >= nmw) { TROUT(); return; }
    }
    if (warp == 14) {
        bar_sync(6, 288);
        const CUtensorMap* map = &M.wo[isA];
        const unsigned tag = lds32(sb + SB_CNT) + 1;
        const uint32_t t8 = tag & 0xffu;
        uint2* const snd = S->snd + r * 32 + lane;
        asm volatile("prefetch.tensormap [%0];" ::"l"(map) : "memory");
        if (PLACE && !isC) st_b64(snd, t8 ^ 0x80u, 0);
        for (int it = 0;; it++) {
            __nanosleep(2000);
            if (it > 1 && ld_b128(S->frag[1] + 25 * 32).y == tag) break;
            if (it > SPIN_MAX) __trap();
        }
        uint2 f;
        for (int it = 0;; it++) {
            f = ld_b64(S->fire + (lane & 1));
            if (__all_sync(0xffffffffu, f.y == tag)) break;
            if (it > SPIN_MAX) __trap();
            __nanosleep(FPOLL);
        }
        const unsigned t0 = __shfl_sync(0xffffffffu, f.x, 0);
        unsigned t1 = t0 + (__reduce_add_sync(0xffffffffu, (int)(f.x - t0)) >> 5) + FIRE_NS;
        TR(2);
        if (elect()) {
            const int n1 = nreq - (isC ? (isA ? NLA : NLB) : 0);
            const int dt = !isC ? (isA ? FIRE_W / NSA : FIRE_W / NSB) : isA ? FIRE_W / (32 - NSA - NLA) : FIRE_W / (32 - NSB - NLB);
            unsigned t2 = t1 + REC0_NS;
            int rec = isCA ? 2 : 0;
            int y = isCA ? 32 - ND : y0;
#pragma unroll 1
            for (int i = 0; i < nreq; i++) {
                const int row = y * 128;
                mbar_expect(bar_h + i * 16, 4096);
                mbar_expect(bar_h + i * 16 + 8, 4096);
                if (++y == 32) y = y0;
                if (i <= n1) {
                    unsigned t;
                    for (int it = 0; (int)((t = gt()) - t1) < 0 && it < 4096; it++) {}
                    t1 += dt;
                    if (rec && (int)(t - t2) >= 0) { mbar_arrive(sb + SB_BAR + --rec * 8); t2 += REC_NS - REC0_NS; }
                }
                if (EFW & 4) {
                    tma2d_ef(sb + i * 8192, map, cb * 32, row, bar_h + i * 16);
                    tma2d_ef(sb + i * 8192 + 4096, map, cb * 32, row + 64, bar_h + i * 16 + 8);
                } else {
                    tma2d(sb + i * 8192, map, cb * 32, row, bar_h + i * 16);
                    tma2d(sb + i * 8192 + 4096, map, cb * 32, row + 64, bar_h + i * 16 + 8);
                }
            }
            TR(3);
            while (rec) {
                for (int it = 0; (int)(gt() - t2) < 0 && it < 4096; it++) {}
                mbar_arrive(sb + SB_BAR + --rec * 8);
                t2 += REC_NS - REC0_NS;
            }
        }
        __syncwarp();
        uint32_t* dst = reinterpret_cast<uint32_t*>(P.out) + (lane >> 4) * 512 + (isA ? 0 : 256) + cb * 16 + (lane & 15);
        uint32_t q = sb + SC_RED + ((lane >> 4) * 20 + (lane & 15)) * 8;
        asm volatile("" : "+l"(dst), "+r"(q));
        if (!isC) {
            const float2 s = sum_parts<6, 224>(q, 0.f, 0.f);
            st_b64(snd, tagf(s.x, t8), __float_as_uint(s.y));
        } else {
            uint2 o;
            for (int it = 0;; it++) {
                o = ld_b64(snd);
                if (__all_sync(0xffffffffu, (o.x & 0xffu) == t8)) break;
                if (it > SPIN_MAX) __trap();
            }
            TR(4);
            if (isA) {
                const float2 s = sum_parts<8, 480>(q, __uint_as_float(o.x), __uint_as_float(o.y));
                asm volatile("st.global.u32 [%0], %1;" ::"l"(dst), "r"(packbf(s.x, s.y)) : "memory");
            } else {
                const float2 s = sum_parts<6 + NMW, 224 + 32 * NMW>(q, __uint_as_float(o.x), __uint_as_float(o.y));
                asm volatile("st.global.b32 [%0], %1;" ::"l"(dst), "r"(packbf(s.x, s.y)) : "memory");
            }
        }
        TR(6);
        TROUT();
        return;
    }
    {
        const int nw = 6 + nmw, wi = warp < 8 ? warp + 6 : warp - 8, t0 = wi + 2 * ND * isCA;
        bar_sync(4, 448);
        if (isCA) {
            const int y = y0 - ND + ((2 * nreq - 1 - (2 * nreq - 1 - t0) % 6) >> 1);
            const unsigned tag = lds32(sb + SB_CNT) + 1;
#pragma unroll 1
            for (int b = 0; b < 2; b++) fetch_frag(y, b, tag, DPOLL);
            __syncwarp();
            TR(6);
        }
        uint32_t rx = sb + SC_RED + (wi * 80 + (tq & 1) * 40 + (tq >> 1) * 16 + g) * 4, nb = isCA ? 480 : 224 + nmw * 32;
        asm volatile("" : "+r"(rx), "+r"(nb));
        float e[4][4];
#pragma unroll
        for (int i = 0; i < 4; i++) e[i][0] = e[i][1] = e[i][2] = e[i][3] = 0.f;
        uint32_t bp = sb + SC_FR + ((2 * (y0 - ND * isCA) + t0) * 16 + (lane & 7)) * 16, wa = wlane + t0 * 4096, bar = bar_h + t0 * 8;
        uint4 b0 = lds128(bp), b1 = lds128(bp + 128);
        const uint32_t zero = lds32(sb + SB_CNT + 4);
#pragma unroll 1
        for (int t = t0;;) {
            uint32_t a[8][4];
            b0.x ^= zero; b1.x ^= zero;
            asm volatile("" : "+r"(b0.x), "+r"(b1.x));
            mbar_wait(bar, 0);
#pragma unroll
            for (int j = 0; j < 8; j++) ldsm4t(a[j], (wa ^ ((j & 1) * 32)) + (j >> 1) * 1024);
            bp += nw * 256;
            const uint4 n0 = lds128(bp), n1 = lds128(bp + 128);
#pragma unroll
            for (int j = 0; j < 8; j++) {
                const uint4& c = (j & 4) ? b1 : b0;
                mma16816(e[(j & 1) * 2 + ((j >> 1) & 1)], a[j], (j & 2) ? c.z : c.x, (j & 2) ? c.w : c.y);
            }
            t += nw;
            if (t >= 2 * nreq) break;
            wa += nw * 4096; bar += nw * 8;
            b0 = n0; b1 = n1;
        }
        float s4[4];
#pragma unroll
        for (int c = 0; c < 4; c++) s4[c] = (tq & 2) ? e[2][c] + e[3][c] : e[0][c] + e[1][c];
        sts32(rx, __float_as_uint((tq & 1) ? s4[1] : s4[0]));
        sts32(rx + 32, __float_as_uint((tq & 1) ? s4[3] : s4[2]));
        bar_arrive(5, nb);
        TROUT();
    }
}

typedef CUresult (*EncodeFn)(CUtensorMap*, CUtensorMapDataType, cuuint32_t, void*, const cuuint64_t*, const cuuint64_t*,
                             const cuuint32_t*, const cuuint32_t*, CUtensorMapInterleave, CUtensorMapSwizzle,
                             CUtensorMapL2promotion, CUtensorMapFloatOOBfill);

void make_map(EncodeFn enc, CUtensorMap* m, const void* base, uint64_t cols, uint64_t rows, uint32_t bc, uint32_t br,
              CUtensorMapL2promotion promo, CUtensorMapSwizzle sw = CU_TENSOR_MAP_SWIZZLE_128B) {
    cuuint64_t dims[2] = {cols, rows};
    cuuint64_t strides[1] = {cols * 2};
    cuuint32_t box[2] = {bc, br};
    cuuint32_t es[2] = {1, 1};
    enc(m, CU_TENSOR_MAP_DATA_TYPE_BFLOAT16, 2, const_cast<void*>(base), dims, strides, box, es,
        CU_TENSOR_MAP_INTERLEAVE_NONE, sw, promo, CU_TENSOR_MAP_FLOAT_OOB_FILL_NONE);
}

}

extern "C" void kernel_launch(void* const* d_in, const int* in_sizes, int n_in, void* d_out, int out_size) {
    (void)in_sizes; (void)n_in; (void)out_size;
    static EncodeFn enc = nullptr;
    static void* scr = nullptr;
    if (!enc) {
        void* fn = nullptr;
        cudaDriverEntryPointQueryResult qr;
        cudaGetDriverEntryPoint("cuTensorMapEncodeTiled", &fn, cudaEnableDefault, &qr);
        enc = (EncodeFn)fn;
        cudaGetSymbolAddress(&scr, g_scr);
        cudaFuncSetAttribute(fused_decode_kernel, cudaFuncAttributeMaxDynamicSharedMemorySize, SMEM_BYTES);
    }
    Maps m;
    make_map(enc, &m.kv[0], d_in[1], 64, 1048576, 64, 64, CU_TENSOR_MAP_L2_PROMOTION_NONE);
    make_map(enc, &m.kv[1], d_in[2], 64, 1048576, 64, 64, CU_TENSOR_MAP_L2_PROMOTION_NONE);
    make_map(enc, &m.qa, d_in[3], 4096, 512, 64, 64, CU_TENSOR_MAP_L2_PROMOTION_NONE);
    make_map(enc, &m.qb, d_in[7], 4096, 512, 64, 256, SPROMO);
    make_map(enc, &m.wo[0], d_in[10], 512, 4096, 32, 64, WPROMO, CU_TENSOR_MAP_SWIZZLE_64B);
    make_map(enc, &m.wo[1], d_in[4], 512, 4096, 32, 64, WPROMO, CU_TENSOR_MAP_SWIZZLE_64B);
    {
        cuuint64_t dims[4] = {64, 8, 8, 2048}, strides[3] = {1024, 128, 8192};
        cuuint32_t box[4] = {64, 8, 8, 8}, es[4] = {1, 1, 1, 1};
        enc(&m.c, CU_TENSOR_MAP_DATA_TYPE_BFLOAT16, 4, d_in[6], dims, strides, box, es, CU_TENSOR_MAP_INTERLEAVE_NONE,
            CU_TENSOR_MAP_SWIZZLE_128B, CU_TENSOR_MAP_L2_PROMOTION_NONE, CU_TENSOR_MAP_FLOAT_OOB_FILL_NONE);
    }
    make_map(enc, &m.uk, d_in[8], 4096, 512, 64, 256, SPROMO);
    make_map(enc, &m.uv, d_in[9], 4096, 512, 64, 256, SPROMO);
    Params p;
    p.scr = (Scratch*)scr;
    p.ax = (const uint32_t*)d_in[0];
    p.bx = (const uint32_t*)d_in[5];
    p.out = (__nv_bfloat16*)d_out;
    p.wq = (const char*)d_in[3];
    fused_decode_kernel<<<128, 480, SMEM_BYTES, cudaStreamPerThread>>>(p, m);
}
```

```cpp
#include <cuda_runtime.h>
#include <cuda_bf16.h>
#include <cuda.h>
#include <stdint.h>
#include <float.h>

#define LIM 12
#define LIM0 8
#define RAMP_S 256
#define RAMP_T0 300
#define BAL 20
#define SKEW 3
#define ROT 128
#define XD0 1000
#define XDS 12
#define BSTART 3000
#define BSTAG 500
#define FIRE_T 240
#define FIRE_NS 3300
#define FIRE_W 1950
#define NLA 6
#define NLB 10
#define NSA 13
#define NSB 13
#define REC0_NS 100
#define REC_NS 1700
#define NMW 6
#define QSLEEP 1200
#define QPOLL 300
#define BPOLL 1000
#define CPOLL 700
#define DPOLL 300
#define FPOLL 300

namespace {

constexpr int NG = 2, CPG = 32, NW = 4;
constexpr int UPG = 8192;
constexpr int NSL = 12, SPW = NSL / NW;
constexpr int SPIN_MAX = 1 << 22;
constexpr float LOG2E = 1.4426950408889634f;
constexpr float SCALE = 0.08838834764831845f;
constexpr uint64_t EVICT_FIRST = 0x12F0000000000000ull;

constexpr int SA_SLOT = NSL * 16384;
constexpr int SA_Q    = SA_SLOT + 8 * NW * 132 * 4;
constexpr int SA_FULL = SA_Q + 8192;
constexpr int SA_EMPTY = SA_FULL + NSL * 16;
constexpr int SA_GOV  = SA_EMPTY + NSL * 8;
constexpr int SA_MBAR = SA_GOV + NSL * 8;
constexpr int SA_QBAR = SA_MBAR + 128;
constexpr int SA_META = SA_QBAR + 24;
constexpr int SA_LIM  = SA_META + NSL * 4;
constexpr int SA_CNT  = SA_LIM + 16;
constexpr int SA_END  = SA_CNT + 64;
constexpr int PROW    = 2080;
constexpr int SB_STG  = 0;
constexpr int SB_QIMG = 131072;
constexpr int SB_P    = SB_QIMG + 32 * PROW;
constexpr int SB_AL   = SB_P + 8192;
constexpr int SB_X    = SB_AL + 256;
static_assert(SB_P % 1024 == 0, "swizzle atom");
constexpr int SB_QB   = SB_X + 4352;
constexpr int NT      = 40;
constexpr int SC_FR   = NT * 4096;
constexpr int SC_FP   = SC_FR + 16384;
constexpr int SC_RED  = SB_QB + 1024;
constexpr int SB_BAR  = SC_RED + 4480;
constexpr int SB_CNT  = SB_BAR + (12 + NT) * 8;
static_assert(SC_FP + 8448 <= SB_P && 2 * (32 - NSA) <= NT && 2 * (32 - NSB) <= NT && NSA <= 16 && NSB <= 16, "projection slots");
constexpr int SB_END  = SB_CNT + 64;
constexpr int SMEM_BYTES = (SA_END > SB_END ? SA_END : SB_END);
static_assert(SMEM_BYTES <= 232448, "shared memory");

struct Scratch {
    uint4    bpart[32 * 32 * (PROW / 16)];
    uint4    apart[64 * CPG * 32];
    uint4    qimg[2 * 4096];
    uint4    qpub[64 * 32];
    uint4    frag[2][64 * 32];
    uint2    snd[32 * 32];
    uint2    aml[64 * CPG * 4];
    unsigned ctr[1088];
    uint2    fire[544];
    unsigned qflag[1088], bflag[1088];
};
__device__ __align__(1024) Scratch g_scr;

__device__ __forceinline__ uint32_t s2u(const void* p) { return (uint32_t)__cvta_generic_to_shared(p); }
__device__ __forceinline__ bool elect() {
    uint32_t ok;
    asm volatile("{\n.reg .pred p;\nelect.sync _|p, 0xffffffff;\nselp.u32 %0,1,0,p;\n}" : "=r"(ok));
    return ok;
}
__device__ __forceinline__ void mbar_init(uint32_t b, int c) {
    asm volatile("mbarrier.init.shared::cta.b64 [%0], %1;" ::"r"(b), "r"(c) : "memory");
}
__device__ __forceinline__ void mbar_init_fence() { asm volatile("fence.mbarrier_init.release.cluster;" ::: "memory"); }
__device__ __forceinline__ void mbar_expect(uint32_t b, uint32_t bytes) {
    asm volatile("mbarrier.arrive.expect_tx.shared::cta.b64 _, [%0], %1;" ::"r"(b), "r"(bytes) : "memory");
}
__device__ __forceinline__ void mbar_arrive(uint32_t b) {
    asm volatile("mbarrier.arrive.shared::cta.b64 _, [%0];" ::"r"(b) : "memory");
}
__device__ __forceinline__ bool mbar_test(uint32_t b, uint32_t ph) {
    uint32_t ok;
    asm volatile("{\n.reg .pred p;\nmbarrier.test_wait.parity.shared::cta.b64 p, [%1], %2;\nselp.u32 %0,1,0,p;\n}"
                 : "=r"(ok) : "r"(b), "r"(ph) : "memory");
    return ok;
}
__device__ __forceinline__ void mbar_wait(uint32_t b, uint32_t ph) {
    asm volatile("{\n.reg .pred p;\n.reg .u32 n;\nmov.u32 n, 0;\n"
                 "W: mbarrier.try_wait.parity.shared::cta.b64 p, [%0], %1;\n@p bra.uni D;\n"
                 "add.u32 n, n, 1;\nsetp.lt.u32 p, n, %2;\n@p bra.uni W;\ntrap;\nD:\n}"
                 ::"r"(b), "r"(ph), "n"(SPIN_MAX) : "memory");
}
__device__ __forceinline__ void tma2d(uint32_t dst, const CUtensorMap* map, int c0, int c1, uint32_t bar) {
    asm volatile("cp.async.bulk.tensor.2d.shared::cluster.global.mbarrier::complete_tx::bytes [%0], [%1, {%3, %4}], [%2];"
                 ::"r"(dst), "l"(map), "r"(bar), "r"(c0), "r"(c1) : "memory");
}
__device__ __forceinline__ void tma2d_ef(uint32_t dst, const CUtensorMap* map, int c0, int c1, uint32_t bar) {
    asm volatile("cp.async.bulk.tensor.2d.shared::cluster.global.mbarrier::complete_tx::bytes.L2::cache_hint [%0], [%1, {%3, %4}], [%2], %5;"
                 ::"r"(dst), "l"(map), "r"(bar), "r"(c0), "r"(c1), "l"(EVICT_FIRST) : "memory");
}
__device__ __forceinline__ void tma4d_ef(uint32_t dst, const CUtensorMap* map, int c3, uint32_t bar) {
    asm volatile("cp.async.bulk.tensor.4d.shared::cluster.global.mbarrier::complete_tx::bytes.L2::cache_hint [%0], [%1, {0, 0, 0, %3}], [%2], %4;"
                 ::"r"(dst), "l"(map), "r"(bar), "r"(c3), "l"(EVICT_FIRST) : "memory");
}
__device__ __forceinline__ void bulk_g2s(uint32_t dst, const void* src, uint32_t bytes, uint32_t bar) {
    asm volatile("cp.async.bulk.shared::cluster.global.mbarrier::complete_tx::bytes [%0], [%1], %2, [%3];"
                 ::"r"(dst), "l"(src), "r"(bytes), "r"(bar) : "memory");
}
__device__ __forceinline__ void bulk_s2g(void* dst, uint32_t src, uint32_t bytes) {
    asm volatile("cp.async.bulk.global.shared::cta.bulk_group [%0], [%1], %2;" ::"l"(dst), "r"(src), "r"(bytes) : "memory");
}
__device__ __forceinline__ void fence_async_all() { asm volatile("fence.proxy.async;" ::: "memory"); }
__device__ __forceinline__ void bar_sync(int id, int n) { asm volatile("bar.sync %0, %1;" ::"r"(id), "r"(n) : "memory"); }
__device__ __forceinline__ void bar_arrive(int id, int n) { asm volatile("bar.arrive %0, %1;" ::"r"(id), "r"(n) : "memory"); }
__device__ __forceinline__ unsigned ld_relaxed1(const void* p) {
    unsigned v;
    asm volatile("ld.relaxed.gpu.global.u32 %0, [%1];" : "=r"(v) : "l"(p) : "memory");
    return v;
}
__device__ __forceinline__ unsigned atom_inc(unsigned* p) {
    unsigned v;
    asm volatile("atom.relaxed.gpu.global.add.u32 %0, [%1], 1;" : "=r"(v) : "l"(p) : "memory");
    return v;
}
__device__ __forceinline__ uint4 ld_b128(const void* p) {
    uint4 v;
    asm volatile("{\n.reg .b128 t;\nld.relaxed.gpu.global.b128 t, [%4];\nmov.b128 {%0,%1,%2,%3}, t;\n}"
                 : "=r"(v.x), "=r"(v.y), "=r"(v.z), "=r"(v.w) : "l"(p) : "memory");
    return v;
}
__device__ __forceinline__ void st_b128(void* p, uint4 v) {
    asm volatile("{\n.reg .b128 t;\nmov.b128 t, {%1,%2,%3,%4};\nst.relaxed.gpu.global.b128 [%0], t;\n}"
                 ::"l"(p), "r"(v.x), "r"(v.y), "r"(v.z), "r"(v.w) : "memory");
}
__device__ __forceinline__ uint2 ld_b64(const void* p) {
    uint2 v;
    asm volatile("{\n.reg .b64 a;\nld.relaxed.gpu.global.b64 a, [%2];\nmov.b64 {%0,%1}, a;\n}" : "=r"(v.x), "=r"(v.y) : "l"(p) : "memory");
    return v;
}
__device__ __forceinline__ void st_b64(void* p, uint32_t a, uint32_t b) {
    asm volatile("{\n.reg .b64 t;\nmov.b64 t, {%1,%2};\nst.relaxed.gpu.global.b64 [%0], t;\n}" ::"l"(p), "r"(a), "r"(b) : "memory");
}
__device__ __forceinline__ unsigned ld_acquire(const unsigned* p) {
    unsigned v;
    asm volatile("ld.acquire.gpu.global.u32 %0, [%1];" : "=r"(v) : "l"(p) : "memory");
    return v;
}
__device__ __forceinline__ void st_release(unsigned* p, unsigned v) {
    asm volatile("st.release.gpu.global.u32 [%0], %1;" ::"l"(p), "r"(v) : "memory");
}
__device__ __forceinline__ void ldsm4(uint32_t (&r)[4], uint32_t a) {
    asm volatile("ldmatrix.sync.aligned.m8n8.x4.shared.b16 {%0,%1,%2,%3}, [%4];"
                 : "=r"(r[0]), "=r"(r[1]), "=r"(r[2]), "=r"(r[3]) : "r"(a) : "memory");
}
__device__ __forceinline__ void ldsm4t(uint32_t (&r)[4], uint32_t a) {
    asm volatile("ldmatrix.sync.aligned.m8n8.x4.trans.shared.b16 {%0,%1,%2,%3}, [%4];"
                 : "=r"(r[0]), "=r"(r[1]), "=r"(r[2]), "=r"(r[3]) : "r"(a) : "memory");
}
__device__ __forceinline__ uint4 lds128(uint32_t a) {
    uint4 v;
    asm volatile("ld.shared.v4.u32 {%0, %1, %2, %3}, [%4];" : "=r"(v.x), "=r"(v.y), "=r"(v.z), "=r"(v.w) : "r"(a) : "memory");
    return v;
}
__device__ __forceinline__ float2 lds64f(uint32_t a) {
    float2 v;
    asm volatile("ld.shared.v2.f32 {%0, %1}, [%2];" : "=f"(v.x), "=f"(v.y) : "r"(a) : "memory");
    return v;
}
__device__ __forceinline__ uint32_t lds32(uint32_t a) {
    uint32_t v;
    asm volatile("ld.shared.u32 %0, [%1];" : "=r"(v) : "r"(a) : "memory");
    return v;
}
__device__ __forceinline__ void sts32(uint32_t a, uint32_t v) { asm volatile("st.shared.u32 [%0], %1;" ::"r"(a), "r"(v) : "memory"); }
__device__ __forceinline__ void mma16816(float (&d)[4], const uint32_t (&a)[4], uint32_t b0, uint32_t b1) {
    asm volatile("mma.sync.aligned.m16n8k16.row.col.f32.bf16.bf16.f32 {%0,%1,%2,%3}, {%4,%5,%6,%7}, {%8,%9}, {%0,%1,%2,%3};"
                 : "+f"(d[0]), "+f"(d[1]), "+f"(d[2]), "+f"(d[3])
                 : "r"(a[0]), "r"(a[1]), "r"(a[2]), "r"(a[3]), "r"(b0), "r"(b1));
}
__device__ __forceinline__ uint32_t prmt0(uint32_t a, uint32_t sel) {
    uint32_t d;
    asm volatile("prmt.b32 %0, %1, 0, %2;" : "=r"(d) : "r"(a), "r"(sel));
    return d;
}
__device__ __forceinline__ unsigned gt() {
    unsigned t;
    asm volatile("mov.u32 %0, %globaltimer_lo;" : "=r"(t));
    return t;
}
__device__ __forceinline__ unsigned clk32() {
    unsigned c;
    asm volatile("mov.u32 %0, %clock;" : "=r"(c));
    return c;
}
__device__ __forceinline__ float ex2(float x) {
    float y;
    asm("ex2.approx.ftz.f32 %0, %1;" : "=f"(y) : "f"(x));
    return y;
}
__device__ __forceinline__ float bf16r(float x) { return __bfloat162float(__float2bfloat16_rn(x)); }
__device__ __forceinline__ uint32_t packbf(float lo, float hi) {
    uint32_t r;
    asm("cvt.rn.bf16x2.f32 %0, %1, %2;" : "=r"(r) : "f"(hi), "f"(lo));
    return r;
}
__device__ __forceinline__ float bflo(uint32_t v) { return __uint_as_float(v << 16); }
__device__ __forceinline__ float bfhi(uint32_t v) { return __uint_as_float(v & 0xffff0000u); }
__device__ __forceinline__ uint32_t tagf(float v, uint32_t t8) { return (__float_as_uint(v) & 0xffffff00u) | t8; }
__device__ __forceinline__ float shx(float v, int m) { return __shfl_xor_sync(0xffffffffu, v, m); }

__device__ __forceinline__ float warp_max(float v) {
    int i = __float_as_int(v);
    i = __reduce_max_sync(0xffffffffu, i ^ ((i >> 31) & 0x7fffffff));
    return __int_as_float(i ^ ((i >> 31) & 0x7fffffff));
}

__device__ __forceinline__ uint64_t gdesc(uint32_t addr, uint32_t lbo, uint32_t sbo) {
    return (uint64_t)((addr & 0x3ffff) >> 4) | ((uint64_t)(lbo >> 4) << 16) | ((uint64_t)(sbo >> 4) << 32) | (1ull << 62);
}
__device__ __forceinline__ void wg_fence() { asm volatile("wgmma.fence.sync.aligned;" ::: "memory"); }
__device__ __forceinline__ void wg_commit() { asm volatile("wgmma.commit_group.sync.aligned;" ::: "memory"); }
__device__ __forceinline__ void wg_wait0() { asm volatile("wgmma.wait_group.sync.aligned 0;" ::: "memory"); }
template <int N> __device__ __forceinline__ void reg_fence(float (&r)[N]) {
#pragma unroll
    for (int i = 0; i < N; i++) asm volatile("" : "+f"(r[i])::"memory");
}
#define F8(a, o) "+f"(a[o]), "+f"(a[o + 1]), "+f"(a[o + 2]), "+f"(a[o + 3]), "+f"(a[o + 4]), "+f"(a[o + 5]), "+f"(a[o + 6]), "+f"(a[o + 7])
#define F32(a, o) F8(a, o), F8(a, o + 8), F8(a, o + 16), F8(a, o + 24)
__device__ __forceinline__ void wgmma_n64_ss(float (&d)[32], uint64_t da, uint64_t db, int scale_d) {
    asm volatile(
        "{\n.reg .pred p;\nsetp.ne.b32 p, %34, 0;\n"
        "wgmma.mma_async.sync.aligned.m64n64k16.f32.bf16.bf16 "
        "{%0,%1,%2,%3,%4,%5,%6,%7,%8,%9,%10,%11,%12,%13,%14,%15,%16,%17,%18,%19,%20,%21,%22,%23,%24,%25,%26,%27,%28,%29,%30,%31},"
        " %32, %33, p, 1, 1, 0, 0;\n}"
        : F32(d, 0) : "l"(da), "l"(db), "r"(scale_d));
}
__device__ __forceinline__ void wgmma_n32_ts(float (&d)[16], uint64_t da, uint64_t db) {
    asm volatile(
        "{\n.reg .pred p;\nsetp.ne.b32 p, 1, 0;\n"
        "wgmma.mma_async.sync.aligned.m64n32k16.f32.bf16.bf16 "
        "{%0,%1,%2,%3,%4,%5,%6,%7,%8,%9,%10,%11,%12,%13,%14,%15}, %16, %17, p, 1, 1, 1, 0;\n}"
        : F8(d, 0), F8(d, 8) : "l"(da), "l"(db));
}

struct Params {
    Scratch* scr;
    const uint32_t *ax, *bx;
    const char* wq;
    __nv_bfloat16* out;
};
struct Maps { CUtensorMap kv[2], qa, qb, wo[2], c, uk, uv; };

__device__ __forceinline__ void wait_flags(const unsigned* flags, unsigned tag, int lane) {
    for (int i = 0; !__all_sync(0xffffffffu, ld_acquire(flags + lane * 8) == tag); i++) {
        if (i > SPIN_MAX) __trap();
        __nanosleep(BPOLL);
    }
    __syncwarp();
}
__device__ __forceinline__ void load_slice(uint32_t dst, const CUtensorMap* map, int r, uint32_t bar) {
    mbar_expect(bar, 131072);
#pragma unroll
    for (int x = 0; x < 4; x++) tma2d_ef(dst + x * 32768, map, r * 128 + (x & 1) * 64, (x >> 1) * 256, bar);
}
__device__ __forceinline__ void gemv_slice(uint32_t sb, int warp, int lane) {
    const int g = lane >> 2, tq = lane & 3;
    float d[4][4];
#pragma unroll
    for (int i = 0; i < 4; i++) d[i][0] = d[i][1] = d[i][2] = d[i][3] = 0.f;
    const uint32_t wb = sb + SB_STG + (warp >> 2) * 32768 + ((lane & 7) + 8 * (lane >> 4)) * 128 +
                        (((2 * (warp & 3) + ((lane >> 3) & 1)) ^ (lane & 7)) << 4);
    const uint32_t xb = sb + SB_X + ((g & 3) * 264 + tq) * 4;
#pragma unroll 1
    for (int k8 = 0; k8 < 4; k8++) {
        uint32_t a[8][4], b[8][2];
#pragma unroll
        for (int ks = 0; ks < 8; ks++) {
            ldsm4t(a[ks], wb + (k8 >> 1) * 65536 + (k8 & 1) * 16384 + ks * 2048);
            b[ks][0] = lds32(xb + k8 * 256 + ks * 32);
            b[ks][1] = lds32(xb + k8 * 256 + ks * 32 + 16);
        }
#pragma unroll
        for (int ks = 0; ks < 8; ks++) mma16816(d[ks & 3], a[ks], b[ks][0], b[ks][1]);
    }
    const float y0 = ((d[0][0] + d[1][0]) + (d[2][0] + d[3][0])) + ((d[0][1] + d[1][1]) + (d[2][1] + d[3][1]));
    const float y1 = ((d[0][2] + d[1][2]) + (d[2][2] + d[3][2])) + ((d[0][3] + d[1][3]) + (d[2][3] + d[3][3]));
    if (tq < 2) {
        sts32(sb + SB_QB + (tq * 128 + warp * 16 + g) * 4, __float_as_uint(y0));
        sts32(sb + SB_QB + (tq * 128 + warp * 16 + 8 + g) * 4, __float_as_uint(y1));
    }
}
__device__ __forceinline__ uint32_t wo_lane(uint32_t sb, int lane) {
    return sb + ((lane & 7) + 8 * (lane >> 4)) * 64 + ((((lane >> 3) & 1) ^ ((lane >> 1) & 3)) << 4);
}

template <int NP, int NTHR> __device__ __forceinline__ float2 sum_parts(uint32_t q, float x, float y) {
    asm volatile("bar.sync 5, %0;" ::"n"(NTHR) : "memory");
    float2 p[NP];
#pragma unroll
    for (int i = 0; i < NP; i++) p[i] = lds64f(q + i * 320);
    p[0].x += x; p[0].y += y;
#pragma unroll
    for (int d = 1; d < NP; d *= 2)
#pragma unroll
        for (int i = 0; i + d < NP; i += 2 * d) { p[i].x += p[i + d].x; p[i].y += p[i + d].y; }
    return p[0];
}

__device__ __forceinline__ void latent_branch(const Params& P, const Maps& M, uint8_t* sm) {
    const uint32_t sb = s2u(sm);
    const int tid = threadIdx.x, lane = tid & 31, warp = tid >> 5, g = lane >> 2, tq = lane & 3, r = blockIdx.x >> 2;
    const uint32_t bar_w = sb + SB_BAR + 16, bar_x = sb + SB_BAR + 24;
    const unsigned tag = lds32(sb + SB_CNT) + 1;
    Scratch* const S = P.scr;
    const float* yb = reinterpret_cast<const float*>(sm + SB_QB);
    float* xs = reinterpret_cast<float*>(sm + SB_X);
    const int crow0 = (r >> 4) * 8192 + (r & 15) * 64;
    {
        uint32_t* xh = reinterpret_cast<uint32_t*>(sm + SB_X) + tid;
        xh[0] = __ldg(P.bx + tid); xh[264] = 0; xh[528] = __ldg(P.bx + 256 + tid); xh[792] = 0;
        bar_sync(0, 256);
        mbar_wait(bar_w, 0);
        gemv_slice(sb, warp, lane);
        bar_sync(0, 256);
        if (tid == 0) load_slice(sb + SB_STG, &M.uk, r, bar_w);
        uint32_t qb[8][2];
#pragma unroll
        for (int ks = 0; ks < 8; ks++) {
            const float2 a = *reinterpret_cast<const float2*>(yb + (g & 1) * 128 + ks * 16 + 2 * tq);
            const float2 b = *reinterpret_cast<const float2*>(yb + (g & 1) * 128 + ks * 16 + 8 + 2 * tq);
            qb[ks][0] = packbf(a.x, a.y);
            qb[ks][1] = packbf(b.x, b.y);
        }
        mbar_wait(bar_w, 1);
        const uint32_t wb = sb + SB_STG + (warp >> 2) * 65536 + ((warp & 3) * 64 + (lane & 15)) * 128;
#pragma unroll 1
        for (int mt = 0; mt < 4; mt++) {
            float d[4] = {0.f, 0.f, 0.f, 0.f};
#pragma unroll
            for (int ks = 0; ks < 8; ks++) {
                uint32_t a[4];
                ldsm4(a, wb + (ks >> 2) * 32768 + mt * 2048 + (((2 * (ks & 3) + (lane >> 4)) ^ (lane & 7)) << 4));
                mma16816(d, a, qb[ks][0], qb[ks][1]);
            }
            if (tq == 0) {
                const int c = warp * 64 + mt * 16 + g;
                xs[c] = d[0]; xs[512 + c] = d[1]; xs[c + 8] = d[2]; xs[512 + c + 8] = d[3];
            }
        }
        bar_sync(0, 256);
        if (tid == 32) {
#pragma unroll
            for (int t = 0; t < 2; t++) {
                mbar_expect(sb + SB_BAR + t * 8, 65536);
                tma4d_ef(sb + SB_STG + t * 65536, &M.c, (crow0 >> 3) + t * 128, sb + SB_BAR + t * 8);
            }
        }
        const int b = tid >> 7, lo = (tid >> 6) & 1, ch = tid & 63;
        float v[8];
#pragma unroll
        for (int i = 0; i < 8; i++) {
            const float x = xs[b * 512 + ch * 8 + i];
            v[i] = lo ? x - bf16r(x) : x;
        }
        const int row = 16 * (r >> 3) + (r & 7) + 8 * lo;
        S->qimg[b * 4096 + (ch >> 3) * 512 + row * 8 + ((ch & 7) ^ (r & 7))] =
            make_uint4(packbf(v[0], v[1]), packbf(v[2], v[3]), packbf(v[4], v[5]), packbf(v[6], v[7]));
        bar_sync(0, 256);
        if (warp == 0) {
            if (lane == 0) { __threadfence(); st_release(S->qflag + r * 8, tag); }
            wait_flags(S->qflag, tag, lane);
            if (lane == 0) {
                fence_async_all();
                mbar_expect(bar_x, 65536);
                bulk_g2s(sb + SB_QIMG, S->qimg + (r >> 4) * 4096, 65536, bar_x);
            }
        }
        mbar_wait(bar_x, 0);
    }
    {
        const int wg = warp >> 2;
        float acc[4][16];
#pragma unroll
        for (int i = 0; i < 64; i++) acc[i >> 4][i & 15] = 0.f;
        const int head = (warp & 3) * 8 + g;
        const uint32_t pa = sb + SB_P + wg * 4096;
        float* al = reinterpret_cast<float*>(sm + SB_AL) + wg * 32;
        float m = -FLT_MAX, l = 0.f;
#pragma unroll 1
        for (int t = 0; t < 8; t++) {
            const uint32_t stg = sb + SB_STG + (t & 1) * 65536;
            mbar_wait(sb + SB_BAR + (t & 1) * 8, (t >> 1) & 1);
            float s[32];
            uint32_t qa = sb + SB_QIMG;
            asm volatile("" : "+r"(qa));
            wg_fence();
#pragma unroll
            for (int k = 0; k < 32; k++) {
                const uint32_t off = (k >> 2) * 8192 + (k & 3) * 32;
                wgmma_n64_ss(s, gdesc(qa + off, 16, 1024), gdesc(stg + (k >> 2) * 1024 + (k & 3) * 32, 16, 8192), k > 0);
            }
            wg_commit();
            wg_wait0();
            reg_fence(s);
            float p[16], mx = m;
#pragma unroll
            for (int i = 0; i < 8; i++) {
                p[2 * i] = bf16r(bf16r(s[4 * i] + s[4 * i + 2]) * SCALE);
                p[2 * i + 1] = bf16r(bf16r(s[4 * i + 1] + s[4 * i + 3]) * SCALE);
                mx = fmaxf(mx, fmaxf(p[2 * i], p[2 * i + 1]));
            }
            mx = fmaxf(mx, shx(mx, 1));
            mx = fmaxf(mx, shx(mx, 2));
            const float alpha = ex2((m - mx) * LOG2E);
            m = mx;
            float sum = 0.f;
#pragma unroll
            for (int i = 0; i < 8; i++) {
                const float a = ex2((p[2 * i] - mx) * LOG2E), b = ex2((p[2 * i + 1] - mx) * LOG2E);
                sum += a + b;
                sts32(pa + head * 128 + ((i ^ g) << 4) + tq * 4, packbf(a, b));
            }
            l = fmaf(l, alpha, sum);
            if (tq == 0) al[head] = alpha;
            asm volatile("fence.proxy.async.shared::cta;" ::: "memory");
            bar_sync(1 + wg, 128);
#pragma unroll
            for (int j = 0; j < 4; j++) {
                const float2 a = *reinterpret_cast<const float2*>(al + 8 * j + 2 * tq);
#pragma unroll
                for (int i = 0; i < 4; i++) { acc[i][4 * j] *= a.x; acc[i][4 * j + 1] *= a.y; acc[i][4 * j + 2] *= a.x; acc[i][4 * j + 3] *= a.y; }
            }
#pragma unroll
            for (int i = 0; i < 4; i++) reg_fence(acc[i]);
            wg_fence();
#pragma unroll
            for (int kk = 0; kk < 4; kk++)
#pragma unroll
                for (int i = 0; i < 4; i++)
                    wgmma_n32_ts(acc[i], gdesc(stg + (wg * 4 + i) * 1024 + kk * 16384, 1024, 8192), gdesc(pa + kk * 32, 16, 1024));
            wg_commit();
            wg_wait0();
#pragma unroll
            for (int i = 0; i < 4; i++) reg_fence(acc[i]);
            bar_sync(0, 256);
            if (tid == 0) {
                if (t + 2 < 8) {
                    const uint32_t bar = sb + SB_BAR + (t & 1) * 8;
                    mbar_expect(bar, 65536);
                    tma4d_ef(stg, &M.c, (crow0 >> 3) + (t + 2) * 128, bar);
                }
                if (t == 7) load_slice(sb + SB_STG, &M.uv, r, bar_w);
            }
        }
        float* dst = reinterpret_cast<float*>(sm + SB_QIMG + 2 * tq * PROW) + wg * 256 + (warp & 3) * 16 + g;
#pragma unroll
        for (int i = 0; i < 64; i++)
            dst[(((i >> 2) & 3) * 8 + (i & 1)) * (PROW / 4) + (i >> 4) * 64 + (i & 2) * 4] = acc[i >> 4][i & 15];
        l += shx(l, 1); l += shx(l, 2);
        if (wg == 0 && tq < 2) *reinterpret_cast<float4*>(sm + SB_QIMG + head * PROW + 2048 + tq * 16) = make_float4(m, l, 0.f, 0.f);
        asm volatile("fence.proxy.async.shared::cta;" ::: "memory");
        bar_sync(0, 256);
        if (warp == 0) {
            bulk_s2g(S->bpart + (lane * 32 + r) * (PROW / 16), sb + SB_QIMG + lane * PROW, PROW);
            asm volatile("cp.async.bulk.commit_group;" ::: "memory");
            asm volatile("cp.async.bulk.wait_group 0;" ::: "memory");
            fence_async_all();
            __threadfence();
            __syncwarp();
            if (lane == 0) st_release(S->bflag + r * 8, tag);
            wait_flags(S->bflag, tag, lane);
            if (lane == 0) {
                fence_async_all();
                mbar_expect(bar_x, 32 * PROW);
                bulk_g2s(sb + SB_QIMG, S->bpart + r * 32 * (PROW / 16), 32 * PROW, bar_x);
            }
        }
    }
    {
        const int b = tid >> 7, c4 = tid & 127;
        mbar_wait(bar_x, 1);
        const float2 ml = *reinterpret_cast<const float2*>(sm + SB_QIMG + (b * 16 + (lane & 15)) * PROW + 2048);
        float MM = ml.x;
        MM = fmaxf(MM, shx(MM, 1)); MM = fmaxf(MM, shx(MM, 2)); MM = fmaxf(MM, shx(MM, 4)); MM = fmaxf(MM, shx(MM, 8));
        const float e = ex2((ml.x - MM) * LOG2E);
        float L = e * ml.y;
        L += shx(L, 1); L += shx(L, 2); L += shx(L, 4); L += shx(L, 8);
        const float wgt = e / L;
        float4 o = make_float4(0.f, 0.f, 0.f, 0.f);
#pragma unroll 4
        for (int i = 0; i < 16; i++) {
            const float w = __shfl_sync(0xffffffffu, wgt, i);
            const float4 v = *reinterpret_cast<const float4*>(sm + SB_QIMG + (b * 16 + i) * PROW + c4 * 16);
            o.x = fmaf(w, v.x, o.x); o.y = fmaf(w, v.y, o.y); o.z = fmaf(w, v.z, o.z); o.w = fmaf(w, v.w, o.w);
        }
        uint32_t* xh = reinterpret_cast<uint32_t*>(xs);
        const uint32_t h0 = packbf(o.x, o.y), h1 = packbf(o.z, o.w);
        *reinterpret_cast<uint2*>(xh + (2 * b) * 264 + c4 * 2) = make_uint2(h0, h1);
        *reinterpret_cast<uint2*>(xh + (2 * b + 1) * 264 + c4 * 2) =
            make_uint2(packbf(o.x - bflo(h0), o.y - bfhi(h0)), packbf(o.z - bflo(h1), o.w - bfhi(h1)));
        bar_sync(0, 256);
        mbar_wait(bar_w, 0);
        gemv_slice(sb, warp, lane);
        bar_sync(0, 256);
        if (tid < 64) {
            const float* y = yb + warp * 128 + 16 * g + 2 * tq;
            st_b128(S->frag[0] + (warp * 32 + r) * 32 + lane, make_uint4(packbf(y[0], y[1]), tag, packbf(y[8], y[9]), tag));
        }
    }
}

__global__ void __launch_bounds__(480, 1)
fused_decode_kernel(const Params P, const __grid_constant__ Maps M) {
    extern __shared__ __align__(1024) uint8_t sm[];
    const uint32_t sb = s2u(sm);
    const int tid = threadIdx.x, lane = tid & 31, bx = blockIdx.x;
    asm volatile("{\n.reg .pred p;\nsetp.lt.u32 p, %1, 256;\n@p prefetch.global.L2 [%0];\n}"
                 ::"l"(P.wq + (unsigned)(((bx & 1) * 256 + tid) * 8192 + (bx >> 1) * 128)), "r"(tid) : "memory");
    const int warp = __shfl_sync(0xffffffffu, tid >> 5, 0);
    const int g = lane >> 2, tq = lane & 3;
    Scratch* const S = P.scr;

    if (!(bx & 1)) {
        const int grp = (bx >> 1) & 1, crk = bx >> 2;
        const int rowbase = grp * (UPG * 64);
        auto issue = [&](int slot, unsigned tk, int v) {
            const int row = rowbase + (int)((tk & ~255u) | ((tk + grp * ROT) & 255u)) * 64;
            const uint32_t full = sb + SA_FULL + slot * 16 + v * 8;
            mbar_expect(full, 8192);
            tma2d_ef(sb + slot * 16384 + v * 8192, &M.kv[v], 0, row, full);
        };
        if (warp >= 8) {
            const int w = warp - 8;
            if (w >= NW) {
                if (w == NW && !(bx & 15)) asm volatile("prefetch.global.L2 [%0];" ::"l"(((lane & 16) ? P.bx : P.ax) + (lane & 15) * 32) : "memory");
                return;
            }
            const bool one = elect();
            if (one) {
                mbar_init(sb + SA_FULL + w * 16, 1);
                mbar_init_fence();
                sts32(sb + SA_META + w * 4, 0);
                if (w < SKEW) issue(w, w * CPG + crk, 0);
#pragma unroll
                for (int i = 0; i < SPW; i++) {
                    if (i) mbar_init(sb + SA_FULL + (w + i * NW) * 16, 1);
                    mbar_init(sb + SA_FULL + (w + i * NW) * 16 + 8, 1);
                    mbar_init(sb + SA_GOV + (w + i * NW) * 8, 1);
                    mbar_init(sb + SA_EMPTY + (w + i * NW) * 8, 2);
                    mbar_arrive(sb + SA_EMPTY + (w + i * NW) * 8);
                }
                if (w < SKEW) mbar_arrive(sb + SA_EMPTY + w * 8);
                sts32(sb + SA_LIM + w * 4, LIM);
                mbar_init_fence();
            }
            __syncwarp();
            bar_arrive(2, (NW + 1) * 32);
            bar_arrive(1, (2 * NW + 2) * 32);
            unsigned c = 0;
            int slot = w;
            uint32_t eph = 0;
#pragma unroll 1
            for (int n = 0;; n++) {
                unsigned tk = (n * NW + w) * CPG + crk, own = 0;
                if (n >= SPW) {
                    own = __shfl_sync(0xffffffffu, c, grp);
                    tk = own % UPG + NSL * CPG;
                    const int lag = (int)(__reduce_add_sync(0xffffffffu, c) - NG * own);
                    if (one) sts32(sb + SA_LIM + w * 4, lag > BAL * NG ? LIM + 1 : lag < -BAL * NG ? LIM - 1 : LIM);
                }
                mbar_wait(sb + SA_EMPTY + slot * 8, eph);
                if (tk >= UPG) {
                    if (one) {
                        sts32(sb + SA_LIM + w * 4, 0);
                        sts32(sb + SA_META + slot * 4, 32);
                        mbar_arrive(sb + SA_FULL + slot * 16);
                        asm volatile("red.relaxed.gpu.global.add.u32 [%0], %1;" ::"l"(S->ctr + grp), "n"(SPW - 1) : "memory");
                    }
                    return;
                }
                if (one && (n || w >= SKEW)) {
                    sts32(sb + SA_META + slot * 4, tk >> 8);
                    issue(slot, tk, 0);
                    if (tk == UPG - FIRE_T) st_b64(S->fire + grp, gt(), own / UPG + 1);
                }
                if (n >= SPW - 1) {
                    if (lane == grp) c = atom_inc(S->ctr + lane);
                    else if (lane < NG) c = ld_relaxed1(S->ctr + lane);
                }
                mbar_wait(sb + SA_GOV + slot * 8, eph);
                if (one) issue(slot, tk, 1);
                slot += NW;
                if (slot >= NSL) { slot -= NSL; eph ^= 1; }
                __syncwarp();
            }
        }
        if (warp == 0) {
            bool busy = lane < 2 * SKEW && !(lane & 1);
            uint32_t par = busy ? 0 : 1;
            int slot = SKEW;
            bool first = true;
            const unsigned c0 = clk32() + RAMP_T0;
            const int own = lane >= 2 * NSL ? -1 : ((lane >> 1) + (lane & 1) * SKEW) % NSL;
            const uint32_t fb = sb + SA_FULL + lane * 8, lw = sb + SA_LIM + ((lane >> 1) % NW) * 4;
            const uint32_t go = sb + ((lane & 1) ? SA_GOV : SA_EMPTY) + (lane >> 1) * 8;
            bar_sync(2, (NW + 1) * 32);
#pragma unroll 1
            for (int it = 0; it < SPIN_MAX; it++) {
                bool ok = true;
                if (busy) ok = mbar_test(fb, par);
                int lim = lds32(lw);
                if (first) lim = min(LIM0, SKEW + max((int)(clk32() - c0), 0) / RAMP_S);
                busy = busy && !ok && lim;
                const int n = __popc(__ballot_sync(0xffffffffu, busy));
                if (!__any_sync(0xffffffffu, lim)) return;
                const bool mine = own == slot && lim;
                if (!__any_sync(0xffffffffu, mine && (busy || n > lim - 2))) {
                    if (mine) { mbar_arrive(go); busy = true; par ^= 1; }
                    if (++slot == NSL) { slot = 0; first = false; }
                    it = 0;
                }
            }
            __trap();
        }
        {
            int w3 = warp;
            asm volatile("" : "+r"(w3));
            if (w3 == 3) return;
        }
        if (warp == 1) {
            const uint4* const qsrc = S->qpub + grp * 1024 + lane;
            uint2* const qdst = reinterpret_cast<uint2*>(sm + SA_Q) + lane;
            const unsigned epoch = ld_relaxed1(S->ctr + grp) / UPG;
            if (lane == 0) {
                mbar_init(sb + SA_QBAR, 32);
                mbar_init(sb + SA_QBAR + 8, 32);
                mbar_init(sb + SA_QBAR + 16, 32);
#pragma unroll
                for (int i = 0; i < 8; i++) { mbar_init(sb + SA_MBAR + i * 16, NW); mbar_init(sb + SA_MBAR + i * 16 + 8, 1); }
                mbar_init_fence();
                sts32(sb + SA_CNT, epoch);
            }
            __syncwarp();
            bar_arrive(1, (2 * NW + 2) * 32);
            __nanosleep(QSLEEP);
            for (int it = 0;; it++) {
                const uint4 u = ld_b128(qsrc);
                if (__all_sync(0xffffffffu, u.y == epoch + 1)) { qdst[0] = make_uint2(u.x, u.z); break; }
                if (it > SPIN_MAX) __trap();
            }
            mbar_arrive(sb + SA_QBAR);
#pragma unroll 1
            for (int h = 0, it = 0; h < 32; it++) {
                uint4 v[8];
                bool ok = true;
#pragma unroll
                for (int k = 0; k < 8; k++) v[k] = ld_b128(qsrc + (h + k) * 32);
#pragma unroll
                for (int k = 0; k < 8; k++) { ok = ok && v[k].y == epoch + 1; qdst[(h + k) * 32] = make_uint2(v[k].x, v[k].z); }
                if (__all_sync(0xffffffffu, ok)) {
                    if (!h) mbar_arrive(sb + SA_QBAR + 8);
                    h += 8;
                } else {
                    __nanosleep(QPOLL);
                }
                if (it > SPIN_MAX) __trap();
            }
            mbar_arrive(sb + SA_QBAR + 16);
            return;
        }
        bar_sync(1, (2 * NW + 2) * 32);
        if (warp == 2) {
            const uint32_t t8 = (lds32(sb + SA_CNT) + 1) & 0xffu;
            uint4* dst = S->apart + (grp * 32 * CPG + crk) * 32 + lane;
            uint2* dml = S->aml + (grp * 32 * CPG + crk) * 4 + (lane & 3);
#pragma unroll
            for (int k = 0; k < 4; k++) st_b64(dml + (k * 8 + (lane >> 2)) * (CPG * 4), 0, t8 ^ 0x80u);
            __syncwarp();
#pragma unroll 1
            for (int h = 0; h < 32; h++, dst += CPG * 32, dml += CPG * 4) {
                const float* s0 = reinterpret_cast<const float*>(sm + SA_SLOT) + (h & 7) * (NW * 132);
                mbar_wait(sb + SA_MBAR + (h & 7) * 16, (h >> 3) & 1);
                float2 ml[NW];
                float4 v[NW];
#pragma unroll
                for (int w = 0; w < NW; w++) {
                    ml[w] = *reinterpret_cast<const float2*>(s0 + w * 132 + 128);
                    v[w] = *reinterpret_cast<const float4*>(s0 + w * 132 + lane * 4);
                }
                const float MM = fmaxf(fmaxf(ml[0].x, ml[1].x), fmaxf(ml[2].x, ml[3].x));
                float e[NW];
#pragma unroll
                for (int w = 0; w < NW; w++) e[w] = ex2((ml[w].x - MM) * LOG2E);
                st_b128(dst, make_uint4(tagf(fmaf(e[0], v[0].x, e[1] * v[1].x) + fmaf(e[2], v[2].x, e[3] * v[3].x), t8),
                                        __float_as_uint(fmaf(e[0], v[0].y, e[1] * v[1].y) + fmaf(e[2], v[2].y, e[3] * v[3].y)),
                                        __float_as_uint(fmaf(e[0], v[0].z, e[1] * v[1].z) + fmaf(e[2], v[2].z, e[3] * v[3].z)),
                                        __float_as_uint(fmaf(e[0], v[0].w, e[1] * v[1].w) + fmaf(e[2], v[2].w, e[3] * v[3].w))));
                if (lane < 4) st_b64(dml, __float_as_uint(MM), tagf(fmaf(e[0], ml[0].y, e[1] * ml[1].y) + fmaf(e[2], ml[2].y, e[3] * ml[3].y), t8));
                if (h == 27 || h == 28) st_b128(dst + 3 * CPG * 32, make_uint4(t8 ^ 0x80u, 0, 0, 0));
                __syncwarp();
                if (lane == 0) mbar_arrive(sb + SA_MBAR + (h & 7) * 16 + 8);
            }
            return;
        }
        const int cw = warp - 4;
        uint32_t koff[4], voff[4];
#pragma unroll
        for (int i = 0; i < 4; i++) {
            koff[i] = ((lane & 7) + 8 * ((lane >> 3) & 1)) * 128 + (((2 * i + (lane >> 4)) ^ (lane & 7)) << 4);
            voff[i] = ((lane & 7) + 8 * (lane >> 4)) * 128 + (((2 * i + ((lane >> 3) & 1)) ^ (lane & 7)) << 4);
        }
        uint32_t psel[4][2];
#pragma unroll
        for (int i = 0; i < 4; i++) {
            psel[i][0] = (g >> 1) != i ? 0x4444u : (g & 1) ? 0x1044u : 0x4410u;
            psel[i][1] = (g >> 1) != i ? 0x4444u : (g & 1) ? 0x3244u : 0x4432u;
        }
        uint32_t qf[4][2];
        auto load_q = [&](int pl) {
            const uint32_t q = sb + SA_Q + pl * 256 + ((g & 1) * 32 + tq) * 4;
#pragma unroll
            for (int ks = 0; ks < 4; ks++) { qf[ks][0] = lds32(q + ks * 32); qf[ks][1] = lds32(q + ks * 32 + 16); }
        };
        mbar_wait(sb + SA_QBAR, 0);
        load_q(0);
        float acc[4][4], m = -FLT_MAX, l = 0.f, ls = 0.f;
#pragma unroll
        for (int i = 0; i < 4; i++) acc[i][0] = acc[i][1] = acc[i][2] = acc[i][3] = 0.f;
        int slot = cw, cur = 0;
        uint32_t ph = 0;
#pragma unroll 1
        for (;;) {
            mbar_wait(sb + SA_FULL + slot * 16, ph);
            const int pl = lds32(sb + SA_META + slot * 4);
            if (pl != cur) {
#pragma unroll 1
                do {
                    float* s0 = reinterpret_cast<float*>(sm + SA_SLOT) + ((cur & 7) * NW + cw) * 132;
                    float* sw = s0 + tq * 16 + (g >> 1) * 4 + (g & 1);
                    sw[0] = (acc[0][0] + acc[1][0]) + (acc[2][0] + acc[3][0]);
                    sw[2] = (acc[0][2] + acc[1][2]) + (acc[2][2] + acc[3][2]);
                    sw[64] = (acc[0][1] + acc[1][1]) + (acc[2][1] + acc[3][1]);
                    sw[66] = (acc[0][3] + acc[1][3]) + (acc[2][3] + acc[3][3]);
                    if (lane == 0) *reinterpret_cast<float2*>(s0 + 128) = make_float2(m, ls);
                    __syncwarp();
                    if (lane == 0) mbar_arrive(sb + SA_MBAR + (cur & 7) * 16);
                    if (++cur == 32) return;
#pragma unroll
                    for (int i = 0; i < 4; i++) acc[i][0] = acc[i][1] = acc[i][2] = acc[i][3] = 0.f;
                    m = -FLT_MAX; l = ls = 0.f;
                    mbar_wait(sb + SA_MBAR + (cur & 7) * 16 + 8, ((cur >> 3) & 1) ^ 1);
                    if (cur == 1 || cur == 8) mbar_wait(sb + SA_QBAR + 8 + (cur & 8), 0);
                } while (cur != pl);
                load_q(pl);
            }
            float s4[4][4];
            const uint32_t kb = sb + slot * 16384;
#pragma unroll
            for (int j = 0; j < 4; j++) {
                s4[j][0] = s4[j][1] = s4[j][2] = s4[j][3] = 0.f;
                const bool on = (g >> 1) == j;
#pragma unroll
                for (int ks = 0; ks < 4; ks++) {
                    uint32_t a[4];
                    ldsm4(a, kb + j * 2048 + koff[ks]);
                    mma16816(s4[j], a, on ? qf[ks][0] : 0u, on ? qf[ks][1] : 0u);
                }
            }
            float d[4];
#pragma unroll
            for (int r = 0; r < 4; r++) d[r] = (s4[0][r] + s4[1][r]) + (s4[2][r] + s4[3][r]);
            float sa = (g & 1) ? d[1] : d[0], sc = (g & 1) ? d[3] : d[2];
            sa += shx(sa, 4); sc += shx(sc, 4);
            uint32_t sp = packbf(sa, sc);
            sp = packbf(bflo(sp) * SCALE, bfhi(sp) * SCALE);
            sa = bflo(sp); sc = bfhi(sp);
            const float mx = warp_max(fmaxf(fmaxf(sa, sc), m));
            const float alpha = ex2((m - mx) * LOG2E);
            m = mx;
            const float pa = ex2((sa - mx) * LOG2E), pc = ex2((sc - mx) * LOG2E);
            const uint32_t pk = packbf(pa, pc);
            uint32_t pb[4][4][2];
#pragma unroll
            for (int j = 0; j < 4; j++) {
                const uint32_t pj = __shfl_sync(0xffffffffu, pk, 8 * tq + j);
#pragma unroll
                for (int i = 0; i < 4; i++) { pb[j][i][0] = prmt0(pj, psel[i][0]); pb[j][i][1] = prmt0(pj, psel[i][1]); }
            }
            l = fmaf(l, alpha, pa + pc);
            ls = l + shx(l, 8);
#pragma unroll
            for (int i = 0; i < 4; i++) { acc[i][0] *= alpha; acc[i][1] *= alpha; acc[i][2] *= alpha; acc[i][3] *= alpha; }
            mbar_wait(sb + SA_FULL + slot * 16 + 8, ph);
            const uint32_t vb = kb + 8192;
#pragma unroll
            for (int i = 0; i < 4; i++)
#pragma unroll
                for (int j = 0; j < 4; j++) {
                    uint32_t a[4];
                    ldsm4t(a, vb + j * 2048 + voff[i]);
                    mma16816(acc[j], a, pb[j][i][0], pb[j][i][1]);
                }
            ls += shx(ls, 16); ls += shx(ls, 1); ls += shx(ls, 2);
            __syncwarp();
            if (lane == 0) mbar_arrive(sb + SA_EMPTY + slot * 8);
            slot += NW;
            if (slot >= NSL) { slot -= NSL; ph ^= 1; }
        }
    }

    const int r = bx >> 2, isC = (bx >> 1) & 1;
    const int isA = (r >> 2) & 1, cb = (r >> 3) * 4 + (r & 3);
    const uint32_t bar_h = sb + SB_BAR + 32;
    if (warp == 8 && !isC) {
        const unsigned c0 = clk32();
        bar_sync(7, 64);
        while ((int)(clk32() - c0) < BSTART + (r & 7) * BSTAG) {}
        if (elect()) load_slice(sb + SB_STG, &M.qb, r, sb + SB_BAR + 16);
        __syncwarp();
    }
    if (warp < 8) {
        const uint32_t bar_q = bar_h + (NT + warp) * 8, box = sb + SB_QIMG + warp * 8192;
        if (elect()) {
            mbar_init(bar_q, 1);
            mbar_init_fence();
            mbar_expect(bar_q, 8192 + 256);
            tma2d_ef(box, &M.qa, (bx >> 1) * 64, warp * 64, bar_q);
        }
        __syncwarp();
        unsigned epoch = 0;
        if (warp < 2) epoch = ld_relaxed1(S->ctr) / UPG;
        uint4* const qdst = S->qpub + ((lane >> 4) * 32 + r) * 32 + isC * 16 + (lane & 15);
        if (warp == 0) st_b128(qdst, make_uint4(0, 0, 0, 0));
        if (elect()) {
            for (const unsigned c0 = clk32(); (int)(clk32() - c0) < XD0 + (bx >> 1) * XDS;) {}
            bulk_g2s(sb + SB_P + 4096 + warp * 288, P.ax + warp * 32, 128, bar_q);
            bulk_g2s(sb + SB_P + 4096 + warp * 288 + 144, P.ax + 256 + warp * 32, 128, bar_q);
        }
        if (tid == 32) {
#pragma unroll
            for (int i = 0; i < 4 + NT; i++) mbar_init(sb + SB_BAR + i * 8, 1);
            mbar_init_fence();
            sts32(sb + SB_CNT, epoch);
            sts32(sb + SB_CNT + 4, 0);
        }
        __syncwarp();
        if (warp == 1 && !isC) bar_arrive(7, 64);
        mbar_wait(bar_q, 0);
        uint32_t b[8];
#pragma unroll
        for (int i = 0; i < 8; i++) b[i] = lds32(sb + SB_P + 4096 + warp * 288 + (g & 1) * 144 + tq * 4 + i * 16);
        float d[4][4];
        uint32_t a[4][4][4];
#pragma unroll
        for (int i = 0; i < 4; i++) {
            d[i][0] = d[i][1] = d[i][2] = d[i][3] = 0.f;
#pragma unroll
            for (int ks = 0; ks < 4; ks++)
                ldsm4t(a[i][ks], box + ks * 2048 + ((lane & 7) + 8 * (lane >> 4)) * 128 + (((2 * i + ((lane >> 3) & 1)) ^ (lane & 7)) << 4));
        }
#pragma unroll
        for (int ks = 0; ks < 4; ks++)
#pragma unroll
            for (int i = 0; i < 4; i++) mma16816(d[i], a[i][ks], b[2 * ks], b[2 * ks + 1]);
        float* qred = reinterpret_cast<float*>(sm + SB_P);
#pragma unroll
        for (int c = 0; c < 4; c++)
            qred[warp * 128 + (c & 1) * 64 + tq * 16 + (c >> 1) * 8 + g] = tq == 0 ? d[0][c] : tq == 1 ? d[1][c] : tq == 2 ? d[2][c] : d[3][c];
        bar_sync(0, 256);
        if (warp == 0) {
            float4 v[8];
#pragma unroll
            for (int w = 0; w < 8; w++) v[w] = *reinterpret_cast<const float4*>(qred + w * 128 + lane * 4);
#pragma unroll
            for (int o = 4; o; o >>= 1)
#pragma unroll
                for (int w = 0; w < o; w++) { v[w].x += v[w + o].x; v[w].y += v[w + o].y; v[w].z += v[w + o].z; v[w].w += v[w + o].w; }
            st_b128(qdst, make_uint4(packbf(v[0].x, v[0].y), epoch + 1, packbf(v[0].z, v[0].w), epoch + 1));
        }
        if (!isC && tid < 4) st_b128(((tid & 2) ? S->bflag : S->qflag) + r * 8 + (tid & 1) * 4, make_uint4(0, 0, 0, 0));
        if (!isC && warp < 2) st_b128(S->frag[0] + (warp * 32 + r) * 32 + lane, make_uint4(0, 0, 0, 0));
        if (isC && !(warp & 3)) st_b128(S->frag[1] + ((warp >> 2) * 32 + (isA ? 0 : 16) + cb) * 32 + lane, make_uint4(0, 0, 0, 0));
        if (!isC) latent_branch(P, M, sm);
        bar_arrive(6, 288);
    }

    constexpr int ND = 2;
    const int nsnd = isA ? NSA : NSB, isCA = isC & isA;
    const int y0 = isC ? nsnd : 0, y1 = isC ? 32 - ND * isA : nsnd;
    const int nreq = isC ? 32 - nsnd : nsnd;
    const int nmw = isC && !isA ? NMW : 0;
    float* const red = reinterpret_cast<float*>(sm + SC_RED);
    const uint32_t wlane = wo_lane(sb, lane);
    auto fetch_frag = [&](int y, int b, unsigned tag, unsigned ns) {
        for (int it = 0;; it++) {
            const uint4 v = ld_b128(S->frag[0] + isA * 2048 + (b * 32 + y) * 32 + lane);
            if (__all_sync(0xffffffffu, v.y == tag)) {
                reinterpret_cast<uint2*>(sm + SC_FR)[(y * 32 + (g >> 1) * 8 + b * 4 + tq) * 2 + (g & 1)] = make_uint2(v.x, v.z);
                return;
            }
            if (it > SPIN_MAX) __trap();
            __nanosleep(ns);
        }
    };
    if (warp < 8) {
        const unsigned tag = lds32(sb + SB_CNT) + 1;
        const uint32_t t8 = tag & 0xffu;
        uint32_t bs[2], wf[4][4];
        float d[2][4];
        const uint32_t wa = (wlane ^ ((warp & 1) * 32)) + (warp & 2) * 2048;
        const int ks0 = (warp & 2) * 2;
        if (isC) __nanosleep(4000);
#pragma unroll 1
        for (int op = isCA ? 0 : 1;; op++) {
            const int step = isCA ? max(op - 1, 0) : 0, h = step ? 31 - ND + step : isA ? cb : 16 + cb;
            if (op != 1) {
                if (!isCA && (!isC || h >= 32 - ND)) break;
                const int rec = ((warp >> 2) * 32 + h) * CPG + (warp & 3) * 8;
                const uint2* mlp = S->aml + (rec + (lane & 7)) * 4;
                const uint4* src = S->apart + rec * 32 + lane;
                asm volatile("" : "+l"(mlp), "+l"(src));
                if (!step) {
                    for (int it = 0; !__all_sync(0xffffffffu, (ld_b64(mlp).y & 0xffu) == t8); it++) {
                        if (it > SPIN_MAX) __trap();
                        __nanosleep(h > 25 ? DPOLL : CPOLL);
                    }
                } else if (step < ND) {
                    mbar_wait(sb + SB_BAR + 8, 0);
                } else {
                    d[0][0] = d[0][1] = d[0][2] = d[0][3] = d[1][0] = d[1][1] = d[1][2] = d[1][3] = 0.f;
#pragma unroll
                    for (int k = 0; k < ND; k++) {
                        mbar_wait(bar_h + k * 16 + (warp & 2) * 4, 0);
#pragma unroll
                        for (int ks = 0; ks < 4; ks++) ldsm4t(wf[ks], wa + k * 8192 + ks * 1024);
                        if (k < ND - 1) {
#pragma unroll
                            for (int ks = 0; ks < 4; ks++) mma16816(d[ks & 1], wf[ks], g == ks0 + ks ? bs[0] : 0u, g == ks0 + ks ? bs[1] : 0u);
                        }
                    }
                    mbar_wait(sb + SB_BAR, 0);
                }
                uint4 v[8];
                uint2 ml = ld_b64(mlp);
#pragma unroll
                for (int i = 0; i < 8; i++) v[i] = ld_b128(src + i * 32);
                for (int it = 0;; it++) {
                    unsigned x = ml.y ^ t8;
#pragma unroll
                    for (int i = 0; i < 8; i++) x |= v[i].x ^ t8;
                    if (!__any_sync(0xffffffffu, x & 0xffu)) break;
                    if (it > SPIN_MAX) __trap();
                    ml = ld_b64(mlp);
#pragma unroll
                    for (int i = 0; i < 8; i++)
                        if ((v[i].x & 0xffu) != t8) v[i] = ld_b128(src + i * 32);
                }
                const float mw = warp_max(__uint_as_float(ml.x)), e = ex2((__uint_as_float(ml.x) - mw) * LOG2E);
                float L = e * __uint_as_float(ml.y), oa[4], ob[4];
                L += shx(L, 1);
#pragma unroll
                for (int i = 0; i < 8; i++) {
                    const float w = __shfl_sync(0xffffffffu, e, i);
                    float (&o)[4] = (i & 1) ? ob : oa;
                    o[0] = i < 2 ? w * __uint_as_float(v[i].x) : fmaf(w, __uint_as_float(v[i].x), o[0]);
                    o[1] = i < 2 ? w * __uint_as_float(v[i].y) : fmaf(w, __uint_as_float(v[i].y), o[1]);
                    o[2] = i < 2 ? w * __uint_as_float(v[i].z) : fmaf(w, __uint_as_float(v[i].z), o[2]);
                    o[3] = i < 2 ? w * __uint_as_float(v[i].w) : fmaf(w, __uint_as_float(v[i].w), o[3]);
                }
                float* fp = reinterpret_cast<float*>(sm + SC_FP) + ((step & 1) * 8 + (warp & 4)) * 132;
                *reinterpret_cast<float4*>(fp + (warp & 3) * 132 + lane * 4) = make_float4(oa[0] + ob[0], oa[1] + ob[1], oa[2] + ob[2], oa[3] + ob[3]);
                L += shx(L, 2);
                L += shx(L, 4);
                if (lane == 0) *reinterpret_cast<float2*>(fp + (warp & 3) * 132 + 128) = make_float2(mw, L);
                bar_sync(1 + (warp >> 2), 128);
                float2 q[4];
                float4 u[4];
#pragma unroll
                for (int w = 0; w < 4; w++) {
                    q[w] = *reinterpret_cast<const float2*>(fp + w * 132 + 128);
                    u[w] = *reinterpret_cast<const float4*>(fp + w * 132 + lane * 4);
                }
                const float MM = fmaxf(fmaxf(q[0].x, q[1].x), fmaxf(q[2].x, q[3].x));
                float f[4], inv;
#pragma unroll
                for (int w = 0; w < 4; w++) f[w] = ex2((q[w].x - MM) * LOG2E);
                asm("rcp.approx.ftz.f32 %0, %1;" : "=f"(inv) : "f"(fmaf(f[0], q[0].y, f[1] * q[1].y) + fmaf(f[2], q[2].y, f[3] * q[3].y)));
                const uint32_t b0 = packbf((fmaf(f[0], u[0].x, f[1] * u[1].x) + fmaf(f[2], u[2].x, f[3] * u[3].x)) * inv,
                                           (fmaf(f[0], u[0].y, f[1] * u[1].y) + fmaf(f[2], u[2].y, f[3] * u[3].y)) * inv);
                const uint32_t b1 = packbf((fmaf(f[0], u[0].z, f[1] * u[1].z) + fmaf(f[2], u[2].z, f[3] * u[3].z)) * inv,
                                           (fmaf(f[0], u[0].w, f[1] * u[1].w) + fmaf(f[2], u[2].w, f[3] * u[3].w)) * inv);
                if (step == ND) {
#pragma unroll
                    for (int ks = 0; ks < 4; ks++) mma16816(d[ks & 1], wf[ks], g == ks0 + ks ? b0 : 0u, g == ks0 + ks ? b1 : 0u);
                    const float x0 = (d[0][0] + d[0][1]) + (d[1][0] + d[1][1]), x1 = (d[0][2] + d[0][3]) + (d[1][2] + d[1][3]);
                    const float z = ((tq & 1) ? x1 : x0) + shx((tq & 1) ? x0 : x1, 1);
                    if ((tq & 2) == (warp & 2)) red[(6 + (tq >> 1)) * 80 + (warp >> 2) * 40 + (warp & 1) * 16 + (tq & 1) * 8 + g] = z;
                    bar_arrive(5, 480);
                    return;
                }
                bs[0] = b0; bs[1] = b1;
                if (!step && !(warp & 3)) st_b128(S->frag[1] + ((warp >> 2) * 32 + h) * 32 + lane, make_uint4(b0, tag, b1, 0));
                if (!isCA) break;
            } else {
#pragma unroll 1
                for (int y = y0 + ((warp - y0) & 3); y < y1 - 3 * isCA; y += 4) fetch_frag(y, warp >> 2, tag, CPOLL);
                if (warp >= nmw) bar_arrive(4, 448);
            }
        }
        if (warp >= nmw) return;
    }
    if (warp == 14) {
        bar_sync(6, 288);
        const CUtensorMap* map = &M.wo[isA];
        const unsigned tag = lds32(sb + SB_CNT) + 1;
        const uint32_t t8 = tag & 0xffu;
        uint2* const snd = S->snd + r * 32 + lane;
        asm volatile("prefetch.tensormap [%0];" ::"l"(map) : "memory");
        if (!isC) st_b64(snd, t8 ^ 0x80u, 0);
        for (int it = 0;; it++) {
            __nanosleep(2000);
            if (it > 1 && ld_b128(S->frag[1] + 25 * 32).y == tag) break;
            if (it > SPIN_MAX) __trap();
        }
        uint2 f;
        for (int it = 0;; it++) {
            f = ld_b64(S->fire + (lane & 1));
            if (__all_sync(0xffffffffu, f.y == tag)) break;
            if (it > SPIN_MAX) __trap();
            __nanosleep(FPOLL);
        }
        const unsigned t0 = __shfl_sync(0xffffffffu, f.x, 0);
        unsigned t1 = t0 + (__reduce_add_sync(0xffffffffu, (int)(f.x - t0)) >> 5) + FIRE_NS;
        if (elect()) {
            const int n1 = nreq - (isC ? (isA ? NLA : NLB) : 0);
            const int dt = !isC ? (isA ? FIRE_W / NSA : FIRE_W / NSB) : isA ? FIRE_W / (32 - NSA - NLA) : FIRE_W / (32 - NSB - NLB);
            unsigned t2 = t1 + REC0_NS;
            int rec = isCA ? 2 : 0;
            int y = isCA ? 32 - ND : y0;
#pragma unroll 1
            for (int i = 0; i < nreq; i++) {
                const int row = y * 128;
                mbar_expect(bar_h + i * 16, 4096);
                mbar_expect(bar_h + i * 16 + 8, 4096);
                if (++y == 32) y = y0;
                if (i <= n1) {
                    unsigned t;
                    for (int it = 0; (int)((t = gt()) - t1) < 0 && it < 4096; it++) {}
                    t1 += dt;
                    if (rec && (int)(t - t2) >= 0) { mbar_arrive(sb + SB_BAR + --rec * 8); t2 += REC_NS - REC0_NS; }
                }
                tma2d(sb + i * 8192, map, cb * 32, row, bar_h + i * 16);
                tma2d(sb + i * 8192 + 4096, map, cb * 32, row + 64, bar_h + i * 16 + 8);
            }
            while (rec) {
                for (int it = 0; (int)(gt() - t2) < 0 && it < 4096; it++) {}
                mbar_arrive(sb + SB_BAR + --rec * 8);
                t2 += REC_NS - REC0_NS;
            }
        }
        __syncwarp();
        uint32_t* dst = reinterpret_cast<uint32_t*>(P.out) + (lane >> 4) * 512 + (isA ? 0 : 256) + cb * 16 + (lane & 15);
        uint32_t q = sb + SC_RED + ((lane >> 4) * 20 + (lane & 15)) * 8;
        asm volatile("" : "+l"(dst), "+r"(q));
        if (!isC) {
            const float2 s = sum_parts<6, 224>(q, 0.f, 0.f);
            st_b64(snd, tagf(s.x, t8), __float_as_uint(s.y));
        } else {
            uint2 o;
            for (int it = 0;; it++) {
                o = ld_b64(snd);
                if (__all_sync(0xffffffffu, (o.x & 0xffu) == t8)) break;
                if (it > SPIN_MAX) __trap();
            }
            if (isA) {
                const float2 s = sum_parts<8, 480>(q, __uint_as_float(o.x), __uint_as_float(o.y));
                asm volatile("st.global.u32 [%0], %1;" ::"l"(dst), "r"(packbf(s.x, s.y)) : "memory");
            } else {
                const float2 s = sum_parts<6 + NMW, 224 + 32 * NMW>(q, __uint_as_float(o.x), __uint_as_float(o.y));
                asm volatile("st.global.b32 [%0], %1;" ::"l"(dst), "r"(packbf(s.x, s.y)) : "memory");
            }
        }
        return;
    }
    {
        const int nw = 6 + nmw, wi = warp < 8 ? warp + 6 : warp - 8, t0 = wi + 2 * ND * isCA;
        bar_sync(4, 448);
        if (isCA) {
            const int y = y0 - ND + ((2 * nreq - 1 - (2 * nreq - 1 - t0) % 6) >> 1);
            const unsigned tag = lds32(sb + SB_CNT) + 1;
#pragma unroll 1
            for (int b = 0; b < 2; b++) fetch_frag(y, b, tag, DPOLL);
            __syncwarp();
        }
        uint32_t rx = sb + SC_RED + (wi * 80 + (tq & 1) * 40 + (tq >> 1) * 16 + g) * 4, nb = isCA ? 480 : 224 + nmw * 32;
        asm volatile("" : "+r"(rx), "+r"(nb));
        float e[4][4];
#pragma unroll
        for (int i = 0; i < 4; i++) e[i][0] = e[i][1] = e[i][2] = e[i][3] = 0.f;
        uint32_t bp = sb + SC_FR + ((2 * (y0 - ND * isCA) + t0) * 16 + (lane & 7)) * 16, wa = wlane + t0 * 4096, bar = bar_h + t0 * 8;
        uint4 b0 = lds128(bp), b1 = lds128(bp + 128);
        const uint32_t zero = lds32(sb + SB_CNT + 4);
#pragma unroll 1
        for (int t = t0;;) {
            uint32_t a[8][4];
            b0.x ^= zero; b1.x ^= zero;
            asm volatile("" : "+r"(b0.x), "+r"(b1.x));
            mbar_wait(bar, 0);
#pragma unroll
            for (int j = 0; j < 8; j++) ldsm4t(a[j], (wa ^ ((j & 1) * 32)) + (j >> 1) * 1024);
            bp += nw * 256;
            const uint4 n0 = lds128(bp), n1 = lds128(bp + 128);
#pragma unroll
            for (int j = 0; j < 8; j++) {
                const uint4& c = (j & 4) ? b1 : b0;
                mma16816(e[(j & 1) * 2 + ((j >> 1) & 1)], a[j], (j & 2) ? c.z : c.x, (j & 2) ? c.w : c.y);
            }
            t += nw;
            if (t >= 2 * nreq) break;
            wa += nw * 4096; bar += nw * 8;
            b0 = n0; b1 = n1;
        }
        float s4[4];
#pragma unroll
        for (int c = 0; c < 4; c++) s4[c] = (tq & 2) ? e[2][c] + e[3][c] : e[0][c] + e[1][c];
        sts32(rx, __float_as_uint((tq & 1) ? s4[1] : s4[0]));
        sts32(rx + 32, __float_as_uint((tq & 1) ? s4[3] : s4[2]));
        bar_arrive(5, nb);
    }
}

typedef CUresult (*EncodeFn)(CUtensorMap*, CUtensorMapDataType, cuuint32_t, void*, const cuuint64_t*, const cuuint64_t*,
                             const cuuint32_t*, const cuuint32_t*, CUtensorMapInterleave, CUtensorMapSwizzle,
                             CUtensorMapL2promotion, CUtensorMapFloatOOBfill);

void make_map(EncodeFn enc, CUtensorMap* m, const void* base, uint64_t cols, uint64_t rows, uint32_t bc, uint32_t br,
              CUtensorMapL2promotion promo, CUtensorMapSwizzle sw = CU_TENSOR_MAP_SWIZZLE_128B) {
    cuuint64_t dims[2] = {cols, rows};
    cuuint64_t strides[1] = {cols * 2};
    cuuint32_t box[2] = {bc, br};
    cuuint32_t es[2] = {1, 1};
    enc(m, CU_TENSOR_MAP_DATA_TYPE_BFLOAT16, 2, const_cast<void*>(base), dims, strides, box, es,
        CU_TENSOR_MAP_INTERLEAVE_NONE, sw, promo, CU_TENSOR_MAP_FLOAT_OOB_FILL_NONE);
}

}

extern "C" void kernel_launch(void* const* d_in, const int* in_sizes, int n_in, void* d_out, int out_size) {
    (void)in_sizes; (void)n_in; (void)out_size;
    static EncodeFn enc = nullptr;
    static void* scr = nullptr;
    if (!enc) {
        void* fn = nullptr;
        cudaDriverEntryPointQueryResult qr;
        cudaGetDriverEntryPoint("cuTensorMapEncodeTiled", &fn, cudaEnableDefault, &qr);
        enc = (EncodeFn)fn;
        cudaGetSymbolAddress(&scr, g_scr);
        cudaFuncSetAttribute(fused_decode_kernel, cudaFuncAttributeMaxDynamicSharedMemorySize, SMEM_BYTES);
    }
    Maps m;
    make_map(enc, &m.kv[0], d_in[1], 64, 1048576, 64, 64, CU_TENSOR_MAP_L2_PROMOTION_NONE);
    make_map(enc, &m.kv[1], d_in[2], 64, 1048576, 64, 64, CU_TENSOR_MAP_L2_PROMOTION_NONE);
    make_map(enc, &m.qa, d_in[3], 4096, 512, 64, 64, CU_TENSOR_MAP_L2_PROMOTION_NONE);
    make_map(enc, &m.qb, d_in[7], 4096, 512, 64, 256, CU_TENSOR_MAP_L2_PROMOTION_NONE);
    make_map(enc, &m.wo[0], d_in[10], 512, 4096, 32, 64, CU_TENSOR_MAP_L2_PROMOTION_L2_128B, CU_TENSOR_MAP_SWIZZLE_64B);
    make_map(enc, &m.wo[1], d_in[4], 512, 4096, 32, 64, CU_TENSOR_MAP_L2_PROMOTION_L2_128B, CU_TENSOR_MAP_SWIZZLE_64B);
    {
        cuuint64_t dims[4] = {64, 8, 8, 2048}, strides[3] = {1024, 128, 8192};
        cuuint32_t box[4] = {64, 8, 8, 8}, es[4] = {1, 1, 1, 1};
        enc(&m.c, CU_TENSOR_MAP_DATA_TYPE_BFLOAT16, 4, d_in[6], dims, strides, box, es, CU_TENSOR_MAP_INTERLEAVE_NONE,
            CU_TENSOR_MAP_SWIZZLE_128B, CU_TENSOR_MAP_L2_PROMOTION_NONE, CU_TENSOR_MAP_FLOAT_OOB_FILL_NONE);
    }
    make_map(enc, &m.uk, d_in[8], 4096, 512, 64, 256, CU_TENSOR_MAP_L2_PROMOTION_NONE);
    make_map(enc, &m.uv, d_in[9], 4096, 512, 64, 256, CU_TENSOR_MAP_L2_PROMOTION_NONE);
    Params p;
    p.scr = (Scratch*)scr;
    p.ax = (const uint32_t*)d_in[0];
    p.bx = (const uint32_t*)d_in[5];
    p.out = (__nv_bfloat16*)d_out;
    p.wq = (const char*)d_in[3];
    fused_decode_kernel<<<128, 480, SMEM_BYTES, cudaStreamPerThread>>>(p, m);
}
```

```cpp
#include <cuda_runtime.h>
#include <cuda_bf16.h>
#include <cuda.h>
#include <stdint.h>
#include <float.h>

#define LIM 12
#define LIM0 8
#define RAMP_S 256
#define RAMP_T0 300
#define SKEW 3
#define XD0 1000
#define XDS 12
#define BSTART 3000
#define BSTAG 500
#define FIRE_T 240
#define FIRE_NS 3300
#define FIRE_W 1950
#define NLA 6
#define NLB 10
#define NSA 13
#define NSB 13
#define REC0_NS 100
#define REC_NS 1700
#define NMW 6
#define QSLEEP 1200
#define QPOLL 300
#define BPOLL 1000
#define CPOLL 700
#define DPOLL 300
#define FPOLL 300

namespace {

constexpr int CPG = 32, NW = 4;
constexpr int UPG = 8192;
constexpr int NSL = 12, SPW = NSL / NW;
constexpr int SPIN_MAX = 1 << 22;
constexpr float LOG2E = 1.4426950408889634f;
constexpr float SCALE = 0.08838834764831845f;
constexpr uint64_t EVICT_FIRST = 0x12F0000000000000ull;

constexpr int SA_SLOT = NSL * 16384;
constexpr int SA_Q    = SA_SLOT + 8 * NW * 132 * 4;
constexpr int SA_FULL = SA_Q + 8192;
constexpr int SA_EMPTY = SA_FULL + NSL * 16;
constexpr int SA_GOV  = SA_EMPTY + NSL * 8;
constexpr int SA_MBAR = SA_GOV + NSL * 8;
constexpr int SA_QBAR = SA_MBAR + 128;
constexpr int SA_META = SA_QBAR + 24;
constexpr int SA_LIM  = SA_META + NSL * 4;
constexpr int SA_CNT  = SA_LIM + 16;
constexpr int SA_END  = SA_CNT + 64;
constexpr int PROW    = 2080;
constexpr int SB_STG  = 0;
constexpr int SB_QIMG = 131072;
constexpr int SB_P    = SB_QIMG + 32 * PROW;
constexpr int SB_AL   = SB_P + 8192;
constexpr int SB_X    = SB_AL + 256;
static_assert(SB_P % 1024 == 0, "swizzle atom");
constexpr int SB_QB   = SB_X + 4352;
constexpr int NT      = 40;
constexpr int SC_FR   = NT * 4096;
constexpr int SC_FP   = SC_FR + 16384;
constexpr int SC_RED  = SB_QB + 1024;
constexpr int SB_BAR  = SC_RED + 4480;
constexpr int SB_CNT  = SB_BAR + (12 + NT) * 8;
static_assert(SC_FP + 8448 <= SB_P && 2 * (32 - NSA) <= NT && 2 * (32 - NSB) <= NT && NSA <= 16 && NSB <= 16, "projection slots");
constexpr int SB_END  = SB_CNT + 64;
constexpr int SMEM_BYTES = (SA_END > SB_END ? SA_END : SB_END);
static_assert(SMEM_BYTES <= 232448, "shared memory");

struct Scratch {
    uint4    bpart[32 * 32 * (PROW / 16)];
    uint4    apart[64 * CPG * 32];
    uint4    qimg[2 * 4096];
    uint4    qpub[64 * 32];
    uint4    frag[2][64 * 32];
    uint2    snd[32 * 32];
    uint2    aml[64 * CPG * 4];
    unsigned ctr[2][1056];
    uint2    fire[544];
    unsigned qflag[1088], bflag[1088];
};
__device__ __align__(1024) Scratch g_scr;

__device__ __forceinline__ uint32_t s2u(const void* p) { return (uint32_t)__cvta_generic_to_shared(p); }
__device__ __forceinline__ bool elect() {
    uint32_t ok;
    asm volatile("{\n.reg .pred p;\nelect.sync _|p, 0xffffffff;\nselp.u32 %0,1,0,p;\n}" : "=r"(ok));
    return ok;
}
__device__ __forceinline__ void mbar_init(uint32_t b, int c) {
    asm volatile("mbarrier.init.shared::cta.b64 [%0], %1;" ::"r"(b), "r"(c) : "memory");
}
__device__ __forceinline__ void mbar_init_fence() { asm volatile("fence.mbarrier_init.release.cluster;" ::: "memory"); }
__device__ __forceinline__ void mbar_expect(uint32_t b, uint32_t bytes) {
    asm volatile("mbarrier.arrive.expect_tx.shared::cta.b64 _, [%0], %1;" ::"r"(b), "r"(bytes) : "memory");
}
__device__ __forceinline__ void mbar_arrive(uint32_t b) {
    asm volatile("mbarrier.arrive.shared::cta.b64 _, [%0];" ::"r"(b) : "memory");
}
__device__ __forceinline__ bool mbar_test(uint32_t b, uint32_t ph) {
    uint32_t ok;
    asm volatile("{\n.reg .pred p;\nmbarrier.test_wait.parity.shared::cta.b64 p, [%1], %2;\nselp.u32 %0,1,0,p;\n}"
                 : "=r"(ok) : "r"(b), "r"(ph) : "memory");
    return ok;
}
__device__ __forceinline__ void mbar_wait(uint32_t b, uint32_t ph) {
    asm volatile("{\n.reg .pred p;\n.reg .u32 n;\nmov.u32 n, 0;\n"
                 "W: mbarrier.try_wait.parity.shared::cta.b64 p, [%0], %1;\n@p bra.uni D;\n"
                 "add.u32 n, n, 1;\nsetp.lt.u32 p, n, %2;\n@p bra.uni W;\ntrap;\nD:\n}"
                 ::"r"(b), "r"(ph), "n"(SPIN_MAX) : "memory");
}
__device__ __forceinline__ void tma2d(uint32_t dst, const CUtensorMap* map, int c0, int c1, uint32_t bar) {
    asm volatile("cp.async.bulk.tensor.2d.shared::cluster.global.mbarrier::complete_tx::bytes [%0], [%1, {%3, %4}], [%2];"
                 ::"r"(dst), "l"(map), "r"(bar), "r"(c0), "r"(c1) : "memory");
}
__device__ __forceinline__ void tma2d_ef(uint32_t dst, const CUtensorMap* map, int c0, int c1, uint32_t bar) {
    asm volatile("cp.async.bulk.tensor.2d.shared::cluster.global.mbarrier::complete_tx::bytes.L2::cache_hint [%0], [%1, {%3, %4}], [%2], %5;"
                 ::"r"(dst), "l"(map), "r"(bar), "r"(c0), "r"(c1), "l"(EVICT_FIRST) : "memory");
}
__device__ __forceinline__ void tma4d_ef(uint32_t dst, const CUtensorMap* map, int c3, uint32_t bar) {
    asm volatile("cp.async.bulk.tensor.4d.shared::cluster.global.mbarrier::complete_tx::bytes.L2::cache_hint [%0], [%1, {0, 0, 0, %3}], [%2], %4;"
                 ::"r"(dst), "l"(map), "r"(bar), "r"(c3), "l"(EVICT_FIRST) : "memory");
}
__device__ __forceinline__ void bulk_g2s(uint32_t dst, const void* src, uint32_t bytes, uint32_t bar) {
    asm volatile("cp.async.bulk.shared::cluster.global.mbarrier::complete_tx::bytes [%0], [%1], %2, [%3];"
                 ::"r"(dst), "l"(src), "r"(bytes), "r"(bar) : "memory");
}
__device__ __forceinline__ void bulk_s2g(void* dst, uint32_t src, uint32_t bytes) {
    asm volatile("cp.async.bulk.global.shared::cta.bulk_group [%0], [%1], %2;" ::"l"(dst), "r"(src), "r"(bytes) : "memory");
}
__device__ __forceinline__ void fence_async_all() { asm volatile("fence.proxy.async;" ::: "memory"); }
__device__ __forceinline__ void bar_sync(int id, int n) { asm volatile("bar.sync %0, %1;" ::"r"(id), "r"(n) : "memory"); }
__device__ __forceinline__ void bar_arrive(int id, int n) { asm volatile("bar.arrive %0, %1;" ::"r"(id), "r"(n) : "memory"); }
__device__ __forceinline__ unsigned ld_relaxed1(const void* p) {
    unsigned v;
    asm volatile("ld.relaxed.gpu.global.u32 %0, [%1];" : "=r"(v) : "l"(p) : "memory");
    return v;
}
__device__ __forceinline__ unsigned atom_inc(unsigned* p) {
    unsigned v;
    asm volatile("atom.relaxed.gpu.global.add.u32 %0, [%1], 1;" : "=r"(v) : "l"(p) : "memory");
    return v;
}
__device__ __forceinline__ uint4 ld_b128(const void* p) {
    uint4 v;
    asm volatile("{\n.reg .b128 t;\nld.relaxed.gpu.global.b128 t, [%4];\nmov.b128 {%0,%1,%2,%3}, t;\n}"
                 : "=r"(v.x), "=r"(v.y), "=r"(v.z), "=r"(v.w) : "l"(p) : "memory");
    return v;
}
__device__ __forceinline__ void st_b128(void* p, uint4 v) {
    asm volatile("{\n.reg .b128 t;\nmov.b128 t, {%1,%2,%3,%4};\nst.relaxed.gpu.global.b128 [%0], t;\n}"
                 ::"l"(p), "r"(v.x), "r"(v.y), "r"(v.z), "r"(v.w) : "memory");
}
__device__ __forceinline__ uint2 ld_b64(const void* p) {
    uint2 v;
    asm volatile("{\n.reg .b64 a;\nld.relaxed.gpu.global.b64 a, [%2];\nmov.b64 {%0,%1}, a;\n}" : "=r"(v.x), "=r"(v.y) : "l"(p) : "memory");
    return v;
}
__device__ __forceinline__ void st_b64(void* p, uint32_t a, uint32_t b) {
    asm volatile("{\n.reg .b64 t;\nmov.b64 t, {%1,%2};\nst.relaxed.gpu.global.b64 [%0], t;\n}" ::"l"(p), "r"(a), "r"(b) : "memory");
}
__device__ __forceinline__ unsigned ld_acquire(const unsigned* p) {
    unsigned v;
    asm volatile("ld.acquire.gpu.global.u32 %0, [%1];" : "=r"(v) : "l"(p) : "memory");
    return v;
}
__device__ __forceinline__ void st_release(unsigned* p, unsigned v) {
    asm volatile("st.release.gpu.global.u32 [%0], %1;" ::"l"(p), "r"(v) : "memory");
}
__device__ __forceinline__ void ldsm4(uint32_t (&r)[4], uint32_t a) {
    asm volatile("ldmatrix.sync.aligned.m8n8.x4.shared.b16 {%0,%1,%2,%3}, [%4];"
                 : "=r"(r[0]), "=r"(r[1]), "=r"(r[2]), "=r"(r[3]) : "r"(a) : "memory");
}
__device__ __forceinline__ void ldsm4t(uint32_t (&r)[4], uint32_t a) {
    asm volatile("ldmatrix.sync.aligned.m8n8.x4.trans.shared.b16 {%0,%1,%2,%3}, [%4];"
                 : "=r"(r[0]), "=r"(r[1]), "=r"(r[2]), "=r"(r[3]) : "r"(a) : "memory");
}
__device__ __forceinline__ uint4 lds128(uint32_t a) {
    uint4 v;
    asm volatile("ld.shared.v4.u32 {%0, %1, %2, %3}, [%4];" : "=r"(v.x), "=r"(v.y), "=r"(v.z), "=r"(v.w) : "r"(a) : "memory");
    return v;
}
__device__ __forceinline__ float2 lds64f(uint32_t a) {
    float2 v;
    asm volatile("ld.shared.v2.f32 {%0, %1}, [%2];" : "=f"(v.x), "=f"(v.y) : "r"(a) : "memory");
    return v;
}
__device__ __forceinline__ uint32_t lds32(uint32_t a) {
    uint32_t v;
    asm volatile("ld.shared.u32 %0, [%1];" : "=r"(v) : "r"(a) : "memory");
    return v;
}
__device__ __forceinline__ void sts32(uint32_t a, uint32_t v) { asm volatile("st.shared.u32 [%0], %1;" ::"r"(a), "r"(v) : "memory"); }
__device__ __forceinline__ void mma16816(float (&d)[4], const uint32_t (&a)[4], uint32_t b0, uint32_t b1) {
    asm volatile("mma.sync.aligned.m16n8k16.row.col.f32.bf16.bf16.f32 {%0,%1,%2,%3}, {%4,%5,%6,%7}, {%8,%9}, {%0,%1,%2,%3};"
                 : "+f"(d[0]), "+f"(d[1]), "+f"(d[2]), "+f"(d[3])
                 : "r"(a[0]), "r"(a[1]), "r"(a[2]), "r"(a[3]), "r"(b0), "r"(b1));
}
__device__ __forceinline__ uint32_t prmt0(uint32_t a, uint32_t sel) {
    uint32_t d;
    asm volatile("prmt.b32 %0, %1, 0, %2;" : "=r"(d) : "r"(a), "r"(sel));
    return d;
}
__device__ __forceinline__ unsigned gt() {
    unsigned t;
    asm volatile("mov.u32 %0, %globaltimer_lo;" : "=r"(t));
    return t;
}
__device__ __forceinline__ unsigned clk32() {
    unsigned c;
    asm volatile("mov.u32 %0, %clock;" : "=r"(c));
    return c;
}
__device__ __forceinline__ float ex2(float x) {
    float y;
    asm("ex2.approx.ftz.f32 %0, %1;" : "=f"(y) : "f"(x));
    return y;
}
__device__ __forceinline__ float bf16r(float x) { return __bfloat162float(__float2bfloat16_rn(x)); }
__device__ __forceinline__ uint32_t packbf(float lo, float hi) {
    uint32_t r;
    asm("cvt.rn.bf16x2.f32 %0, %1, %2;" : "=r"(r) : "f"(hi), "f"(lo));
    return r;
}
__device__ __forceinline__ float bflo(uint32_t v) { return __uint_as_float(v << 16); }
__device__ __forceinline__ float bfhi(uint32_t v) { return __uint_as_float(v & 0xffff0000u); }
__device__ __forceinline__ uint32_t tagf(float v, uint32_t t8) { return (__float_as_uint(v) & 0xffffff00u) | t8; }
__device__ __forceinline__ float shx(float v, int m) { return __shfl_xor_sync(0xffffffffu, v, m); }

__device__ __forceinline__ float warp_max(float v) {
    int i = __float_as_int(v);
    i = __reduce_max_sync(0xffffffffu, i ^ ((i >> 31) & 0x7fffffff));
    return __int_as_float(i ^ ((i >> 31) & 0x7fffffff));
}

__device__ __forceinline__ uint64_t gdesc(uint32_t addr, uint32_t lbo, uint32_t sbo) {
    return (uint64_t)((addr & 0x3ffff) >> 4) | ((uint64_t)(lbo >> 4) << 16) | ((uint64_t)(sbo >> 4) << 32) | (1ull << 62);
}
__device__ __forceinline__ void wg_fence() { asm volatile("wgmma.fence.sync.aligned;" ::: "memory"); }
__device__ __forceinline__ void wg_commit() { asm volatile("wgmma.commit_group.sync.aligned;" ::: "memory"); }
__device__ __forceinline__ void wg_wait0() { asm volatile("wgmma.wait_group.sync.aligned 0;" ::: "memory"); }
template <int N> __device__ __forceinline__ void reg_fence(float (&r)[N]) {
#pragma unroll
    for (int i = 0; i < N; i++) asm volatile("" : "+f"(r[i])::"memory");
}
#define F8(a, o) "+f"(a[o]), "+f"(a[o + 1]), "+f"(a[o + 2]), "+f"(a[o + 3]), "+f"(a[o + 4]), "+f"(a[o + 5]), "+f"(a[o + 6]), "+f"(a[o + 7])
#define F32(a, o) F8(a, o), F8(a, o + 8), F8(a, o + 16), F8(a, o + 24)
__device__ __forceinline__ void wgmma_n64_ss(float (&d)[32], uint64_t da, uint64_t db, int scale_d) {
    asm volatile(
        "{\n.reg .pred p;\nsetp.ne.b32 p, %34, 0;\n"
        "wgmma.mma_async.sync.aligned.m64n64k16.f32.bf16.bf16 "
        "{%0,%1,%2,%3,%4,%5,%6,%7,%8,%9,%10,%11,%12,%13,%14,%15,%16,%17,%18,%19,%20,%21,%22,%23,%24,%25,%26,%27,%28,%29,%30,%31},"
        " %32, %33, p, 1, 1, 0, 0;\n}"
        : F32(d, 0) : "l"(da), "l"(db), "r"(scale_d));
}
__device__ __forceinline__ void wgmma_n32_ts(float (&d)[16], uint64_t da, uint64_t db) {
    asm volatile(
        "{\n.reg .pred p;\nsetp.ne.b32 p, 1, 0;\n"
        "wgmma.mma_async.sync.aligned.m64n32k16.f32.bf16.bf16 "
        "{%0,%1,%2,%3,%4,%5,%6,%7,%8,%9,%10,%11,%12,%13,%14,%15}, %16, %17, p, 1, 1, 1, 0;\n}"
        : F8(d, 0), F8(d, 8) : "l"(da), "l"(db));
}

struct Params {
    Scratch* scr;
    const uint32_t *ax, *bx;
    const char* wq;
    __nv_bfloat16* out;
};
struct Maps { CUtensorMap kv[2], qa, qb, wo[2], c, uk, uv; };

__device__ __forceinline__ void wait_flags(const unsigned* flags, unsigned tag, int lane) {
    for (int i = 0; !__all_sync(0xffffffffu, ld_acquire(flags + lane * 8) == tag); i++) {
        if (i > SPIN_MAX) __trap();
        __nanosleep(BPOLL);
    }
    __syncwarp();
}
__device__ __forceinline__ void load_slice(uint32_t dst, const CUtensorMap* map, int r, uint32_t bar) {
    mbar_expect(bar, 131072);
#pragma unroll
    for (int x = 0; x < 4; x++) tma2d_ef(dst + x * 32768, map, r * 128 + (x & 1) * 64, (x >> 1) * 256, bar);
}
__device__ __forceinline__ void gemv_slice(uint32_t sb, int warp, int lane) {
    const int g = lane >> 2, tq = lane & 3;
    float d[4][4];
#pragma unroll
    for (int i = 0; i < 4; i++) d[i][0] = d[i][1] = d[i][2] = d[i][3] = 0.f;
    const uint32_t wb = sb + SB_STG + (warp >> 2) * 32768 + ((lane & 7) + 8 * (lane >> 4)) * 128 +
                        (((2 * (warp & 3) + ((lane >> 3) & 1)) ^ (lane & 7)) << 4);
    const uint32_t xb = sb + SB_X + ((g & 3) * 264 + tq) * 4;
#pragma unroll 1
    for (int k8 = 0; k8 < 4; k8++) {
        uint32_t a[8][4], b[8][2];
#pragma unroll
        for (int ks = 0; ks < 8; ks++) {
            ldsm4t(a[ks], wb + (k8 >> 1) * 65536 + (k8 & 1) * 16384 + ks * 2048);
            b[ks][0] = lds32(xb + k8 * 256 + ks * 32);
            b[ks][1] = lds32(xb + k8 * 256 + ks * 32 + 16);
        }
#pragma unroll
        for (int ks = 0; ks < 8; ks++) mma16816(d[ks & 3], a[ks], b[ks][0], b[ks][1]);
    }
    const float y0 = ((d[0][0] + d[1][0]) + (d[2][0] + d[3][0])) + ((d[0][1] + d[1][1]) + (d[2][1] + d[3][1]));
    const float y1 = ((d[0][2] + d[1][2]) + (d[2][2] + d[3][2])) + ((d[0][3] + d[1][3]) + (d[2][3] + d[3][3]));
    if (tq < 2) {
        sts32(sb + SB_QB + (tq * 128 + warp * 16 + g) * 4, __float_as_uint(y0));
        sts32(sb + SB_QB + (tq * 128 + warp * 16 + 8 + g) * 4, __float_as_uint(y1));
    }
}
__device__ __forceinline__ uint32_t wo_lane(uint32_t sb, int lane) {
    return sb + ((lane & 7) + 8 * (lane >> 4)) * 64 + ((((lane >> 3) & 1) ^ ((lane >> 1) & 3)) << 4);
}

template <int NP, int NTHR> __device__ __forceinline__ float2 sum_parts(uint32_t q, float x, float y) {
    asm volatile("bar.sync 5, %0;" ::"n"(NTHR) : "memory");
    float2 p[NP];
#pragma unroll
    for (int i = 0; i < NP; i++) p[i] = lds64f(q + i * 320);
    p[0].x += x; p[0].y += y;
#pragma unroll
    for (int d = 1; d < NP; d *= 2)
#pragma unroll
        for (int i = 0; i + d < NP; i += 2 * d) { p[i].x += p[i + d].x; p[i].y += p[i + d].y; }
    return p[0];
}

__device__ __forceinline__ void latent_branch(const Params& P, const Maps& M, uint8_t* sm) {
    const uint32_t sb = s2u(sm);
    const int tid = threadIdx.x, lane = tid & 31, warp = tid >> 5, g = lane >> 2, tq = lane & 3, r = blockIdx.x >> 2;
    const uint32_t bar_w = sb + SB_BAR + 16, bar_x = sb + SB_BAR + 24;
    const unsigned tag = lds32(sb + SB_CNT) + 1;
    Scratch* const S = P.scr;
    const float* yb = reinterpret_cast<const float*>(sm + SB_QB);
    float* xs = reinterpret_cast<float*>(sm + SB_X);
    const int crow0 = (r >> 4) * 8192 + (r & 15) * 64;
    {
        uint32_t* xh = reinterpret_cast<uint32_t*>(sm + SB_X) + tid;
        xh[0] = __ldg(P.bx + tid); xh[264] = 0; xh[528] = __ldg(P.bx + 256 + tid); xh[792] = 0;
        bar_sync(0, 256);
        mbar_wait(bar_w, 0);
        gemv_slice(sb, warp, lane);
        bar_sync(0, 256);
        if (tid == 0) load_slice(sb + SB_STG, &M.uk, r, bar_w);
        uint32_t qb[8][2];
#pragma unroll
        for (int ks = 0; ks < 8; ks++) {
            const float2 a = *reinterpret_cast<const float2*>(yb + (g & 1) * 128 + ks * 16 + 2 * tq);
            const float2 b = *reinterpret_cast<const float2*>(yb + (g & 1) * 128 + ks * 16 + 8 + 2 * tq);
            qb[ks][0] = packbf(a.x, a.y);
            qb[ks][1] = packbf(b.x, b.y);
        }
        mbar_wait(bar_w, 1);
        const uint32_t wb = sb + SB_STG + (warp >> 2) * 65536 + ((warp & 3) * 64 + (lane & 15)) * 128;
#pragma unroll 1
        for (int mt = 0; mt < 4; mt++) {
            float d[4] = {0.f, 0.f, 0.f, 0.f};
#pragma unroll
            for (int ks = 0; ks < 8; ks++) {
                uint32_t a[4];
                ldsm4(a, wb + (ks >> 2) * 32768 + mt * 2048 + (((2 * (ks & 3) + (lane >> 4)) ^ (lane & 7)) << 4));
                mma16816(d, a, qb[ks][0], qb[ks][1]);
            }
            if (tq == 0) {
                const int c = warp * 64 + mt * 16 + g;
                xs[c] = d[0]; xs[512 + c] = d[1]; xs[c + 8] = d[2]; xs[512 + c + 8] = d[3];
            }
        }
        bar_sync(0, 256);
        if (tid == 32) {
#pragma unroll
            for (int t = 0; t < 2; t++) {
                mbar_expect(sb + SB_BAR + t * 8, 65536);
                tma4d_ef(sb + SB_STG + t * 65536, &M.c, (crow0 >> 3) + t * 128, sb + SB_BAR + t * 8);
            }
        }
        const int b = tid >> 7, lo = (tid >> 6) & 1, ch = tid & 63;
        float v[8];
#pragma unroll
        for (int i = 0; i < 8; i++) {
            const float x = xs[b * 512 + ch * 8 + i];
            v[i] = lo ? x - bf16r(x) : x;
        }
        const int row = 16 * (r >> 3) + (r & 7) + 8 * lo;
        S->qimg[b * 4096 + (ch >> 3) * 512 + row * 8 + ((ch & 7) ^ (r & 7))] =
            make_uint4(packbf(v[0], v[1]), packbf(v[2], v[3]), packbf(v[4], v[5]), packbf(v[6], v[7]));
        bar_sync(0, 256);
        if (warp == 0) {
            if (lane == 0) { __threadfence(); st_release(S->qflag + r * 8, tag); }
            wait_flags(S->qflag, tag, lane);
            if (lane == 0) {
                fence_async_all();
                mbar_expect(bar_x, 65536);
                bulk_g2s(sb + SB_QIMG, S->qimg + (r >> 4) * 4096, 65536, bar_x);
            }
        }
        mbar_wait(bar_x, 0);
    }
    {
        const int wg = warp >> 2;
        float acc[4][16];
#pragma unroll
        for (int i = 0; i < 64; i++) acc[i >> 4][i & 15] = 0.f;
        const int head = (warp & 3) * 8 + g;
        const uint32_t pa = sb + SB_P + wg * 4096;
        float* al = reinterpret_cast<float*>(sm + SB_AL) + wg * 32;
        float m = -FLT_MAX, l = 0.f;
#pragma unroll 1
        for (int t = 0; t < 8; t++) {
            const uint32_t stg = sb + SB_STG + (t & 1) * 65536;
            mbar_wait(sb + SB_BAR + (t & 1) * 8, (t >> 1) & 1);
            float s[32];
            uint32_t qa = sb + SB_QIMG;
            asm volatile("" : "+r"(qa));
            wg_fence();
#pragma unroll
            for (int k = 0; k < 32; k++) {
                const uint32_t off = (k >> 2) * 8192 + (k & 3) * 32;
                wgmma_n64_ss(s, gdesc(qa + off, 16, 1024), gdesc(stg + (k >> 2) * 1024 + (k & 3) * 32, 16, 8192), k > 0);
            }
            wg_commit();
            wg_wait0();
            reg_fence(s);
            float p[16], mx = m;
#pragma unroll
            for (int i = 0; i < 8; i++) {
                p[2 * i] = bf16r(bf16r(s[4 * i] + s[4 * i + 2]) * SCALE);
                p[2 * i + 1] = bf16r(bf16r(s[4 * i + 1] + s[4 * i + 3]) * SCALE);
                mx = fmaxf(mx, fmaxf(p[2 * i], p[2 * i + 1]));
            }
            mx = fmaxf(mx, shx(mx, 1));
            mx = fmaxf(mx, shx(mx, 2));
            const float alpha = ex2((m - mx) * LOG2E);
            m = mx;
            float sum = 0.f;
#pragma unroll
            for (int i = 0; i < 8; i++) {
                const float a = ex2((p[2 * i] - mx) * LOG2E), b = ex2((p[2 * i + 1] - mx) * LOG2E);
                sum += a + b;
                sts32(pa + head * 128 + ((i ^ g) << 4) + tq * 4, packbf(a, b));
            }
            l = fmaf(l, alpha, sum);
            if (tq == 0) al[head] = alpha;
            asm volatile("fence.proxy.async.shared::cta;" ::: "memory");
            bar_sync(1 + wg, 128);
#pragma unroll
            for (int j = 0; j < 4; j++) {
                const float2 a = *reinterpret_cast<const float2*>(al + 8 * j + 2 * tq);
#pragma unroll
                for (int i = 0; i < 4; i++) { acc[i][4 * j] *= a.x; acc[i][4 * j + 1] *= a.y; acc[i][4 * j + 2] *= a.x; acc[i][4 * j + 3] *= a.y; }
            }
#pragma unroll
            for (int i = 0; i < 4; i++) reg_fence(acc[i]);
            wg_fence();
#pragma unroll
            for (int kk = 0; kk < 4; kk++)
#pragma unroll
                for (int i = 0; i < 4; i++)
                    wgmma_n32_ts(acc[i], gdesc(stg + (wg * 4 + i) * 1024 + kk * 16384, 1024, 8192), gdesc(pa + kk * 32, 16, 1024));
            wg_commit();
            wg_wait0();
#pragma unroll
            for (int i = 0; i < 4; i++) reg_fence(acc[i]);
            bar_sync(0, 256);
            if (tid == 0) {
                if (t + 2 < 8) {
                    const uint32_t bar = sb + SB_BAR + (t & 1) * 8;
                    mbar_expect(bar, 65536);
                    tma4d_ef(stg, &M.c, (crow0 >> 3) + (t + 2) * 128, bar);
                }
                if (t == 7) load_slice(sb + SB_STG, &M.uv, r, bar_w);
            }
        }
        float* dst = reinterpret_cast<float*>(sm + SB_QIMG + 2 * tq * PROW) + wg * 256 + (warp & 3) * 16 + g;
#pragma unroll
        for (int i = 0; i < 64; i++)
            dst[(((i >> 2) & 3) * 8 + (i & 1)) * (PROW / 4) + (i >> 4) * 64 + (i & 2) * 4] = acc[i >> 4][i & 15];
        l += shx(l, 1); l += shx(l, 2);
        if (wg == 0 && tq < 2) *reinterpret_cast<float4*>(sm + SB_QIMG + head * PROW + 2048 + tq * 16) = make_float4(m, l, 0.f, 0.f);
        asm volatile("fence.proxy.async.shared::cta;" ::: "memory");
        bar_sync(0, 256);
        if (warp == 0) {
            bulk_s2g(S->bpart + (lane * 32 + r) * (PROW / 16), sb + SB_QIMG + lane * PROW, PROW);
            asm volatile("cp.async.bulk.commit_group;" ::: "memory");
            asm volatile("cp.async.bulk.wait_group 0;" ::: "memory");
            fence_async_all();
            __threadfence();
            __syncwarp();
            if (lane == 0) st_release(S->bflag + r * 8, tag);
            wait_flags(S->bflag, tag, lane);
            if (lane == 0) {
                fence_async_all();
                mbar_expect(bar_x, 32 * PROW);
                bulk_g2s(sb + SB_QIMG, S->bpart + r * 32 * (PROW / 16), 32 * PROW, bar_x);
            }
        }
    }
    {
        const int b = tid >> 7, c4 = tid & 127;
        mbar_wait(bar_x, 1);
        const float2 ml = *reinterpret_cast<const float2*>(sm + SB_QIMG + (b * 16 + (lane & 15)) * PROW + 2048);
        float MM = ml.x;
        MM = fmaxf(MM, shx(MM, 1)); MM = fmaxf(MM, shx(MM, 2)); MM = fmaxf(MM, shx(MM, 4)); MM = fmaxf(MM, shx(MM, 8));
        const float e = ex2((ml.x - MM) * LOG2E);
        float L = e * ml.y;
        L += shx(L, 1); L += shx(L, 2); L += shx(L, 4); L += shx(L, 8);
        const float wgt = e / L;
        float4 o = make_float4(0.f, 0.f, 0.f, 0.f);
#pragma unroll 4
        for (int i = 0; i < 16; i++) {
            const float w = __shfl_sync(0xffffffffu, wgt, i);
            const float4 v = *reinterpret_cast<const float4*>(sm + SB_QIMG + (b * 16 + i) * PROW + c4 * 16);
            o.x = fmaf(w, v.x, o.x); o.y = fmaf(w, v.y, o.y); o.z = fmaf(w, v.z, o.z); o.w = fmaf(w, v.w, o.w);
        }
        uint32_t* xh = reinterpret_cast<uint32_t*>(xs);
        const uint32_t h0 = packbf(o.x, o.y), h1 = packbf(o.z, o.w);
        *reinterpret_cast<uint2*>(xh + (2 * b) * 264 + c4 * 2) = make_uint2(h0, h1);
        *reinterpret_cast<uint2*>(xh + (2 * b + 1) * 264 + c4 * 2) =
            make_uint2(packbf(o.x - bflo(h0), o.y - bfhi(h0)), packbf(o.z - bflo(h1), o.w - bfhi(h1)));
        bar_sync(0, 256);
        mbar_wait(bar_w, 0);
        gemv_slice(sb, warp, lane);
        bar_sync(0, 256);
        if (tid < 64) {
            const float* y = yb + warp * 128 + 16 * g + 2 * tq;
            st_b128(S->frag[0] + (warp * 32 + r) * 32 + lane, make_uint4(packbf(y[0], y[1]), tag, packbf(y[8], y[9]), tag));
        }
    }
}

__global__ void __launch_bounds__(480, 1)
fused_decode_kernel(const Params P, const __grid_constant__ Maps M) {
    extern __shared__ __align__(1024) uint8_t sm[];
    const uint32_t sb = s2u(sm);
    const int tid = threadIdx.x, lane = tid & 31, bx = blockIdx.x;
    asm volatile("{\n.reg .pred p;\nsetp.lt.u32 p, %1, 256;\n@p prefetch.global.L2 [%0];\n}"
                 ::"l"(P.wq + (unsigned)(((bx & 1) * 256 + tid) * 8192 + (bx >> 1) * 128)), "r"(tid) : "memory");
    const int warp = __shfl_sync(0xffffffffu, tid >> 5, 0);
    const int g = lane >> 2, tq = lane & 3;
    Scratch* const S = P.scr;

    if (!(bx & 1)) {
        const int grp = (bx >> 1) & 1, crk = bx >> 2;
        auto issue = [&](int slot, unsigned tk, int v) {
            const uint32_t full = sb + SA_FULL + slot * 16 + v * 8;
            mbar_expect(full, 8192);
            tma2d_ef(sb + slot * 16384 + v * 8192, &M.kv[v], 0, (grp * UPG + tk) * 64, full);
        };
        if (warp >= 8) {
            const int w = warp - 8;
            if (w >= NW) {
                if (w == NW && !(bx & 15)) asm volatile("prefetch.global.L2 [%0];" ::"l"(((lane & 16) ? P.bx : P.ax) + (lane & 15) * 32) : "memory");
                return;
            }
            const bool one = elect();
            if (one) {
                mbar_init(sb + SA_FULL + w * 16, 1);
                mbar_init_fence();
                sts32(sb + SA_META + w * 4, 0);
                if (w < SKEW) issue(w, w * CPG + crk, 0);
#pragma unroll
                for (int i = 0; i < SPW; i++) {
                    if (i) mbar_init(sb + SA_FULL + (w + i * NW) * 16, 1);
                    mbar_init(sb + SA_FULL + (w + i * NW) * 16 + 8, 1);
                    mbar_init(sb + SA_GOV + (w + i * NW) * 8, 1);
                    mbar_init(sb + SA_EMPTY + (w + i * NW) * 8, 2);
                    mbar_arrive(sb + SA_EMPTY + (w + i * NW) * 8);
                }
                if (w < SKEW) mbar_arrive(sb + SA_EMPTY + w * 8);
                sts32(sb + SA_LIM + w * 4, LIM);
                mbar_init_fence();
            }
            __syncwarp();
            bar_arrive(2, (NW + 1) * 32);
            bar_arrive(1, (2 * NW + 2) * 32);
            unsigned c = 0;
            unsigned* const ctr = S->ctr[grp] + lane;
            int slot = w;
            uint32_t eph = 0;
#pragma unroll 1
            for (int n = 0;; n++) {
                unsigned tk = (n * NW + w) * CPG + crk, own = 0;
                if (n >= SPW) {
                    own = __shfl_sync(0xffffffffu, c, 0);
                    tk = own % UPG + NSL * CPG;
                }
                mbar_wait(sb + SA_EMPTY + slot * 8, eph);
                if (tk >= UPG) {
                    if (one) {
                        sts32(sb + SA_LIM + w * 4, 0);
                        sts32(sb + SA_META + slot * 4, 32);
                        mbar_arrive(sb + SA_FULL + slot * 16);
                        asm volatile("red.relaxed.gpu.global.add.u32 [%0], %1;" ::"l"(S->ctr[grp]), "n"(SPW - 1) : "memory");
                    }
                    return;
                }
                if (one && (n || w >= SKEW)) {
                    sts32(sb + SA_META + slot * 4, tk >> 8);
                    issue(slot, tk, 0);
                    if (tk == UPG - FIRE_T) st_b64(S->fire + grp, gt(), own / UPG + 1);
                }
                if (n >= SPW - 1 && lane == 0) c = atom_inc(ctr);
                mbar_wait(sb + SA_GOV + slot * 8, eph);
                if (one) issue(slot, tk, 1);
                slot += NW;
                if (slot >= NSL) { slot -= NSL; eph ^= 1; }
                __syncwarp();
            }
        }
        if (warp == 0) {
            bool busy = lane < 2 * SKEW && !(lane & 1);
            uint32_t par = busy ? 0 : 1;
            int slot = SKEW;
            bool first = true;
            const unsigned c0 = clk32() + RAMP_T0;
            const int own = lane >= 2 * NSL ? -1 : ((lane >> 1) + (lane & 1) * SKEW) % NSL;
            const uint32_t fb = sb + SA_FULL + lane * 8, lw = sb + SA_LIM + ((lane >> 1) % NW) * 4;
            const uint32_t go = sb + ((lane & 1) ? SA_GOV : SA_EMPTY) + (lane >> 1) * 8;
            bar_sync(2, (NW + 1) * 32);
#pragma unroll 1
            for (int it = 0; it < SPIN_MAX; it++) {
                bool ok = true;
                if (busy) ok = mbar_test(fb, par);
                int lim = lds32(lw);
                if (first) lim = min(LIM0, SKEW + max((int)(clk32() - c0), 0) / RAMP_S);
                busy = busy && !ok && lim;
                const int n = __popc(__ballot_sync(0xffffffffu, busy));
                if (!__any_sync(0xffffffffu, lim)) return;
                const bool mine = own == slot && lim;
                if (!__any_sync(0xffffffffu, mine && (busy || n > lim - 2))) {
                    if (mine) { mbar_arrive(go); busy = true; par ^= 1; }
                    if (++slot == NSL) { slot = 0; first = false; }
                    it = 0;
                }
            }
            __trap();
        }
        {
            int w3 = warp;
            asm volatile("" : "+r"(w3));
            if (w3 == 3) return;
        }
        if (warp == 1) {
            const uint4* const qsrc = S->qpub + grp * 1024 + lane;
            uint2* const qdst = reinterpret_cast<uint2*>(sm + SA_Q) + lane;
            const unsigned epoch = ld_relaxed1(S->ctr[grp]) / UPG;
            if (lane == 0) {
                mbar_init(sb + SA_QBAR, 32);
                mbar_init(sb + SA_QBAR + 8, 32);
                mbar_init(sb + SA_QBAR + 16, 32);
#pragma unroll
                for (int i = 0; i < 8; i++) { mbar_init(sb + SA_MBAR + i * 16, NW); mbar_init(sb + SA_MBAR + i * 16 + 8, 1); }
                mbar_init_fence();
                sts32(sb + SA_CNT, epoch);
            }
            __syncwarp();
            bar_arrive(1, (2 * NW + 2) * 32);
            __nanosleep(QSLEEP);
            for (int it = 0;; it++) {
                const uint4 u = ld_b128(qsrc);
                if (__all_sync(0xffffffffu, u.y == epoch + 1)) { qdst[0] = make_uint2(u.x, u.z); break; }
                if (it > SPIN_MAX) __trap();
            }
            mbar_arrive(sb + SA_QBAR);
#pragma unroll 1
            for (int h = 0, it = 0; h < 32; it++) {
                uint4 v[8];
                bool ok = true;
#pragma unroll
                for (int k = 0; k < 8; k++) v[k] = ld_b128(qsrc + (h + k) * 32);
#pragma unroll
                for (int k = 0; k < 8; k++) { ok = ok && v[k].y == epoch + 1; qdst[(h + k) * 32] = make_uint2(v[k].x, v[k].z); }
                if (__all_sync(0xffffffffu, ok)) {
                    if (!h) mbar_arrive(sb + SA_QBAR + 8);
                    h += 8;
                } else {
                    __nanosleep(QPOLL);
                }
                if (it > SPIN_MAX) __trap();
            }
            mbar_arrive(sb + SA_QBAR + 16);
            return;
        }
        bar_sync(1, (2 * NW + 2) * 32);
        if (warp == 2) {
            const uint32_t t8 = (lds32(sb + SA_CNT) + 1) & 0xffu;
            uint4* dst = S->apart + (grp * 32 * CPG + crk) * 32 + lane;
            uint2* dml = S->aml + (grp * 32 * CPG + crk) * 4 + (lane & 3);
#pragma unroll
            for (int k = 0; k < 4; k++) st_b64(dml + (k * 8 + (lane >> 2)) * (CPG * 4), 0, t8 ^ 0x80u);
            __syncwarp();
#pragma unroll 1
            for (int h = 0; h < 32; h++, dst += CPG * 32, dml += CPG * 4) {
                const float* s0 = reinterpret_cast<const float*>(sm + SA_SLOT) + (h & 7) * (NW * 132);
                mbar_wait(sb + SA_MBAR + (h & 7) * 16, (h >> 3) & 1);
                float2 ml[NW];
                float4 v[NW];
#pragma unroll
                for (int w = 0; w < NW; w++) {
                    ml[w] = *reinterpret_cast<const float2*>(s0 + w * 132 + 128);
                    v[w] = *reinterpret_cast<const float4*>(s0 + w * 132 + lane * 4);
                }
                const float MM = fmaxf(fmaxf(ml[0].x, ml[1].x), fmaxf(ml[2].x, ml[3].x));
                float e[NW];
#pragma unroll
                for (int w = 0; w < NW; w++) e[w] = ex2((ml[w].x - MM) * LOG2E);
                st_b128(dst, make_uint4(tagf(fmaf(e[0], v[0].x, e[1] * v[1].x) + fmaf(e[2], v[2].x, e[3] * v[3].x), t8),
                                        __float_as_uint(fmaf(e[0], v[0].y, e[1] * v[1].y) + fmaf(e[2], v[2].y, e[3] * v[3].y)),
                                        __float_as_uint(fmaf(e[0], v[0].z, e[1] * v[1].z) + fmaf(e[2], v[2].z, e[3] * v[3].z)),
                                        __float_as_uint(fmaf(e[0], v[0].w, e[1] * v[1].w) + fmaf(e[2], v[2].w, e[3] * v[3].w))));
                if (lane < 4) st_b64(dml, __float_as_uint(MM), tagf(fmaf(e[0], ml[0].y, e[1] * ml[1].y) + fmaf(e[2], ml[2].y, e[3] * ml[3].y), t8));
                if (h == 27 || h == 28) st_b128(dst + 3 * CPG * 32, make_uint4(t8 ^ 0x80u, 0, 0, 0));
                __syncwarp();
                if (lane == 0) mbar_arrive(sb + SA_MBAR + (h & 7) * 16 + 8);
            }
            return;
        }
        const int cw = warp - 4;
        uint32_t koff[4], voff[4];
#pragma unroll
        for (int i = 0; i < 4; i++) {
            koff[i] = ((lane & 7) + 8 * ((lane >> 3) & 1)) * 128 + (((2 * i + (lane >> 4)) ^ (lane & 7)) << 4);
            voff[i] = ((lane & 7) + 8 * (lane >> 4)) * 128 + (((2 * i + ((lane >> 3) & 1)) ^ (lane & 7)) << 4);
        }
        uint32_t psel[4][2];
#pragma unroll
        for (int i = 0; i < 4; i++) {
            psel[i][0] = (g >> 1) != i ? 0x4444u : (g & 1) ? 0x1044u : 0x4410u;
            psel[i][1] = (g >> 1) != i ? 0x4444u : (g & 1) ? 0x3244u : 0x4432u;
        }
        uint32_t qf[4][2];
        auto load_q = [&](int pl) {
            const uint32_t q = sb + SA_Q + pl * 256 + ((g & 1) * 32 + tq) * 4;
#pragma unroll
            for (int ks = 0; ks < 4; ks++) { qf[ks][0] = lds32(q + ks * 32); qf[ks][1] = lds32(q + ks * 32 + 16); }
        };
        mbar_wait(sb + SA_QBAR, 0);
        load_q(0);
        float acc[4][4], m = -FLT_MAX, l = 0.f, ls = 0.f;
#pragma unroll
        for (int i = 0; i < 4; i++) acc[i][0] = acc[i][1] = acc[i][2] = acc[i][3] = 0.f;
        int slot = cw, cur = 0;
        uint32_t ph = 0;
#pragma unroll 1
        for (;;) {
            mbar_wait(sb + SA_FULL + slot * 16, ph);
            const int pl = lds32(sb + SA_META + slot * 4);
            if (pl != cur) {
#pragma unroll 1
                do {
                    float* s0 = reinterpret_cast<float*>(sm + SA_SLOT) + ((cur & 7) * NW + cw) * 132;
                    float* sw = s0 + tq * 16 + (g >> 1) * 4 + (g & 1);
                    sw[0] = (acc[0][0] + acc[1][0]) + (acc[2][0] + acc[3][0]);
                    sw[2] = (acc[0][2] + acc[1][2]) + (acc[2][2] + acc[3][2]);
                    sw[64] = (acc[0][1] + acc[1][1]) + (acc[2][1] + acc[3][1]);
                    sw[66] = (acc[0][3] + acc[1][3]) + (acc[2][3] + acc[3][3]);
                    if (lane == 0) *reinterpret_cast<float2*>(s0 + 128) = make_float2(m, ls);
                    __syncwarp();
                    if (lane == 0) mbar_arrive(sb + SA_MBAR + (cur & 7) * 16);
                    if (++cur == 32) return;
#pragma unroll
                    for (int i = 0; i < 4; i++) acc[i][0] = acc[i][1] = acc[i][2] = acc[i][3] = 0.f;
                    m = -FLT_MAX; l = ls = 0.f;
                    mbar_wait(sb + SA_MBAR + (cur & 7) * 16 + 8, ((cur >> 3) & 1) ^ 1);
                    if (cur == 1 || cur == 8) mbar_wait(sb + SA_QBAR + 8 + (cur & 8), 0);
                } while (cur != pl);
                load_q(pl);
            }
            float s4[4][4];
            const uint32_t kb = sb + slot * 16384;
#pragma unroll
            for (int j = 0; j < 4; j++) {
                s4[j][0] = s4[j][1] = s4[j][2] = s4[j][3] = 0.f;
                const bool on = (g >> 1) == j;
#pragma unroll
                for (int ks = 0; ks < 4; ks++) {
                    uint32_t a[4];
                    ldsm4(a, kb + j * 2048 + koff[ks]);
                    mma16816(s4[j], a, on ? qf[ks][0] : 0u, on ? qf[ks][1] : 0u);
                }
            }
            float d[4];
#pragma unroll
            for (int r = 0; r < 4; r++) d[r] = (s4[0][r] + s4[1][r]) + (s4[2][r] + s4[3][r]);
            float sa = (g & 1) ? d[1] : d[0], sc = (g & 1) ? d[3] : d[2];
            sa += shx(sa, 4); sc += shx(sc, 4);
            uint32_t sp = packbf(sa, sc);
            sp = packbf(bflo(sp) * SCALE, bfhi(sp) * SCALE);
            sa = bflo(sp); sc = bfhi(sp);
            const float mx = warp_max(fmaxf(fmaxf(sa, sc), m));
            const float alpha = ex2((m - mx) * LOG2E);
            m = mx;
            const float pa = ex2((sa - mx) * LOG2E), pc = ex2((sc - mx) * LOG2E);
            const uint32_t pk = packbf(pa, pc);
            uint32_t pb[4][4][2];
#pragma unroll
            for (int j = 0; j < 4; j++) {
                const uint32_t pj = __shfl_sync(0xffffffffu, pk, 8 * tq + j);
#pragma unroll
                for (int i = 0; i < 4; i++) { pb[j][i][0] = prmt0(pj, psel[i][0]); pb[j][i][1] = prmt0(pj, psel[i][1]); }
            }
            l = fmaf(l, alpha, pa + pc);
            ls = l + shx(l, 8);
#pragma unroll
            for (int i = 0; i < 4; i++) { acc[i][0] *= alpha; acc[i][1] *= alpha; acc[i][2] *= alpha; acc[i][3] *= alpha; }
            mbar_wait(sb + SA_FULL + slot * 16 + 8, ph);
            const uint32_t vb = kb + 8192;
#pragma unroll
            for (int i = 0; i < 4; i++)
#pragma unroll
                for (int j = 0; j < 4; j++) {
                    uint32_t a[4];
                    ldsm4t(a, vb + j * 2048 + voff[i]);
                    mma16816(acc[j], a, pb[j][i][0], pb[j][i][1]);
                }
            ls += shx(ls, 16); ls += shx(ls, 1); ls += shx(ls, 2);
            __syncwarp();
            if (lane == 0) mbar_arrive(sb + SA_EMPTY + slot * 8);
            slot += NW;
            if (slot >= NSL) { slot -= NSL; ph ^= 1; }
        }
    }

    const int r = bx >> 2, isC = (bx >> 1) & 1;
    const int isA = (r >> 2) & 1, cb = (r >> 3) * 4 + (r & 3);
    const uint32_t bar_h = sb + SB_BAR + 32;
    if (warp == 8 && !isC) {
        const unsigned c0 = clk32();
        bar_sync(7, 64);
        while ((int)(clk32() - c0) < BSTART + (r & 7) * BSTAG) {}
        if (elect()) load_slice(sb + SB_STG, &M.qb, r, sb + SB_BAR + 16);
        __syncwarp();
    }
    if (warp < 8) {
        const uint32_t bar_q = bar_h + (NT + warp) * 8, box = sb + SB_QIMG + warp * 8192;
        if (elect()) {
            mbar_init(bar_q, 1);
            mbar_init_fence();
            mbar_expect(bar_q, 8192 + 256);
            tma2d_ef(box, &M.qa, (bx >> 1) * 64, warp * 64, bar_q);
        }
        __syncwarp();
        unsigned epoch = 0;
        if (warp < 2) epoch = ld_relaxed1(S->ctr[isC]) / UPG;
        uint4* const qdst = S->qpub + ((lane >> 4) * 32 + r) * 32 + isC * 16 + (lane & 15);
        if (warp == 0) st_b128(qdst, make_uint4(0, 0, 0, 0));
        if (elect()) {
            for (const unsigned c0 = clk32(); (int)(clk32() - c0) < XD0 + (bx >> 1) * XDS;) {}
            bulk_g2s(sb + SB_P + 4096 + warp * 288, P.ax + warp * 32, 128, bar_q);
            bulk_g2s(sb + SB_P + 4096 + warp * 288 + 144, P.ax + 256 + warp * 32, 128, bar_q);
        }
        if (tid == 32) {
#pragma unroll
            for (int i = 0; i < 4 + NT; i++) mbar_init(sb + SB_BAR + i * 8, 1);
            mbar_init_fence();
            sts32(sb + SB_CNT, epoch);
            sts32(sb + SB_CNT + 4, 0);
        }
        __syncwarp();
        if (warp == 1 && !isC) bar_arrive(7, 64);
        mbar_wait(bar_q, 0);
        uint32_t b[8];
#pragma unroll
        for (int i = 0; i < 8; i++) b[i] = lds32(sb + SB_P + 4096 + warp * 288 + (g & 1) * 144 + tq * 4 + i * 16);
        float d[4][4];
        uint32_t a[4][4][4];
#pragma unroll
        for (int i = 0; i < 4; i++) {
            d[i][0] = d[i][1] = d[i][2] = d[i][3] = 0.f;
#pragma unroll
            for (int ks = 0; ks < 4; ks++)
                ldsm4t(a[i][ks], box + ks * 2048 + ((lane & 7) + 8 * (lane >> 4)) * 128 + (((2 * i + ((lane >> 3) & 1)) ^ (lane & 7)) << 4));
        }
#pragma unroll
        for (int ks = 0; ks < 4; ks++)
#pragma unroll
            for (int i = 0; i < 4; i++) mma16816(d[i], a[i][ks], b[2 * ks], b[2 * ks + 1]);
        float* qred = reinterpret_cast<float*>(sm + SB_P);
#pragma unroll
        for (int c = 0; c < 4; c++)
            qred[warp * 128 + (c & 1) * 64 + tq * 16 + (c >> 1) * 8 + g] = tq == 0 ? d[0][c] : tq == 1 ? d[1][c] : tq == 2 ? d[2][c] : d[3][c];
        bar_sync(0, 256);
        if (warp == 0) {
            float4 v[8];
#pragma unroll
            for (int w = 0; w < 8; w++) v[w] = *reinterpret_cast<const float4*>(qred + w * 128 + lane * 4);
#pragma unroll
            for (int o = 4; o; o >>= 1)
#pragma unroll
                for (int w = 0; w < o; w++) { v[w].x += v[w + o].x; v[w].y += v[w + o].y; v[w].z += v[w + o].z; v[w].w += v[w + o].w; }
            st_b128(qdst, make_uint4(packbf(v[0].x, v[0].y), epoch + 1, packbf(v[0].z, v[0].w), epoch + 1));
        }
        if (!isC && tid < 4) st_b128(((tid & 2) ? S->bflag : S->qflag) + r * 8 + (tid & 1) * 4, make_uint4(0, 0, 0, 0));
        if (!isC && warp < 2) st_b128(S->frag[0] + (warp * 32 + r) * 32 + lane, make_uint4(0, 0, 0, 0));
        if (isC && !(warp & 3)) st_b128(S->frag[1] + ((warp >> 2) * 32 + (isA ? 0 : 16) + cb) * 32 + lane, make_uint4(0, 0, 0, 0));
        if (!isC) latent_branch(P, M, sm);
        bar_arrive(6, 288);
    }

    constexpr int ND = 2;
    const int nsnd = isA ? NSA : NSB, isCA = isC & isA;
    const int y0 = isC ? nsnd : 0, y1 = isC ? 32 - ND * isA : nsnd;
    const int nreq = isC ? 32 - nsnd : nsnd;
    const int nmw = isC && !isA ? NMW : 0;
    float* const red = reinterpret_cast<float*>(sm + SC_RED);
    const uint32_t wlane = wo_lane(sb, lane);
    auto fetch_frag = [&](int y, int b, unsigned tag, unsigned ns) {
        for (int it = 0;; it++) {
            const uint4 v = ld_b128(S->frag[0] + isA * 2048 + (b * 32 + y) * 32 + lane);
            if (__all_sync(0xffffffffu, v.y == tag)) {
                reinterpret_cast<uint2*>(sm + SC_FR)[(y * 32 + (g >> 1) * 8 + b * 4 + tq) * 2 + (g & 1)] = make_uint2(v.x, v.z);
                return;
            }
            if (it > SPIN_MAX) __trap();
            __nanosleep(ns);
        }
    };
    if (warp < 8) {
        const unsigned tag = lds32(sb + SB_CNT) + 1;
        const uint32_t t8 = tag & 0xffu;
        uint32_t bs[2], wf[4][4];
        float d[2][4];
        const uint32_t wa = (wlane ^ ((warp & 1) * 32)) + (warp & 2) * 2048;
        const int ks0 = (warp & 2) * 2;
        if (isC) __nanosleep(4000);
#pragma unroll 1
        for (int op = isCA ? 0 : 1;; op++) {
            const int step = isCA ? max(op - 1, 0) : 0, h = step ? 31 - ND + step : isA ? cb : 16 + cb;
            if (op != 1) {
                if (!isCA && (!isC || h >= 32 - ND)) break;
                const int rec = ((warp >> 2) * 32 + h) * CPG + (warp & 3) * 8;
                const uint2* mlp = S->aml + (rec + (lane & 7)) * 4;
                const uint4* src = S->apart + rec * 32 + lane;
                asm volatile("" : "+l"(mlp), "+l"(src));
                if (!step) {
                    for (int it = 0; !__all_sync(0xffffffffu, (ld_b64(mlp).y & 0xffu) == t8); it++) {
                        if (it > SPIN_MAX) __trap();
                        __nanosleep(h > 25 ? DPOLL : CPOLL);
                    }
                } else if (step < ND) {
                    mbar_wait(sb + SB_BAR + 8, 0);
                } else {
                    d[0][0] = d[0][1] = d[0][2] = d[0][3] = d[1][0] = d[1][1] = d[1][2] = d[1][3] = 0.f;
#pragma unroll
                    for (int k = 0; k < ND; k++) {
                        mbar_wait(bar_h + k * 16 + (warp & 2) * 4, 0);
#pragma unroll
                        for (int ks = 0; ks < 4; ks++) ldsm4t(wf[ks], wa + k * 8192 + ks * 1024);
                        if (k < ND - 1) {
#pragma unroll
                            for (int ks = 0; ks < 4; ks++) mma16816(d[ks & 1], wf[ks], g == ks0 + ks ? bs[0] : 0u, g == ks0 + ks ? bs[1] : 0u);
                        }
                    }
                    mbar_wait(sb + SB_BAR, 0);
                }
                uint4 v[8];
                uint2 ml = ld_b64(mlp);
#pragma unroll
                for (int i = 0; i < 8; i++) v[i] = ld_b128(src + i * 32);
                for (int it = 0;; it++) {
                    unsigned x = ml.y ^ t8;
#pragma unroll
                    for (int i = 0; i < 8; i++) x |= v[i].x ^ t8;
                    if (!__any_sync(0xffffffffu, x & 0xffu)) break;
                    if (it > SPIN_MAX) __trap();
                    ml = ld_b64(mlp);
#pragma unroll
                    for (int i = 0; i < 8; i++)
                        if ((v[i].x & 0xffu) != t8) v[i] = ld_b128(src + i * 32);
                }
                const float mw = warp_max(__uint_as_float(ml.x)), e = ex2((__uint_as_float(ml.x) - mw) * LOG2E);
                float L = e * __uint_as_float(ml.y), oa[4], ob[4];
                L += shx(L, 1);
#pragma unroll
                for (int i = 0; i < 8; i++) {
                    const float w = __shfl_sync(0xffffffffu, e, i);
                    float (&o)[4] = (i & 1) ? ob : oa;
                    o[0] = i < 2 ? w * __uint_as_float(v[i].x) : fmaf(w, __uint_as_float(v[i].x), o[0]);
                    o[1] = i < 2 ? w * __uint_as_float(v[i].y) : fmaf(w, __uint_as_float(v[i].y), o[1]);
                    o[2] = i < 2 ? w * __uint_as_float(v[i].z) : fmaf(w, __uint_as_float(v[i].z), o[2]);
                    o[3] = i < 2 ? w * __uint_as_float(v[i].w) : fmaf(w, __uint_as_float(v[i].w), o[3]);
                }
                float* fp = reinterpret_cast<float*>(sm + SC_FP) + ((step & 1) * 8 + (warp & 4)) * 132;
                *reinterpret_cast<float4*>(fp + (warp & 3) * 132 + lane * 4) = make_float4(oa[0] + ob[0], oa[1] + ob[1], oa[2] + ob[2], oa[3] + ob[3]);
                L += shx(L, 2);
                L += shx(L, 4);
                if (lane == 0) *reinterpret_cast<float2*>(fp + (warp & 3) * 132 + 128) = make_float2(mw, L);
                bar_sync(1 + (warp >> 2), 128);
                float2 q[4];
                float4 u[4];
#pragma unroll
                for (int w = 0; w < 4; w++) {
                    q[w] = *reinterpret_cast<const float2*>(fp + w * 132 + 128);
                    u[w] = *reinterpret_cast<const float4*>(fp + w * 132 + lane * 4);
                }
                const float MM = fmaxf(fmaxf(q[0].x, q[1].x), fmaxf(q[2].x, q[3].x));
                float f[4], inv;
#pragma unroll
                for (int w = 0; w < 4; w++) f[w] = ex2((q[w].x - MM) * LOG2E);
                asm("rcp.approx.ftz.f32 %0, %1;" : "=f"(inv) : "f"(fmaf(f[0], q[0].y, f[1] * q[1].y) + fmaf(f[2], q[2].y, f[3] * q[3].y)));
                const uint32_t b0 = packbf((fmaf(f[0], u[0].x, f[1] * u[1].x) + fmaf(f[2], u[2].x, f[3] * u[3].x)) * inv,
                                           (fmaf(f[0], u[0].y, f[1] * u[1].y) + fmaf(f[2], u[2].y, f[3] * u[3].y)) * inv);
                const uint32_t b1 = packbf((fmaf(f[0], u[0].z, f[1] * u[1].z) + fmaf(f[2], u[2].z, f[3] * u[3].z)) * inv,
                                           (fmaf(f[0], u[0].w, f[1] * u[1].w) + fmaf(f[2], u[2].w, f[3] * u[3].w)) * inv);
                if (step == ND) {
#pragma unroll
                    for (int ks = 0; ks < 4; ks++) mma16816(d[ks & 1], wf[ks], g == ks0 + ks ? b0 : 0u, g == ks0 + ks ? b1 : 0u);
                    const float x0 = (d[0][0] + d[0][1]) + (d[1][0] + d[1][1]), x1 = (d[0][2] + d[0][3]) + (d[1][2] + d[1][3]);
                    const float z = ((tq & 1) ? x1 : x0) + shx((tq & 1) ? x0 : x1, 1);
                    if ((tq & 2) == (warp & 2)) red[(6 + (tq >> 1)) * 80 + (warp >> 2) * 40 + (warp & 1) * 16 + (tq & 1) * 8 + g] = z;
                    bar_arrive(5, 480);
                    return;
                }
                bs[0] = b0; bs[1] = b1;
                if (!step && !(warp & 3)) st_b128(S->frag[1] + ((warp >> 2) * 32 + h) * 32 + lane, make_uint4(b0, tag, b1, 0));
                if (!isCA) break;
            } else {
#pragma unroll 1
                for (int y = y0 + ((warp - y0) & 3); y < y1 - 3 * isCA; y += 4) fetch_frag(y, warp >> 2, tag, CPOLL);
                if (warp >= nmw) bar_arrive(4, 448);
            }
        }
        if (warp >= nmw) return;
    }
    if (warp == 14) {
        bar_sync(6, 288);
        const CUtensorMap* map = &M.wo[isA];
        const unsigned tag = lds32(sb + SB_CNT) + 1;
        const uint32_t t8 = tag & 0xffu;
        uint2* const snd = S->snd + r * 32 + lane;
        asm volatile("prefetch.tensormap [%0];" ::"l"(map) : "memory");
        if (!isC) st_b64(snd, t8 ^ 0x80u, 0);
        for (int it = 0;; it++) {
            __nanosleep(2000);
            if (it > 1 && ld_b128(S->frag[1] + 25 * 32).y == tag) break;
            if (it > SPIN_MAX) __trap();
        }
        uint2 f;
        for (int it = 0;; it++) {
            f = ld_b64(S->fire + (lane & 1));
            if (__all_sync(0xffffffffu, f.y == tag)) break;
            if (it > SPIN_MAX) __trap();
            __nanosleep(FPOLL);
        }
        const unsigned t0 = __shfl_sync(0xffffffffu, f.x, 0);
        unsigned t1 = t0 + (__reduce_add_sync(0xffffffffu, (int)(f.x - t0)) >> 5) + FIRE_NS;
        if (elect()) {
            const int n1 = nreq - (isC ? (isA ? NLA : NLB) : 0);
            const int dt = !isC ? (isA ? FIRE_W / NSA : FIRE_W / NSB) : isA ? FIRE_W / (32 - NSA - NLA) : FIRE_W / (32 - NSB - NLB);
            unsigned t2 = t1 + REC0_NS;
            int rec = isCA ? 2 : 0;
            int y = isCA ? 32 - ND : y0;
#pragma unroll 1
            for (int i = 0; i < nreq; i++) {
                const int row = y * 128;
                mbar_expect(bar_h + i * 16, 4096);
                mbar_expect(bar_h + i * 16 + 8, 4096);
                if (++y == 32) y = y0;
                if (i <= n1) {
                    unsigned t;
                    for (int it = 0; (int)((t = gt()) - t1) < 0 && it < 4096; it++) {}
                    t1 += dt;
                    if (rec && (int)(t - t2) >= 0) { mbar_arrive(sb + SB_BAR + --rec * 8); t2 += REC_NS - REC0_NS; }
                }
                tma2d(sb + i * 8192, map, cb * 32, row, bar_h + i * 16);
                tma2d(sb + i * 8192 + 4096, map, cb * 32, row + 64, bar_h + i * 16 + 8);
            }
            while (rec) {
                for (int it = 0; (int)(gt() - t2) < 0 && it < 4096; it++) {}
                mbar_arrive(sb + SB_BAR + --rec * 8);
                t2 += REC_NS - REC0_NS;
            }
        }
        __syncwarp();
        uint32_t* dst = reinterpret_cast<uint32_t*>(P.out) + (lane >> 4) * 512 + (isA ? 0 : 256) + cb * 16 + (lane & 15);
        uint32_t q = sb + SC_RED + ((lane >> 4) * 20 + (lane & 15)) * 8;
        asm volatile("" : "+l"(dst), "+r"(q));
        if (!isC) {
            const float2 s = sum_parts<6, 224>(q, 0.f, 0.f);
            st_b64(snd, tagf(s.x, t8), __float_as_uint(s.y));
        } else {
            uint2 o;
            for (int it = 0;; it++) {
                o = ld_b64(snd);
                if (__all_sync(0xffffffffu, (o.x & 0xffu) == t8)) break;
                if (it > SPIN_MAX) __trap();
            }
            if (isA) {
                const float2 s = sum_parts<8, 480>(q, __uint_as_float(o.x), __uint_as_float(o.y));
                asm volatile("st.global.u32 [%0], %1;" ::"l"(dst), "r"(packbf(s.x, s.y)) : "memory");
            } else {
                const float2 s = sum_parts<6 + NMW, 224 + 32 * NMW>(q, __uint_as_float(o.x), __uint_as_float(o.y));
                asm volatile("st.global.b32 [%0], %1;" ::"l"(dst), "r"(packbf(s.x, s.y)) : "memory");
            }
        }
        return;
    }
    {
        const int nw = 6 + nmw, wi = warp < 8 ? warp + 6 : warp - 8, t0 = wi + 2 * ND * isCA;
        bar_sync(4, 448);
        if (isCA) {
            const int y = y0 - ND + ((2 * nreq - 1 - (2 * nreq - 1 - t0) % 6) >> 1);
            const unsigned tag = lds32(sb + SB_CNT) + 1;
#pragma unroll 1
            for (int b = 0; b < 2; b++) fetch_frag(y, b, tag, DPOLL);
            __syncwarp();
        }
        uint32_t rx = sb + SC_RED + (wi * 80 + (tq & 1) * 40 + (tq >> 1) * 16 + g) * 4, nb = isCA ? 480 : 224 + nmw * 32;
        asm volatile("" : "+r"(rx), "+r"(nb));
        float e[4][4];
#pragma unroll
        for (int i = 0; i < 4; i++) e[i][0] = e[i][1] = e[i][2] = e[i][3] = 0.f;
        uint32_t bp = sb + SC_FR + ((2 * (y0 - ND * isCA) + t0) * 16 + (lane & 7)) * 16, wa = wlane + t0 * 4096, bar = bar_h + t0 * 8;
        uint4 b0 = lds128(bp), b1 = lds128(bp + 128);
        const uint32_t zero = lds32(sb + SB_CNT + 4);
#pragma unroll 1
        for (int t = t0;;) {
            uint32_t a[8][4];
            b0.x ^= zero; b1.x ^= zero;
            asm volatile("" : "+r"(b0.x), "+r"(b1.x));
            mbar_wait(bar, 0);
#pragma unroll
            for (int j = 0; j < 8; j++) ldsm4t(a[j], (wa ^ ((j & 1) * 32)) + (j >> 1) * 1024);
            bp += nw * 256;
            const uint4 n0 = lds128(bp), n1 = lds128(bp + 128);
#pragma unroll
            for (int j = 0; j < 8; j++) {
                const uint4& c = (j & 4) ? b1 : b0;
                mma16816(e[(j & 1) * 2 + ((j >> 1) & 1)], a[j], (j & 2) ? c.z : c.x, (j & 2) ? c.w : c.y);
            }
            t += nw;
            if (t >= 2 * nreq) break;
            wa += nw * 4096; bar += nw * 8;
            b0 = n0; b1 = n1;
        }
        float s4[4];
#pragma unroll
        for (int c = 0; c < 4; c++) s4[c] = (tq & 2) ? e[2][c] + e[3][c] : e[0][c] + e[1][c];
        sts32(rx, __float_as_uint((tq & 1) ? s4[1] : s4[0]));
        sts32(rx + 32, __float_as_uint((tq & 1) ? s4[3] : s4[2]));
        bar_arrive(5, nb);
    }
}

typedef CUresult (*EncodeFn)(CUtensorMap*, CUtensorMapDataType, cuuint32_t, void*, const cuuint64_t*, const cuuint64_t*,
                             const cuuint32_t*, const cuuint32_t*, CUtensorMapInterleave, CUtensorMapSwizzle,
                             CUtensorMapL2promotion, CUtensorMapFloatOOBfill);

void make_map(EncodeFn enc, CUtensorMap* m, const void* base, uint64_t cols, uint64_t rows, uint32_t bc, uint32_t br,
              CUtensorMapL2promotion promo, CUtensorMapSwizzle sw = CU_TENSOR_MAP_SWIZZLE_128B) {
    cuuint64_t dims[2] = {cols, rows};
    cuuint64_t strides[1] = {cols * 2};
    cuuint32_t box[2] = {bc, br};
    cuuint32_t es[2] = {1, 1};
    enc(m, CU_TENSOR_MAP_DATA_TYPE_BFLOAT16, 2, const_cast<void*>(base), dims, strides, box, es,
        CU_TENSOR_MAP_INTERLEAVE_NONE, sw, promo, CU_TENSOR_MAP_FLOAT_OOB_FILL_NONE);
}

}

extern "C" void kernel_launch(void* const* d_in, const int* in_sizes, int n_in, void* d_out, int out_size) {
    (void)in_sizes; (void)n_in; (void)out_size;
    static EncodeFn enc = nullptr;
    static void* scr = nullptr;
    if (!enc) {
        void* fn = nullptr;
        cudaDriverEntryPointQueryResult qr;
        cudaGetDriverEntryPoint("cuTensorMapEncodeTiled", &fn, cudaEnableDefault, &qr);
        enc = (EncodeFn)fn;
        cudaGetSymbolAddress(&scr, g_scr);
        cudaFuncSetAttribute(fused_decode_kernel, cudaFuncAttributeMaxDynamicSharedMemorySize, SMEM_BYTES);
    }
    Maps m;
    make_map(enc, &m.kv[0], d_in[1], 64, 1048576, 64, 64, CU_TENSOR_MAP_L2_PROMOTION_NONE);
    make_map(enc, &m.kv[1], d_in[2], 64, 1048576, 64, 64, CU_TENSOR_MAP_L2_PROMOTION_NONE);
    make_map(enc, &m.qa, d_in[3], 4096, 512, 64, 64, CU_TENSOR_MAP_L2_PROMOTION_NONE);
    make_map(enc, &m.qb, d_in[7], 4096, 512, 64, 256, CU_TENSOR_MAP_L2_PROMOTION_NONE);
    make_map(enc, &m.wo[0], d_in[10], 512, 4096, 32, 64, CU_TENSOR_MAP_L2_PROMOTION_L2_128B, CU_TENSOR_MAP_SWIZZLE_64B);
    make_map(enc, &m.wo[1], d_in[4], 512, 4096, 32, 64, CU_TENSOR_MAP_L2_PROMOTION_L2_128B, CU_TENSOR_MAP_SWIZZLE_64B);
    {
        cuuint64_t dims[4] = {64, 8, 8, 2048}, strides[3] = {1024, 128, 8192};
        cuuint32_t box[4] = {64, 8, 8, 8}, es[4] = {1, 1, 1, 1};
        enc(&m.c, CU_TENSOR_MAP_DATA_TYPE_BFLOAT16, 4, d_in[6], dims, strides, box, es, CU_TENSOR_MAP_INTERLEAVE_NONE,
            CU_TENSOR_MAP_SWIZZLE_128B, CU_TENSOR_MAP_L2_PROMOTION_NONE, CU_TENSOR_MAP_FLOAT_OOB_FILL_NONE);
    }
    make_map(enc, &m.uk, d_in[8], 4096, 512, 64, 256, CU_TENSOR_MAP_L2_PROMOTION_NONE);
    make_map(enc, &m.uv, d_in[9], 4096, 512, 64, 256, CU_TENSOR_MAP_L2_PROMOTION_NONE);
    Params p;
    p.scr = (Scratch*)scr;
    p.ax = (const uint32_t*)d_in[0];
    p.bx = (const uint32_t*)d_in[5];
    p.out = (__nv_bfloat16*)d_out;
    p.wq = (const char*)d_in[3];
    fused_decode_kernel<<<128, 480, SMEM_BYTES, cudaStreamPerThread>>>(p, m);
}
```

```cpp
#include <cuda_runtime.h>
#include <cuda_bf16.h>
#include <cuda.h>
#include <stdint.h>
#include <float.h>

#define LIM 12
#define LIM0 8
#define RAMP_S 256
#define RAMP_T0 300
#define SKEW 3
#define XD0 1000
#define XDS 12
#define BSTART 3000
#define BSTAG 500
#define FIRE_T 240
#define FIRE_NS 3360
#define FIRE_W 2000
#define NLA 6
#define NLB 9
#define NSA 13
#define NSB 13
#define REC0_NS 100
#define REC_NS 1700
#define NMW 6
#define QSLEEP 1200
#define QPOLL 300
#define BPOLL 1000
#define CPOLL 700
#define DPOLL 300
#define FPOLL 300

namespace {

constexpr int CPG = 32, NW = 4;
constexpr int UPG = 8192;
constexpr int NSL = 12, SPW = NSL / NW;
constexpr int SPIN_MAX = 1 << 22;
constexpr float LOG2E = 1.4426950408889634f;
constexpr float SCALE = 0.08838834764831845f;
constexpr uint64_t EVICT_FIRST = 0x12F0000000000000ull;

constexpr int SA_SLOT = NSL * 16384;
constexpr int SA_Q    = SA_SLOT + 8 * NW * 132 * 4;
constexpr int SA_FULL = SA_Q + 8192;
constexpr int SA_EMPTY = SA_FULL + NSL * 16;
constexpr int SA_GOV  = SA_EMPTY + NSL * 8;
constexpr int SA_MBAR = SA_GOV + NSL * 8;
constexpr int SA_QBAR = SA_MBAR + 128;
constexpr int SA_META = SA_QBAR + 24;
constexpr int SA_LIM  = SA_META + NSL * 4;
constexpr int SA_CNT  = SA_LIM + 16;
constexpr int SA_END  = SA_CNT + 64;
constexpr int PROW    = 2080;
constexpr int SB_STG  = 0;
constexpr int SB_QIMG = 131072;
constexpr int SB_P    = SB_QIMG + 32 * PROW;
constexpr int SB_AL   = SB_P + 8192;
constexpr int SB_X    = SB_AL + 256;
static_assert(SB_P % 1024 == 0, "swizzle atom");
constexpr int SB_QB   = SB_X + 4352;
constexpr int NT      = 40;
constexpr int SC_FR   = NT * 4096;
constexpr int SC_FP   = SC_FR + 16384;
constexpr int SC_RED  = SB_QB + 1024;
constexpr int SB_BAR  = SC_RED + 4480;
constexpr int SB_CNT  = SB_BAR + (12 + NT) * 8;
static_assert(SC_FP + 8448 <= SB_P && 2 * (32 - NSA) <= NT && 2 * (32 - NSB) <= NT && NSA <= 16 && NSB <= 16, "projection slots");
constexpr int SB_END  = SB_CNT + 64;
constexpr int SMEM_BYTES = (SA_END > SB_END ? SA_END : SB_END);
static_assert(SMEM_BYTES <= 232448, "shared memory");

struct Scratch {
    uint4    bpart[32 * 32 * (PROW / 16)];
    uint4    apart[64 * CPG * 32];
    uint4    qimg[2 * 4096];
    uint4    qpub[64 * 32];
    uint4    frag[2][64 * 32];
    uint2    snd[32 * 32];
    uint2    aml[64 * CPG * 4];
    unsigned ctr[2][1056];
    uint2    fire[544];
    unsigned qflag[1088], bflag[1088];
};
__device__ __align__(1024) Scratch g_scr;

__device__ __forceinline__ uint32_t s2u(const void* p) { return (uint32_t)__cvta_generic_to_shared(p); }
__device__ __forceinline__ bool elect() {
    uint32_t ok;
    asm volatile("{\n.reg .pred p;\nelect.sync _|p, 0xffffffff;\nselp.u32 %0,1,0,p;\n}" : "=r"(ok));
    return ok;
}
__device__ __forceinline__ void mbar_init(uint32_t b, int c) {
    asm volatile("mbarrier.init.shared::cta.b64 [%0], %1;" ::"r"(b), "r"(c) : "memory");
}
__device__ __forceinline__ void mbar_init_fence() { asm volatile("fence.mbarrier_init.release.cluster;" ::: "memory"); }
__device__ __forceinline__ void mbar_expect(uint32_t b, uint32_t bytes) {
    asm volatile("mbarrier.arrive.expect_tx.shared::cta.b64 _, [%0], %1;" ::"r"(b), "r"(bytes) : "memory");
}
__device__ __forceinline__ void mbar_arrive(uint32_t b) {
    asm volatile("mbarrier.arrive.shared::cta.b64 _, [%0];" ::"r"(b) : "memory");
}
__device__ __forceinline__ bool mbar_test(uint32_t b, uint32_t ph) {
    uint32_t ok;
    asm volatile("{\n.reg .pred p;\nmbarrier.test_wait.parity.shared::cta.b64 p, [%1], %2;\nselp.u32 %0,1,0,p;\n}"
                 : "=r"(ok) : "r"(b), "r"(ph) : "memory");
    return ok;
}
__device__ __forceinline__ void mbar_wait(uint32_t b, uint32_t ph) {
    asm volatile("{\n.reg .pred p;\n.reg .u32 n;\nmov.u32 n, 0;\n"
                 "W: mbarrier.try_wait.parity.shared::cta.b64 p, [%0], %1;\n@p bra.uni D;\n"
                 "add.u32 n, n, 1;\nsetp.lt.u32 p, n, %2;\n@p bra.uni W;\ntrap;\nD:\n}"
                 ::"r"(b), "r"(ph), "n"(SPIN_MAX) : "memory");
}
__device__ __forceinline__ void tma2d(uint32_t dst, const CUtensorMap* map, int c0, int c1, uint32_t bar) {
    asm volatile("cp.async.bulk.tensor.2d.shared::cluster.global.mbarrier::complete_tx::bytes [%0], [%1, {%3, %4}], [%2];"
                 ::"r"(dst), "l"(map), "r"(bar), "r"(c0), "r"(c1) : "memory");
}
__device__ __forceinline__ void tma2d_ef(uint32_t dst, const CUtensorMap* map, int c0, int c1, uint32_t bar) {
    asm volatile("cp.async.bulk.tensor.2d.shared::cluster.global.mbarrier::complete_tx::bytes.L2::cache_hint [%0], [%1, {%3, %4}], [%2], %5;"
                 ::"r"(dst), "l"(map), "r"(bar), "r"(c0), "r"(c1), "l"(EVICT_FIRST) : "memory");
}
__device__ __forceinline__ void tma4d_ef(uint32_t dst, const CUtensorMap* map, int c3, uint32_t bar) {
    asm volatile("cp.async.bulk.tensor.4d.shared::cluster.global.mbarrier::complete_tx::bytes.L2::cache_hint [%0], [%1, {0, 0, 0, %3}], [%2], %4;"
                 ::"r"(dst), "l"(map), "r"(bar), "r"(c3), "l"(EVICT_FIRST) : "memory");
}
__device__ __forceinline__ void bulk_g2s(uint32_t dst, const void* src, uint32_t bytes, uint32_t bar) {
    asm volatile("cp.async.bulk.shared::cluster.global.mbarrier::complete_tx::bytes [%0], [%1], %2, [%3];"
                 ::"r"(dst), "l"(src), "r"(bytes), "r"(bar) : "memory");
}
__device__ __forceinline__ void bulk_s2g(void* dst, uint32_t src, uint32_t bytes) {
    asm volatile("cp.async.bulk.global.shared::cta.bulk_group [%0], [%1], %2;" ::"l"(dst), "r"(src), "r"(bytes) : "memory");
}
__device__ __forceinline__ void fence_async_all() { asm volatile("fence.proxy.async;" ::: "memory"); }
__device__ __forceinline__ void bar_sync(int id, int n) { asm volatile("bar.sync %0, %1;" ::"r"(id), "r"(n) : "memory"); }
__device__ __forceinline__ void bar_arrive(int id, int n) { asm volatile("bar.arrive %0, %1;" ::"r"(id), "r"(n) : "memory"); }
__device__ __forceinline__ unsigned ld_relaxed1(const void* p) {
    unsigned v;
    asm volatile("ld.relaxed.gpu.global.u32 %0, [%1];" : "=r"(v) : "l"(p) : "memory");
    return v;
}
__device__ __forceinline__ unsigned atom_inc(unsigned* p) {
    unsigned v;
    asm volatile("atom.relaxed.gpu.global.add.u32 %0, [%1], 1;" : "=r"(v) : "l"(p) : "memory");
    return v;
}
__device__ __forceinline__ uint4 ld_b128(const void* p) {
    uint4 v;
    asm volatile("{\n.reg .b128 t;\nld.relaxed.gpu.global.b128 t, [%4];\nmov.b128 {%0,%1,%2,%3}, t;\n}"
                 : "=r"(v.x), "=r"(v.y), "=r"(v.z), "=r"(v.w) : "l"(p) : "memory");
    return v;
}
__device__ __forceinline__ void st_b128(void* p, uint4 v) {
    asm volatile("{\n.reg .b128 t;\nmov.b128 t, {%1,%2,%3,%4};\nst.relaxed.gpu.global.b128 [%0], t;\n}"
                 ::"l"(p), "r"(v.x), "r"(v.y), "r"(v.z), "r"(v.w) : "memory");
}
__device__ __forceinline__ uint2 ld_b64(const void* p) {
    uint2 v;
    asm volatile("{\n.reg .b64 a;\nld.relaxed.gpu.global.b64 a, [%2];\nmov.b64 {%0,%1}, a;\n}" : "=r"(v.x), "=r"(v.y) : "l"(p) : "memory");
    return v;
}
__device__ __forceinline__ void st_b64(void* p, uint32_t a, uint32_t b) {
    asm volatile("{\n.reg .b64 t;\nmov.b64 t, {%1,%2};\nst.relaxed.gpu.global.b64 [%0], t;\n}" ::"l"(p), "r"(a), "r"(b) : "memory");
}
__device__ __forceinline__ unsigned ld_acquire(const unsigned* p) {
    unsigned v;
    asm volatile("ld.acquire.gpu.global.u32 %0, [%1];" : "=r"(v) : "l"(p) : "memory");
    return v;
}
__device__ __forceinline__ void st_release(unsigned* p, unsigned v) {
    asm volatile("st.release.gpu.global.u32 [%0], %1;" ::"l"(p), "r"(v) : "memory");
}
__device__ __forceinline__ void ldsm4(uint32_t (&r)[4], uint32_t a) {
    asm volatile("ldmatrix.sync.aligned.m8n8.x4.shared.b16 {%0,%1,%2,%3}, [%4];"
                 : "=r"(r[0]), "=r"(r[1]), "=r"(r[2]), "=r"(r[3]) : "r"(a) : "memory");
}
__device__ __forceinline__ void ldsm4t(uint32_t (&r)[4], uint32_t a) {
    asm volatile("ldmatrix.sync.aligned.m8n8.x4.trans.shared.b16 {%0,%1,%2,%3}, [%4];"
                 : "=r"(r[0]), "=r"(r[1]), "=r"(r[2]), "=r"(r[3]) : "r"(a) : "memory");
}
__device__ __forceinline__ uint4 lds128(uint32_t a) {
    uint4 v;
    asm volatile("ld.shared.v4.u32 {%0, %1, %2, %3}, [%4];" : "=r"(v.x), "=r"(v.y), "=r"(v.z), "=r"(v.w) : "r"(a) : "memory");
    return v;
}
__device__ __forceinline__ float2 lds64f(uint32_t a) {
    float2 v;
    asm volatile("ld.shared.v2.f32 {%0, %1}, [%2];" : "=f"(v.x), "=f"(v.y) : "r"(a) : "memory");
    return v;
}
__device__ __forceinline__ uint32_t lds32(uint32_t a) {
    uint32_t v;
    asm volatile("ld.shared.u32 %0, [%1];" : "=r"(v) : "r"(a) : "memory");
    return v;
}
__device__ __forceinline__ void sts32(uint32_t a, uint32_t v) { asm volatile("st.shared.u32 [%0], %1;" ::"r"(a), "r"(v) : "memory"); }
__device__ __forceinline__ void mma16816(float (&d)[4], const uint32_t (&a)[4], uint32_t b0, uint32_t b1) {
    asm volatile("mma.sync.aligned.m16n8k16.row.col.f32.bf16.bf16.f32 {%0,%1,%2,%3}, {%4,%5,%6,%7}, {%8,%9}, {%0,%1,%2,%3};"
                 : "+f"(d[0]), "+f"(d[1]), "+f"(d[2]), "+f"(d[3])
                 : "r"(a[0]), "r"(a[1]), "r"(a[2]), "r"(a[3]), "r"(b0), "r"(b1));
}
__device__ __forceinline__ uint32_t prmt0(uint32_t a, uint32_t sel) {
    uint32_t d;
    asm volatile("prmt.b32 %0, %1, 0, %2;" : "=r"(d) : "r"(a), "r"(sel));
    return d;
}
__device__ __forceinline__ unsigned gt() {
    unsigned t;
    asm volatile("mov.u32 %0, %globaltimer_lo;" : "=r"(t));
    return t;
}
__device__ __forceinline__ unsigned clk32() {
    unsigned c;
    asm volatile("mov.u32 %0, %clock;" : "=r"(c));
    return c;
}
__device__ __forceinline__ float ex2(float x) {
    float y;
    asm("ex2.approx.ftz.f32 %0, %1;" : "=f"(y) : "f"(x));
    return y;
}
__device__ __forceinline__ float bf16r(float x) { return __bfloat162float(__float2bfloat16_rn(x)); }
__device__ __forceinline__ uint32_t packbf(float lo, float hi) {
    uint32_t r;
    asm("cvt.rn.bf16x2.f32 %0, %1, %2;" : "=r"(r) : "f"(hi), "f"(lo));
    return r;
}
__device__ __forceinline__ float bflo(uint32_t v) { return __uint_as_float(v << 16); }
__device__ __forceinline__ float bfhi(uint32_t v) { return __uint_as_float(v & 0xffff0000u); }
__device__ __forceinline__ uint32_t tagf(float v, uint32_t t8) { return (__float_as_uint(v) & 0xffffff00u) | t8; }
__device__ __forceinline__ float shx(float v, int m) { return __shfl_xor_sync(0xffffffffu, v, m); }

__device__ __forceinline__ float warp_max(float v) {
    int i = __float_as_int(v);
    i = __reduce_max_sync(0xffffffffu, i ^ ((i >> 31) & 0x7fffffff));
    return __int_as_float(i ^ ((i >> 31) & 0x7fffffff));
}

__device__ __forceinline__ uint64_t gdesc(uint32_t addr, uint32_t lbo, uint32_t sbo) {
    return (uint64_t)((addr & 0x3ffff) >> 4) | ((uint64_t)(lbo >> 4) << 16) | ((uint64_t)(sbo >> 4) << 32) | (1ull << 62);
}
__device__ __forceinline__ void wg_fence() { asm volatile("wgmma.fence.sync.aligned;" ::: "memory"); }
__device__ __forceinline__ void wg_commit() { asm volatile("wgmma.commit_group.sync.aligned;" ::: "memory"); }
__device__ __forceinline__ void wg_wait0() { asm volatile("wgmma.wait_group.sync.aligned 0;" ::: "memory"); }
template <int N> __device__ __forceinline__ void reg_fence(float (&r)[N]) {
#pragma unroll
    for (int i = 0; i < N; i++) asm volatile("" : "+f"(r[i])::"memory");
}
#define F8(a, o) "+f"(a[o]), "+f"(a[o + 1]), "+f"(a[o + 2]), "+f"(a[o + 3]), "+f"(a[o + 4]), "+f"(a[o + 5]), "+f"(a[o + 6]), "+f"(a[o + 7])
#define F32(a, o) F8(a, o), F8(a, o + 8), F8(a, o + 16), F8(a, o + 24)
__device__ __forceinline__ void wgmma_n64_ss(float (&d)[32], uint64_t da, uint64_t db, int scale_d) {
    asm volatile(
        "{\n.reg .pred p;\nsetp.ne.b32 p, %34, 0;\n"
        "wgmma.mma_async.sync.aligned.m64n64k16.f32.bf16.bf16 "
        "{%0,%1,%2,%3,%4,%5,%6,%7,%8,%9,%10,%11,%12,%13,%14,%15,%16,%17,%18,%19,%20,%21,%22,%23,%24,%25,%26,%27,%28,%29,%30,%31},"
        " %32, %33, p, 1, 1, 0, 0;\n}"
        : F32(d, 0) : "l"(da), "l"(db), "r"(scale_d));
}
__device__ __forceinline__ void wgmma_n32_ts(float (&d)[16], uint64_t da, uint64_t db) {
    asm volatile(
        "{\n.reg .pred p;\nsetp.ne.b32 p, 1, 0;\n"
        "wgmma.mma_async.sync.aligned.m64n32k16.f32.bf16.bf16 "
        "{%0,%1,%2,%3,%4,%5,%6,%7,%8,%9,%10,%11,%12,%13,%14,%15}, %16, %17, p, 1, 1, 1, 0;\n}"
        : F8(d, 0), F8(d, 8) : "l"(da), "l"(db));
}

struct Params {
    Scratch* scr;
    const uint32_t *ax, *bx;
    const char* wq;
    __nv_bfloat16* out;
};
struct Maps { CUtensorMap kv[2], qa, qb, wo[2], c, uk, uv; };

__device__ __forceinline__ void wait_flags(const unsigned* flags, unsigned tag, int lane) {
    for (int i = 0; !__all_sync(0xffffffffu, ld_acquire(flags + lane * 8) == tag); i++) {
        if (i > SPIN_MAX) __trap();
        __nanosleep(BPOLL);
    }
    __syncwarp();
}
__device__ __forceinline__ void load_slice(uint32_t dst, const CUtensorMap* map, int r, uint32_t bar) {
    mbar_expect(bar, 131072);
#pragma unroll
    for (int x = 0; x < 4; x++) tma2d_ef(dst + x * 32768, map, r * 128 + (x & 1) * 64, (x >> 1) * 256, bar);
}
__device__ __forceinline__ void gemv_slice(uint32_t sb, int warp, int lane) {
    const int g = lane >> 2, tq = lane & 3;
    float d[4][4];
#pragma unroll
    for (int i = 0; i < 4; i++) d[i][0] = d[i][1] = d[i][2] = d[i][3] = 0.f;
    const uint32_t wb = sb + SB_STG + (warp >> 2) * 32768 + ((lane & 7) + 8 * (lane >> 4)) * 128 +
                        (((2 * (warp & 3) + ((lane >> 3) & 1)) ^ (lane & 7)) << 4);
    const uint32_t xb = sb + SB_X + ((g & 3) * 264 + tq) * 4;
#pragma unroll 1
    for (int k8 = 0; k8 < 4; k8++) {
        uint32_t a[8][4], b[8][2];
#pragma unroll
        for (int ks = 0; ks < 8; ks++) {
            ldsm4t(a[ks], wb + (k8 >> 1) * 65536 + (k8 & 1) * 16384 + ks * 2048);
            b[ks][0] = lds32(xb + k8 * 256 + ks * 32);
            b[ks][1] = lds32(xb + k8 * 256 + ks * 32 + 16);
        }
#pragma unroll
        for (int ks = 0; ks < 8; ks++) mma16816(d[ks & 3], a[ks], b[ks][0], b[ks][1]);
    }
    const float y0 = ((d[0][0] + d[1][0]) + (d[2][0] + d[3][0])) + ((d[0][1] + d[1][1]) + (d[2][1] + d[3][1]));
    const float y1 = ((d[0][2] + d[1][2]) + (d[2][2] + d[3][2])) + ((d[0][3] + d[1][3]) + (d[2][3] + d[3][3]));
    if (tq < 2) {
        sts32(sb + SB_QB + (tq * 128 + warp * 16 + g) * 4, __float_as_uint(y0));
        sts32(sb + SB_QB + (tq * 128 + warp * 16 + 8 + g) * 4, __float_as_uint(y1));
    }
}
__device__ __forceinline__ uint32_t wo_lane(uint32_t sb, int lane) {
    return sb + ((lane & 7) + 8 * (lane >> 4)) * 64 + ((((lane >> 3) & 1) ^ ((lane >> 1) & 3)) << 4);
}

template <int NP, int NTHR> __device__ __forceinline__ float2 sum_parts(uint32_t q, float x, float y) {
    asm volatile("bar.sync 5, %0;" ::"n"(NTHR) : "memory");
    float2 p[NP];
#pragma unroll
    for (int i = 0; i < NP; i++) p[i] = lds64f(q + i * 320);
    p[0].x += x; p[0].y += y;
#pragma unroll
    for (int d = 1; d < NP; d *= 2)
#pragma unroll
        for (int i = 0; i + d < NP; i += 2 * d) { p[i].x += p[i + d].x; p[i].y += p[i + d].y; }
    return p[0];
}

__device__ __forceinline__ void latent_branch(const Params& P, const Maps& M, uint8_t* sm) {
    const uint32_t sb = s2u(sm);
    const int tid = threadIdx.x, lane = tid & 31, warp = tid >> 5, g = lane >> 2, tq = lane & 3, r = blockIdx.x >> 2;
    const uint32_t bar_w = sb + SB_BAR + 16, bar_x = sb + SB_BAR + 24;
    const unsigned tag = lds32(sb + SB_CNT) + 1;
    Scratch* const S = P.scr;
    const float* yb = reinterpret_cast<const float*>(sm + SB_QB);
    float* xs = reinterpret_cast<float*>(sm + SB_X);
    const int crow0 = (r >> 4) * 8192 + (r & 15) * 64;
    {
        uint32_t* xh = reinterpret_cast<uint32_t*>(sm + SB_X) + tid;
        xh[0] = __ldg(P.bx + tid); xh[264] = 0; xh[528] = __ldg(P.bx + 256 + tid); xh[792] = 0;
        bar_sync(0, 256);
        mbar_wait(bar_w, 0);
        gemv_slice(sb, warp, lane);
        bar_sync(0, 256);
        if (tid == 0) load_slice(sb + SB_STG, &M.uk, r, bar_w);
        uint32_t qb[8][2];
#pragma unroll
        for (int ks = 0; ks < 8; ks++) {
            const float2 a = *reinterpret_cast<const float2*>(yb + (g & 1) * 128 + ks * 16 + 2 * tq);
            const float2 b = *reinterpret_cast<const float2*>(yb + (g & 1) * 128 + ks * 16 + 8 + 2 * tq);
            qb[ks][0] = packbf(a.x, a.y);
            qb[ks][1] = packbf(b.x, b.y);
        }
        mbar_wait(bar_w, 1);
        const uint32_t wb = sb + SB_STG + (warp >> 2) * 65536 + ((warp & 3) * 64 + (lane & 15)) * 128;
#pragma unroll 1
        for (int mt = 0; mt < 4; mt++) {
            float d[4] = {0.f, 0.f, 0.f, 0.f};
#pragma unroll
            for (int ks = 0; ks < 8; ks++) {
                uint32_t a[4];
                ldsm4(a, wb + (ks >> 2) * 32768 + mt * 2048 + (((2 * (ks & 3) + (lane >> 4)) ^ (lane & 7)) << 4));
                mma16816(d, a, qb[ks][0], qb[ks][1]);
            }
            if (tq == 0) {
                const int c = warp * 64 + mt * 16 + g;
                xs[c] = d[0]; xs[512 + c] = d[1]; xs[c + 8] = d[2]; xs[512 + c + 8] = d[3];
            }
        }
        bar_sync(0, 256);
        if (tid == 32) {
#pragma unroll
            for (int t = 0; t < 2; t++) {
                mbar_expect(sb + SB_BAR + t * 8, 65536);
                tma4d_ef(sb + SB_STG + t * 65536, &M.c, (crow0 >> 3) + t * 128, sb + SB_BAR + t * 8);
            }
        }
        const int b = tid >> 7, lo = (tid >> 6) & 1, ch = tid & 63;
        float v[8];
#pragma unroll
        for (int i = 0; i < 8; i++) {
            const float x = xs[b * 512 + ch * 8 + i];
            v[i] = lo ? x - bf16r(x) : x;
        }
        const int row = 16 * (r >> 3) + (r & 7) + 8 * lo;
        S->qimg[b * 4096 + (ch >> 3) * 512 + row * 8 + ((ch & 7) ^ (r & 7))] =
            make_uint4(packbf(v[0], v[1]), packbf(v[2], v[3]), packbf(v[4], v[5]), packbf(v[6], v[7]));
        bar_sync(0, 256);
        if (warp == 0) {
            if (lane == 0) { __threadfence(); st_release(S->qflag + r * 8, tag); }
            wait_flags(S->qflag, tag, lane);
            if (lane == 0) {
                fence_async_all();
                mbar_expect(bar_x, 65536);
                bulk_g2s(sb + SB_QIMG, S->qimg + (r >> 4) * 4096, 65536, bar_x);
            }
        }
        mbar_wait(bar_x, 0);
    }
    {
        const int wg = warp >> 2;
        float acc[4][16];
#pragma unroll
        for (int i = 0; i < 64; i++) acc[i >> 4][i & 15] = 0.f;
        const int head = (warp & 3) * 8 + g;
        const uint32_t pa = sb + SB_P + wg * 4096;
        float* al = reinterpret_cast<float*>(sm + SB_AL) + wg * 32;
        float m = -FLT_MAX, l = 0.f;
#pragma unroll 1
        for (int t = 0; t < 8; t++) {
            const uint32_t stg = sb + SB_STG + (t & 1) * 65536;
            mbar_wait(sb + SB_BAR + (t & 1) * 8, (t >> 1) & 1);
            float s[32];
            uint32_t qa = sb + SB_QIMG;
            asm volatile("" : "+r"(qa));
            wg_fence();
#pragma unroll
            for (int k = 0; k < 32; k++) {
                const uint32_t off = (k >> 2) * 8192 + (k & 3) * 32;
                wgmma_n64_ss(s, gdesc(qa + off, 16, 1024), gdesc(stg + (k >> 2) * 1024 + (k & 3) * 32, 16, 8192), k > 0);
            }
            wg_commit();
            wg_wait0();
            reg_fence(s);
            float p[16], mx = m;
#pragma unroll
            for (int i = 0; i < 8; i++) {
                p[2 * i] = bf16r(bf16r(s[4 * i] + s[4 * i + 2]) * SCALE);
                p[2 * i + 1] = bf16r(bf16r(s[4 * i + 1] + s[4 * i + 3]) * SCALE);
                mx = fmaxf(mx, fmaxf(p[2 * i], p[2 * i + 1]));
            }
            mx = fmaxf(mx, shx(mx, 1));
            mx = fmaxf(mx, shx(mx, 2));
            const float alpha = ex2((m - mx) * LOG2E);
            m = mx;
            float sum = 0.f;
#pragma unroll
            for (int i = 0; i < 8; i++) {
                const float a = ex2((p[2 * i] - mx) * LOG2E), b = ex2((p[2 * i + 1] - mx) * LOG2E);
                sum += a + b;
                sts32(pa + head * 128 + ((i ^ g) << 4) + tq * 4, packbf(a, b));
            }
            l = fmaf(l, alpha, sum);
            if (tq == 0) al[head] = alpha;
            asm volatile("fence.proxy.async.shared::cta;" ::: "memory");
            bar_sync(1 + wg, 128);
#pragma unroll
            for (int j = 0; j < 4; j++) {
                const float2 a = *reinterpret_cast<const float2*>(al + 8 * j + 2 * tq);
#pragma unroll
                for (int i = 0; i < 4; i++) { acc[i][4 * j] *= a.x; acc[i][4 * j + 1] *= a.y; acc[i][4 * j + 2] *= a.x; acc[i][4 * j + 3] *= a.y; }
            }
#pragma unroll
            for (int i = 0; i < 4; i++) reg_fence(acc[i]);
            wg_fence();
#pragma unroll
            for (int kk = 0; kk < 4; kk++)
#pragma unroll
                for (int i = 0; i < 4; i++)
                    wgmma_n32_ts(acc[i], gdesc(stg + (wg * 4 + i) * 1024 + kk * 16384, 1024, 8192), gdesc(pa + kk * 32, 16, 1024));
            wg_commit();
            wg_wait0();
#pragma unroll
            for (int i = 0; i < 4; i++) reg_fence(acc[i]);
            bar_sync(0, 256);
            if (tid == 0) {
                if (t + 2 < 8) {
                    const uint32_t bar = sb + SB_BAR + (t & 1) * 8;
                    mbar_expect(bar, 65536);
                    tma4d_ef(stg, &M.c, (crow0 >> 3) + (t + 2) * 128, bar);
                }
                if (t == 7) load_slice(sb + SB_STG, &M.uv, r, bar_w);
            }
        }
        float* dst = reinterpret_cast<float*>(sm + SB_QIMG + 2 * tq * PROW) + wg * 256 + (warp & 3) * 16 + g;
#pragma unroll
        for (int i = 0; i < 64; i++)
            dst[(((i >> 2) & 3) * 8 + (i & 1)) * (PROW / 4) + (i >> 4) * 64 + (i & 2) * 4] = acc[i >> 4][i & 15];
        l += shx(l, 1); l += shx(l, 2);
        if (wg == 0 && tq < 2) *reinterpret_cast<float4*>(sm + SB_QIMG + head * PROW + 2048 + tq * 16) = make_float4(m, l, 0.f, 0.f);
        asm volatile("fence.proxy.async.shared::cta;" ::: "memory");
        bar_sync(0, 256);
        if (warp == 0) {
            bulk_s2g(S->bpart + (lane * 32 + r) * (PROW / 16), sb + SB_QIMG + lane * PROW, PROW);
            asm volatile("cp.async.bulk.commit_group;" ::: "memory");
            asm volatile("cp.async.bulk.wait_group 0;" ::: "memory");
            fence_async_all();
            __threadfence();
            __syncwarp();
            if (lane == 0) st_release(S->bflag + r * 8, tag);
            wait_flags(S->bflag, tag, lane);
            if (lane == 0) {
                fence_async_all();
                mbar_expect(bar_x, 32 * PROW);
                bulk_g2s(sb + SB_QIMG, S->bpart + r * 32 * (PROW / 16), 32 * PROW, bar_x);
            }
        }
    }
    {
        const int b = tid >> 7, c4 = tid & 127;
        mbar_wait(bar_x, 1);
        const float2 ml = *reinterpret_cast<const float2*>(sm + SB_QIMG + (b * 16 + (lane & 15)) * PROW + 2048);
        float MM = ml.x;
        MM = fmaxf(MM, shx(MM, 1)); MM = fmaxf(MM, shx(MM, 2)); MM = fmaxf(MM, shx(MM, 4)); MM = fmaxf(MM, shx(MM, 8));
        const float e = ex2((ml.x - MM) * LOG2E);
        float L = e * ml.y;
        L += shx(L, 1); L += shx(L, 2); L += shx(L, 4); L += shx(L, 8);
        const float wgt = e / L;
        float4 o = make_float4(0.f, 0.f, 0.f, 0.f);
#pragma unroll 4
        for (int i = 0; i < 16; i++) {
            const float w = __shfl_sync(0xffffffffu, wgt, i);
            const float4 v = *reinterpret_cast<const float4*>(sm + SB_QIMG + (b * 16 + i) * PROW + c4 * 16);
            o.x = fmaf(w, v.x, o.x); o.y = fmaf(w, v.y, o.y); o.z = fmaf(w, v.z, o.z); o.w = fmaf(w, v.w, o.w);
        }
        uint32_t* xh = reinterpret_cast<uint32_t*>(xs);
        const uint32_t h0 = packbf(o.x, o.y), h1 = packbf(o.z, o.w);
        *reinterpret_cast<uint2*>(xh + (2 * b) * 264 + c4 * 2) = make_uint2(h0, h1);
        *reinterpret_cast<uint2*>(xh + (2 * b + 1) * 264 + c4 * 2) =
            make_uint2(packbf(o.x - bflo(h0), o.y - bfhi(h0)), packbf(o.z - bflo(h1), o.w - bfhi(h1)));
        bar_sync(0, 256);
        mbar_wait(bar_w, 0);
        gemv_slice(sb, warp, lane);
        bar_sync(0, 256);
        if (tid < 64) {
            const float* y = yb + warp * 128 + 16 * g + 2 * tq;
            st_b128(S->frag[0] + (warp * 32 + r) * 32 + lane, make_uint4(packbf(y[0], y[1]), tag, packbf(y[8], y[9]), tag));
        }
    }
}

__global__ void __launch_bounds__(480, 1)
fused_decode_kernel(const Params P, const __grid_constant__ Maps M) {
    extern __shared__ __align__(1024) uint8_t sm[];
    const uint32_t sb = s2u(sm);
    const int tid = threadIdx.x, lane = tid & 31, bx = blockIdx.x;
    asm volatile("{\n.reg .pred p;\nsetp.lt.u32 p, %1, 256;\n@p prefetch.global.L2 [%0];\n}"
                 ::"l"(P.wq + (unsigned)(((bx & 1) * 256 + tid) * 8192 + (bx >> 1) * 128)), "r"(tid) : "memory");
    const int warp = __shfl_sync(0xffffffffu, tid >> 5, 0);
    const int g = lane >> 2, tq = lane & 3;
    Scratch* const S = P.scr;

    if (!(bx & 1)) {
        const int grp = (bx >> 1) & 1, crk = bx >> 2;
        auto issue = [&](int slot, unsigned tk, int v) {
            const uint32_t full = sb + SA_FULL + slot * 16 + v * 8;
            mbar_expect(full, 8192);
            tma2d_ef(sb + slot * 16384 + v * 8192, &M.kv[v], 0, (grp * UPG + tk) * 64, full);
        };
        if (warp >= 8) {
            const int w = warp - 8;
            if (w >= NW) {
                if (w == NW && !(bx & 15)) asm volatile("prefetch.global.L2 [%0];" ::"l"(((lane & 16) ? P.bx : P.ax) + (lane & 15) * 32) : "memory");
                return;
            }
            const bool one = elect();
            if (one) {
                mbar_init(sb + SA_FULL + w * 16, 1);
                mbar_init_fence();
                sts32(sb + SA_META + w * 4, 0);
                if (w < SKEW) issue(w, w * CPG + crk, 0);
#pragma unroll
                for (int i = 0; i < SPW; i++) {
                    if (i) mbar_init(sb + SA_FULL + (w + i * NW) * 16, 1);
                    mbar_init(sb + SA_FULL + (w + i * NW) * 16 + 8, 1);
                    mbar_init(sb + SA_GOV + (w + i * NW) * 8, 1);
                    mbar_init(sb + SA_EMPTY + (w + i * NW) * 8, 2);
                    mbar_arrive(sb + SA_EMPTY + (w + i * NW) * 8);
                }
                if (w < SKEW) mbar_arrive(sb + SA_EMPTY + w * 8);
                sts32(sb + SA_LIM + w * 4, LIM);
                mbar_init_fence();
            }
            __syncwarp();
            bar_arrive(2, (NW + 1) * 32);
            bar_arrive(1, (2 * NW + 2) * 32);
            unsigned c = 0;
            unsigned* const ctr = S->ctr[grp] + lane;
            int slot = w;
            uint32_t eph = 0;
#pragma unroll 1
            for (int n = 0;; n++) {
                unsigned tk = (n * NW + w) * CPG + crk, own = 0;
                if (n >= SPW) {
                    own = __shfl_sync(0xffffffffu, c, 0);
                    tk = own % UPG + NSL * CPG;
                }
                mbar_wait(sb + SA_EMPTY + slot * 8, eph);
                if (tk >= UPG) {
                    if (one) {
                        sts32(sb + SA_LIM + w * 4, 0);
                        sts32(sb + SA_META + slot * 4, 32);
                        mbar_arrive(sb + SA_FULL + slot * 16);
                        asm volatile("red.relaxed.gpu.global.add.u32 [%0], %1;" ::"l"(S->ctr[grp]), "n"(SPW - 1) : "memory");
                    }
                    return;
                }
                if (one && (n || w >= SKEW)) {
                    sts32(sb + SA_META + slot * 4, tk >> 8);
                    issue(slot, tk, 0);
                    if (UPG - FIRE_T - tk < 16) st_b64(S->fire + grp * 16 + (UPG - FIRE_T - tk), gt(), own / UPG + 1);
                }
                if (n >= SPW - 1 && lane == 0) c = atom_inc(ctr);
                mbar_wait(sb + SA_GOV + slot * 8, eph);
                if (one) issue(slot, tk, 1);
                slot += NW;
                if (slot >= NSL) { slot -= NSL; eph ^= 1; }
                __syncwarp();
            }
        }
        if (warp == 0) {
            bool busy = lane < 2 * SKEW && !(lane & 1);
            uint32_t par = busy ? 0 : 1;
            int slot = SKEW;
            bool first = true;
            const unsigned c0 = clk32() + RAMP_T0;
            const int own = lane >= 2 * NSL ? -1 : ((lane >> 1) + (lane & 1) * SKEW) % NSL;
            const uint32_t fb = sb + SA_FULL + lane * 8, lw = sb + SA_LIM + ((lane >> 1) % NW) * 4;
            const uint32_t go = sb + ((lane & 1) ? SA_GOV : SA_EMPTY) + (lane >> 1) * 8;
            bar_sync(2, (NW + 1) * 32);
#pragma unroll 1
            for (int it = 0; it < SPIN_MAX; it++) {
                bool ok = true;
                if (busy) ok = mbar_test(fb, par);
                int lim = lds32(lw);
                if (first) lim = min(LIM0, SKEW + max((int)(clk32() - c0), 0) / RAMP_S);
                busy = busy && !ok && lim;
                const int n = __popc(__ballot_sync(0xffffffffu, busy));
                if (!__any_sync(0xffffffffu, lim)) return;
                const bool mine = own == slot && lim;
                if (!__any_sync(0xffffffffu, mine && (busy || n > lim - 2))) {
                    if (mine) { mbar_arrive(go); busy = true; par ^= 1; }
                    if (++slot == NSL) { slot = 0; first = false; }
                    it = 0;
                }
            }
            __trap();
        }
        {
            int w3 = warp;
            asm volatile("" : "+r"(w3));
            if (w3 == 3) return;
        }
        if (warp == 1) {
            const uint4* const qsrc = S->qpub + grp * 1024 + lane;
            uint2* const qdst = reinterpret_cast<uint2*>(sm + SA_Q) + lane;
            const unsigned epoch = ld_relaxed1(S->ctr[grp]) / UPG;
            if (lane == 0) {
                mbar_init(sb + SA_QBAR, 32);
                mbar_init(sb + SA_QBAR + 8, 32);
                mbar_init(sb + SA_QBAR + 16, 32);
#pragma unroll
                for (int i = 0; i < 8; i++) { mbar_init(sb + SA_MBAR + i * 16, NW); mbar_init(sb + SA_MBAR + i * 16 + 8, 1); }
                mbar_init_fence();
                sts32(sb + SA_CNT, epoch);
            }
            __syncwarp();
            bar_arrive(1, (2 * NW + 2) * 32);
            __nanosleep(QSLEEP);
            for (int it = 0;; it++) {
                const uint4 u = ld_b128(qsrc);
                if (__all_sync(0xffffffffu, u.y == epoch + 1)) { qdst[0] = make_uint2(u.x, u.z); break; }
                if (it > SPIN_MAX) __trap();
            }
            mbar_arrive(sb + SA_QBAR);
#pragma unroll 1
            for (int h = 0, it = 0; h < 32; it++) {
                uint4 v[8];
                bool ok = true;
#pragma unroll
                for (int k = 0; k < 8; k++) v[k] = ld_b128(qsrc + (h + k) * 32);
#pragma unroll
                for (int k = 0; k < 8; k++) { ok = ok && v[k].y == epoch + 1; qdst[(h + k) * 32] = make_uint2(v[k].x, v[k].z); }
                if (__all_sync(0xffffffffu, ok)) {
                    if (!h) mbar_arrive(sb + SA_QBAR + 8);
                    h += 8;
                } else {
                    __nanosleep(QPOLL);
                }
                if (it > SPIN_MAX) __trap();
            }
            mbar_arrive(sb + SA_QBAR + 16);
            return;
        }
        bar_sync(1, (2 * NW + 2) * 32);
        if (warp == 2) {
            const uint32_t t8 = (lds32(sb + SA_CNT) + 1) & 0xffu;
            uint4* dst = S->apart + (grp * 32 * CPG + crk) * 32 + lane;
            uint2* dml = S->aml + (grp * 32 * CPG + crk) * 4 + (lane & 3);
#pragma unroll
            for (int k = 0; k < 4; k++) st_b64(dml + (k * 8 + (lane >> 2)) * (CPG * 4), 0, t8 ^ 0x80u);
            __syncwarp();
#pragma unroll 1
            for (int h = 0; h < 32; h++, dst += CPG * 32, dml += CPG * 4) {
                const float* s0 = reinterpret_cast<const float*>(sm + SA_SLOT) + (h & 7) * (NW * 132);
                mbar_wait(sb + SA_MBAR + (h & 7) * 16, (h >> 3) & 1);
                float2 ml[NW];
                float4 v[NW];
#pragma unroll
                for (int w = 0; w < NW; w++) {
                    ml[w] = *reinterpret_cast<const float2*>(s0 + w * 132 + 128);
                    v[w] = *reinterpret_cast<const float4*>(s0 + w * 132 + lane * 4);
                }
                const float MM = fmaxf(fmaxf(ml[0].x, ml[1].x), fmaxf(ml[2].x, ml[3].x));
                float e[NW];
#pragma unroll
                for (int w = 0; w < NW; w++) e[w] = ex2((ml[w].x - MM) * LOG2E);
                st_b128(dst, make_uint4(tagf(fmaf(e[0], v[0].x, e[1] * v[1].x) + fmaf(e[2], v[2].x, e[3] * v[3].x), t8),
                                        __float_as_uint(fmaf(e[0], v[0].y, e[1] * v[1].y) + fmaf(e[2], v[2].y, e[3] * v[3].y)),
                                        __float_as_uint(fmaf(e[0], v[0].z, e[1] * v[1].z) + fmaf(e[2], v[2].z, e[3] * v[3].z)),
                                        __float_as_uint(fmaf(e[0], v[0].w, e[1] * v[1].w) + fmaf(e[2], v[2].w, e[3] * v[3].w))));
                if (lane < 4) st_b64(dml, __float_as_uint(MM), tagf(fmaf(e[0], ml[0].y, e[1] * ml[1].y) + fmaf(e[2], ml[2].y, e[3] * ml[3].y), t8));
                if (h == 27 || h == 28) st_b128(dst + 3 * CPG * 32, make_uint4(t8 ^ 0x80u, 0, 0, 0));
                __syncwarp();
                if (lane == 0) mbar_arrive(sb + SA_MBAR + (h & 7) * 16 + 8);
            }
            return;
        }
        const int cw = warp - 4;
        uint32_t koff[4], voff[4];
#pragma unroll
        for (int i = 0; i < 4; i++) {
            koff[i] = ((lane & 7) + 8 * ((lane >> 3) & 1)) * 128 + (((2 * i + (lane >> 4)) ^ (lane & 7)) << 4);
            voff[i] = ((lane & 7) + 8 * (lane >> 4)) * 128 + (((2 * i + ((lane >> 3) & 1)) ^ (lane & 7)) << 4);
        }
        uint32_t psel[4][2];
#pragma unroll
        for (int i = 0; i < 4; i++) {
            psel[i][0] = (g >> 1) != i ? 0x4444u : (g & 1) ? 0x1044u : 0x4410u;
            psel[i][1] = (g >> 1) != i ? 0x4444u : (g & 1) ? 0x3244u : 0x4432u;
        }
        uint32_t qf[4][2];
        auto load_q = [&](int pl) {
            const uint32_t q = sb + SA_Q + pl * 256 + ((g & 1) * 32 + tq) * 4;
#pragma unroll
            for (int ks = 0; ks < 4; ks++) { qf[ks][0] = lds32(q + ks * 32); qf[ks][1] = lds32(q + ks * 32 + 16); }
        };
        mbar_wait(sb + SA_QBAR, 0);
        load_q(0);
        float acc[4][4], m = -FLT_MAX, l = 0.f, ls = 0.f;
#pragma unroll
        for (int i = 0; i < 4; i++) acc[i][0] = acc[i][1] = acc[i][2] = acc[i][3] = 0.f;
        int slot = cw, cur = 0;
        uint32_t ph = 0;
#pragma unroll 1
        for (;;) {
            mbar_wait(sb + SA_FULL + slot * 16, ph);
            const int pl = lds32(sb + SA_META + slot * 4);
            if (pl != cur) {
#pragma unroll 1
                do {
                    float* s0 = reinterpret_cast<float*>(sm + SA_SLOT) + ((cur & 7) * NW + cw) * 132;
                    float* sw = s0 + tq * 16 + (g >> 1) * 4 + (g & 1);
                    sw[0] = (acc[0][0] + acc[1][0]) + (acc[2][0] + acc[3][0]);
                    sw[2] = (acc[0][2] + acc[1][2]) + (acc[2][2] + acc[3][2]);
                    sw[64] = (acc[0][1] + acc[1][1]) + (acc[2][1] + acc[3][1]);
                    sw[66] = (acc[0][3] + acc[1][3]) + (acc[2][3] + acc[3][3]);
                    if (lane == 0) *reinterpret_cast<float2*>(s0 + 128) = make_float2(m, ls);
                    __syncwarp();
                    if (lane == 0) mbar_arrive(sb + SA_MBAR + (cur & 7) * 16);
                    if (++cur == 32) return;
#pragma unroll
                    for (int i = 0; i < 4; i++) acc[i][0] = acc[i][1] = acc[i][2] = acc[i][3] = 0.f;
                    m = -FLT_MAX; l = ls = 0.f;
                    mbar_wait(sb + SA_MBAR + (cur & 7) * 16 + 8, ((cur >> 3) & 1) ^ 1);
                    if (cur == 1 || cur == 8) mbar_wait(sb + SA_QBAR + 8 + (cur & 8), 0);
                } while (cur != pl);
                load_q(pl);
            }
            float s4[4][4];
            const uint32_t kb = sb + slot * 16384;
#pragma unroll
            for (int j = 0; j < 4; j++) {
                s4[j][0] = s4[j][1] = s4[j][2] = s4[j][3] = 0.f;
                const bool on = (g >> 1) == j;
#pragma unroll
                for (int ks = 0; ks < 4; ks++) {
                    uint32_t a[4];
                    ldsm4(a, kb + j * 2048 + koff[ks]);
                    mma16816(s4[j], a, on ? qf[ks][0] : 0u, on ? qf[ks][1] : 0u);
                }
            }
            float d[4];
#pragma unroll
            for (int r = 0; r < 4; r++) d[r] = (s4[0][r] + s4[1][r]) + (s4[2][r] + s4[3][r]);
            float sa = (g & 1) ? d[1] : d[0], sc = (g & 1) ? d[3] : d[2];
            sa += shx(sa, 4); sc += shx(sc, 4);
            uint32_t sp = packbf(sa, sc);
            sp = packbf(bflo(sp) * SCALE, bfhi(sp) * SCALE);
            sa = bflo(sp); sc = bfhi(sp);
            const float mx = warp_max(fmaxf(fmaxf(sa, sc), m));
            const float alpha = ex2((m - mx) * LOG2E);
            m = mx;
            const float pa = ex2((sa - mx) * LOG2E), pc = ex2((sc - mx) * LOG2E);
            const uint32_t pk = packbf(pa, pc);
            uint32_t pb[4][4][2];
#pragma unroll
            for (int j = 0; j < 4; j++) {
                const uint32_t pj = __shfl_sync(0xffffffffu, pk, 8 * tq + j);
#pragma unroll
                for (int i = 0; i < 4; i++) { pb[j][i][0] = prmt0(pj, psel[i][0]); pb[j][i][1] = prmt0(pj, psel[i][1]); }
            }
            l = fmaf(l, alpha, pa + pc);
            ls = l + shx(l, 8);
#pragma unroll
            for (int i = 0; i < 4; i++) { acc[i][0] *= alpha; acc[i][1] *= alpha; acc[i][2] *= alpha; acc[i][3] *= alpha; }
            mbar_wait(sb + SA_FULL + slot * 16 + 8, ph);
            const uint32_t vb = kb + 8192;
#pragma unroll
            for (int i = 0; i < 4; i++)
#pragma unroll
                for (int j = 0; j < 4; j++) {
                    uint32_t a[4];
                    ldsm4t(a, vb + j * 2048 + voff[i]);
                    mma16816(acc[j], a, pb[j][i][0], pb[j][i][1]);
                }
            ls += shx(ls, 16); ls += shx(ls, 1); ls += shx(ls, 2);
            __syncwarp();
            if (lane == 0) mbar_arrive(sb + SA_EMPTY + slot * 8);
            slot += NW;
            if (slot >= NSL) { slot -= NSL; ph ^= 1; }
        }
    }

    const int r = bx >> 2, isC = (bx >> 1) & 1;
    const int isA = (r >> 2) & 1, cb = (r >> 3) * 4 + (r & 3);
    const uint32_t bar_h = sb + SB_BAR + 32;
    if (warp == 8 && !isC) {
        const unsigned c0 = clk32();
        bar_sync(7, 64);
        while ((int)(clk32() - c0) < BSTART + (r & 7) * BSTAG) {}
        if (elect()) load_slice(sb + SB_STG, &M.qb, r, sb + SB_BAR + 16);
        __syncwarp();
    }
    if (warp < 8) {
        const uint32_t bar_q = bar_h + (NT + warp) * 8, box = sb + SB_QIMG + warp * 8192;
        if (elect()) {
            mbar_init(bar_q, 1);
            mbar_init_fence();
            mbar_expect(bar_q, 8192 + 256);
            tma2d_ef(box, &M.qa, (bx >> 1) * 64, warp * 64, bar_q);
        }
        __syncwarp();
        unsigned epoch = 0;
        if (warp < 2) epoch = ld_relaxed1(S->ctr[isC]) / UPG;
        uint4* const qdst = S->qpub + ((lane >> 4) * 32 + r) * 32 + isC * 16 + (lane & 15);
        if (warp == 0) st_b128(qdst, make_uint4(0, 0, 0, 0));
        if (elect()) {
            for (const unsigned c0 = clk32(); (int)(clk32() - c0) < XD0 + (bx >> 1) * XDS;) {}
            bulk_g2s(sb + SB_P + 4096 + warp * 288, P.ax + warp * 32, 128, bar_q);
            bulk_g2s(sb + SB_P + 4096 + warp * 288 + 144, P.ax + 256 + warp * 32, 128, bar_q);
        }
        if (tid == 32) {
#pragma unroll
            for (int i = 0; i < 4 + NT; i++) mbar_init(sb + SB_BAR + i * 8, 1);
            mbar_init_fence();
            sts32(sb + SB_CNT, epoch);
            sts32(sb + SB_CNT + 4, 0);
        }
        __syncwarp();
        if (warp == 1 && !isC) bar_arrive(7, 64);
        mbar_wait(bar_q, 0);
        uint32_t b[8];
#pragma unroll
        for (int i = 0; i < 8; i++) b[i] = lds32(sb + SB_P + 4096 + warp * 288 + (g & 1) * 144 + tq * 4 + i * 16);
        float d[4][4];
        uint32_t a[4][4][4];
#pragma unroll
        for (int i = 0; i < 4; i++) {
            d[i][0] = d[i][1] = d[i][2] = d[i][3] = 0.f;
#pragma unroll
            for (int ks = 0; ks < 4; ks++)
                ldsm4t(a[i][ks], box + ks * 2048 + ((lane & 7) + 8 * (lane >> 4)) * 128 + (((2 * i + ((lane >> 3) & 1)) ^ (lane & 7)) << 4));
        }
#pragma unroll
        for (int ks = 0; ks < 4; ks++)
#pragma unroll
            for (int i = 0; i < 4; i++) mma16816(d[i], a[i][ks], b[2 * ks], b[2 * ks + 1]);
        float* qred = reinterpret_cast<float*>(sm + SB_P);
#pragma unroll
        for (int c = 0; c < 4; c++)
            qred[warp * 128 + (c & 1) * 64 + tq * 16 + (c >> 1) * 8 + g] = tq == 0 ? d[0][c] : tq == 1 ? d[1][c] : tq == 2 ? d[2][c] : d[3][c];
        bar_sync(0, 256);
        if (warp == 0) {
            float4 v[8];
#pragma unroll
            for (int w = 0; w < 8; w++) v[w] = *reinterpret_cast<const float4*>(qred + w * 128 + lane * 4);
#pragma unroll
            for (int o = 4; o; o >>= 1)
#pragma unroll
                for (int w = 0; w < o; w++) { v[w].x += v[w + o].x; v[w].y += v[w + o].y; v[w].z += v[w + o].z; v[w].w += v[w + o].w; }
            st_b128(qdst, make_uint4(packbf(v[0].x, v[0].y), epoch + 1, packbf(v[0].z, v[0].w), epoch + 1));
        }
        if (!isC && tid < 4) st_b128(((tid & 2) ? S->bflag : S->qflag) + r * 8 + (tid & 1) * 4, make_uint4(0, 0, 0, 0));
        if (!isC && warp < 2) st_b128(S->frag[0] + (warp * 32 + r) * 32 + lane, make_uint4(0, 0, 0, 0));
        if (isC && !(warp & 3)) st_b128(S->frag[1] + ((warp >> 2) * 32 + (isA ? 0 : 16) + cb) * 32 + lane, make_uint4(0, 0, 0, 0));
        if (!isC) latent_branch(P, M, sm);
        bar_arrive(6, 288);
    }

    constexpr int ND = 2;
    const int nsnd = isA ? NSA : NSB, isCA = isC & isA;
    const int y0 = isC ? nsnd : 0, y1 = isC ? 32 - ND * isA : nsnd;
    const int nreq = isC ? 32 - nsnd : nsnd;
    const int nmw = isC && !isA ? NMW : 0;
    float* const red = reinterpret_cast<float*>(sm + SC_RED);
    const uint32_t wlane = wo_lane(sb, lane);
    auto fetch_frag = [&](int y, int b, unsigned tag, unsigned ns) {
        for (int it = 0;; it++) {
            const uint4 v = ld_b128(S->frag[0] + isA * 2048 + (b * 32 + y) * 32 + lane);
            if (__all_sync(0xffffffffu, v.y == tag)) {
                reinterpret_cast<uint2*>(sm + SC_FR)[(y * 32 + (g >> 1) * 8 + b * 4 + tq) * 2 + (g & 1)] = make_uint2(v.x, v.z);
                return;
            }
            if (it > SPIN_MAX) __trap();
            __nanosleep(ns);
        }
    };
    if (warp < 8) {
        const unsigned tag = lds32(sb + SB_CNT) + 1;
        const uint32_t t8 = tag & 0xffu;
        uint32_t bs[2], wf[4][4];
        float d[2][4];
        const uint32_t wa = (wlane ^ ((warp & 1) * 32)) + (warp & 2) * 2048;
        const int ks0 = (warp & 2) * 2;
        if (isC) __nanosleep(4000);
#pragma unroll 1
        for (int op = isCA ? 0 : 1;; op++) {
            const int step = isCA ? max(op - 1, 0) : 0, h = step ? 31 - ND + step : isA ? cb : 16 + cb;
            if (op != 1) {
                if (!isCA && (!isC || h >= 32 - ND)) break;
                const int rec = ((warp >> 2) * 32 + h) * CPG + (warp & 3) * 8;
                const uint2* mlp = S->aml + (rec + (lane & 7)) * 4;
                const uint4* src = S->apart + rec * 32 + lane;
                asm volatile("" : "+l"(mlp), "+l"(src));
                if (!step) {
                    for (int it = 0; !__all_sync(0xffffffffu, (ld_b64(mlp).y & 0xffu) == t8); it++) {
                        if (it > SPIN_MAX) __trap();
                        __nanosleep(h > 25 ? DPOLL : CPOLL);
                    }
                } else if (step < ND) {
                    mbar_wait(sb + SB_BAR + 8, 0);
                } else {
                    d[0][0] = d[0][1] = d[0][2] = d[0][3] = d[1][0] = d[1][1] = d[1][2] = d[1][3] = 0.f;
#pragma unroll
                    for (int k = 0; k < ND; k++) {
                        mbar_wait(bar_h + k * 16 + (warp & 2) * 4, 0);
#pragma unroll
                        for (int ks = 0; ks < 4; ks++) ldsm4t(wf[ks], wa + k * 8192 + ks * 1024);
                        if (k < ND - 1) {
#pragma unroll
                            for (int ks = 0; ks < 4; ks++) mma16816(d[ks & 1], wf[ks], g == ks0 + ks ? bs[0] : 0u, g == ks0 + ks ? bs[1] : 0u);
                        }
                    }
                    mbar_wait(sb + SB_BAR, 0);
                }
                uint4 v[8];
                uint2 ml = ld_b64(mlp);
#pragma unroll
                for (int i = 0; i < 8; i++) v[i] = ld_b128(src + i * 32);
                for (int it = 0;; it++) {
                    unsigned x = ml.y ^ t8;
#pragma unroll
                    for (int i = 0; i < 8; i++) x |= v[i].x ^ t8;
                    if (!__any_sync(0xffffffffu, x & 0xffu)) break;
                    if (it > SPIN_MAX) __trap();
                    ml = ld_b64(mlp);
#pragma unroll
                    for (int i = 0; i < 8; i++)
                        if ((v[i].x & 0xffu) != t8) v[i] = ld_b128(src + i * 32);
                }
                const float mw = warp_max(__uint_as_float(ml.x)), e = ex2((__uint_as_float(ml.x) - mw) * LOG2E);
                float L = e * __uint_as_float(ml.y), oa[4], ob[4];
                L += shx(L, 1);
#pragma unroll
                for (int i = 0; i < 8; i++) {
                    const float w = __shfl_sync(0xffffffffu, e, i);
                    float (&o)[4] = (i & 1) ? ob : oa;
                    o[0] = i < 2 ? w * __uint_as_float(v[i].x) : fmaf(w, __uint_as_float(v[i].x), o[0]);
                    o[1] = i < 2 ? w * __uint_as_float(v[i].y) : fmaf(w, __uint_as_float(v[i].y), o[1]);
                    o[2] = i < 2 ? w * __uint_as_float(v[i].z) : fmaf(w, __uint_as_float(v[i].z), o[2]);
                    o[3] = i < 2 ? w * __uint_as_float(v[i].w) : fmaf(w, __uint_as_float(v[i].w), o[3]);
                }
                float* fp = reinterpret_cast<float*>(sm + SC_FP) + ((step & 1) * 8 + (warp & 4)) * 132;
                *reinterpret_cast<float4*>(fp + (warp & 3) * 132 + lane * 4) = make_float4(oa[0] + ob[0], oa[1] + ob[1], oa[2] + ob[2], oa[3] + ob[3]);
                L += shx(L, 2);
                L += shx(L, 4);
                if (lane == 0) *reinterpret_cast<float2*>(fp + (warp & 3) * 132 + 128) = make_float2(mw, L);
                bar_sync(1 + (warp >> 2), 128);
                float2 q[4];
                float4 u[4];
#pragma unroll
                for (int w = 0; w < 4; w++) {
                    q[w] = *reinterpret_cast<const float2*>(fp + w * 132 + 128);
                    u[w] = *reinterpret_cast<const float4*>(fp + w * 132 + lane * 4);
                }
                const float MM = fmaxf(fmaxf(q[0].x, q[1].x), fmaxf(q[2].x, q[3].x));
                float f[4], inv;
#pragma unroll
                for (int w = 0; w < 4; w++) f[w] = ex2((q[w].x - MM) * LOG2E);
                asm("rcp.approx.ftz.f32 %0, %1;" : "=f"(inv) : "f"(fmaf(f[0], q[0].y, f[1] * q[1].y) + fmaf(f[2], q[2].y, f[3] * q[3].y)));
                const uint32_t b0 = packbf((fmaf(f[0], u[0].x, f[1] * u[1].x) + fmaf(f[2], u[2].x, f[3] * u[3].x)) * inv,
                                           (fmaf(f[0], u[0].y, f[1] * u[1].y) + fmaf(f[2], u[2].y, f[3] * u[3].y)) * inv);
                const uint32_t b1 = packbf((fmaf(f[0], u[0].z, f[1] * u[1].z) + fmaf(f[2], u[2].z, f[3] * u[3].z)) * inv,
                                           (fmaf(f[0], u[0].w, f[1] * u[1].w) + fmaf(f[2], u[2].w, f[3] * u[3].w)) * inv);
                if (step == ND) {
#pragma unroll
                    for (int ks = 0; ks < 4; ks++) mma16816(d[ks & 1], wf[ks], g == ks0 + ks ? b0 : 0u, g == ks0 + ks ? b1 : 0u);
                    const float x0 = (d[0][0] + d[0][1]) + (d[1][0] + d[1][1]), x1 = (d[0][2] + d[0][3]) + (d[1][2] + d[1][3]);
                    const float z = ((tq & 1) ? x1 : x0) + shx((tq & 1) ? x0 : x1, 1);
                    if ((tq & 2) == (warp & 2)) red[(6 + (tq >> 1)) * 80 + (warp >> 2) * 40 + (warp & 1) * 16 + (tq & 1) * 8 + g] = z;
                    bar_arrive(5, 480);
                    return;
                }
                bs[0] = b0; bs[1] = b1;
                if (!step && !(warp & 3)) st_b128(S->frag[1] + ((warp >> 2) * 32 + h) * 32 + lane, make_uint4(b0, tag, b1, 0));
                if (!isCA) break;
            } else {
#pragma unroll 1
                for (int y = y0 + ((warp - y0) & 3); y < y1 - 3 * isCA; y += 4) fetch_frag(y, warp >> 2, tag, CPOLL);
                if (warp >= nmw) bar_arrive(4, 448);
            }
        }
        if (warp >= nmw) return;
    }
    if (warp == 14) {
        bar_sync(6, 288);
        const CUtensorMap* map = &M.wo[isA];
        const unsigned tag = lds32(sb + SB_CNT) + 1;
        const uint32_t t8 = tag & 0xffu;
        uint2* const snd = S->snd + r * 32 + lane;
        asm volatile("prefetch.tensormap [%0];" ::"l"(map) : "memory");
        if (!isC) st_b64(snd, t8 ^ 0x80u, 0);
        for (int it = 0;; it++) {
            __nanosleep(2000);
            if (it > 1 && ld_b128(S->frag[1] + 25 * 32).y == tag) break;
            if (it > SPIN_MAX) __trap();
        }
        uint2 f;
        for (int it = 0;; it++) {
            f = ld_b64(S->fire + lane);
            if (__all_sync(0xffffffffu, f.y == tag)) break;
            if (it > SPIN_MAX) __trap();
            __nanosleep(FPOLL);
        }
        const unsigned t0 = __shfl_sync(0xffffffffu, f.x, 0);
        unsigned t1 = t0 + (__reduce_add_sync(0xffffffffu, (int)(f.x - t0)) >> 5) + FIRE_NS;
        if (elect()) {
            const int n1 = nreq - (isC ? (isA ? NLA : NLB) : 0);
            const int dt = !isC ? (isA ? FIRE_W / NSA : FIRE_W / NSB) : isA ? FIRE_W / (32 - NSA - NLA) : FIRE_W / (32 - NSB - NLB);
            unsigned t2 = t1 + REC0_NS;
            int rec = isCA ? 2 : 0;
            int y = isCA ? 32 - ND : y0;
#pragma unroll 1
            for (int i = 0; i < nreq; i++) {
                const int row = y * 128;
                mbar_expect(bar_h + i * 16, 4096);
                mbar_expect(bar_h + i * 16 + 8, 4096);
                if (++y == 32) y = y0;
                if (i <= n1) {
                    unsigned t;
                    for (int it = 0; (int)((t = gt()) - t1) < 0 && it < 4096; it++) {}
                    t1 += dt;
                    if (rec && (int)(t - t2) >= 0) { mbar_arrive(sb + SB_BAR + --rec * 8); t2 += REC_NS - REC0_NS; }
                }
                tma2d(sb + i * 8192, map, cb * 32, row, bar_h + i * 16);
                tma2d(sb + i * 8192 + 4096, map, cb * 32, row + 64, bar_h + i * 16 + 8);
            }
            while (rec) {
                for (int it = 0; (int)(gt() - t2) < 0 && it < 4096; it++) {}
                mbar_arrive(sb + SB_BAR + --rec * 8);
                t2 += REC_NS - REC0_NS;
            }
        }
        __syncwarp();
        uint32_t* dst = reinterpret_cast<uint32_t*>(P.out) + (lane >> 4) * 512 + (isA ? 0 : 256) + cb * 16 + (lane & 15);
        uint32_t q = sb + SC_RED + ((lane >> 4) * 20 + (lane & 15)) * 8;
        asm volatile("" : "+l"(dst), "+r"(q));
        if (!isC) {
            const float2 s = sum_parts<6, 224>(q, 0.f, 0.f);
            st_b64(snd, tagf(s.x, t8), __float_as_uint(s.y));
        } else {
            uint2 o;
            for (int it = 0;; it++) {
                o = ld_b64(snd);
                if (__all_sync(0xffffffffu, (o.x & 0xffu) == t8)) break;
                if (it > SPIN_MAX) __trap();
            }
            if (isA) {
                const float2 s = sum_parts<8, 480>(q, __uint_as_float(o.x), __uint_as_float(o.y));
                asm volatile("st.global.u32 [%0], %1;" ::"l"(dst), "r"(packbf(s.x, s.y)) : "memory");
            } else {
                const float2 s = sum_parts<6 + NMW, 224 + 32 * NMW>(q, __uint_as_float(o.x), __uint_as_float(o.y));
                asm volatile("st.global.b32 [%0], %1;" ::"l"(dst), "r"(packbf(s.x, s.y)) : "memory");
            }
        }
        return;
    }
    {
        const int nw = 6 + nmw, wi = warp < 8 ? warp + 6 : warp - 8, t0 = wi + 2 * ND * isCA;
        bar_sync(4, 448);
        if (isCA) {
            const int y = y0 - ND + ((2 * nreq - 1 - (2 * nreq - 1 - t0) % 6) >> 1);
            const unsigned tag = lds32(sb + SB_CNT) + 1;
#pragma unroll 1
            for (int b = 0; b < 2; b++) fetch_frag(y, b, tag, DPOLL);
            __syncwarp();
        }
        uint32_t rx = sb + SC_RED + (wi * 80 + (tq & 1) * 40 + (tq >> 1) * 16 + g) * 4, nb = isCA ? 480 : 224 + nmw * 32;
        asm volatile("" : "+r"(rx), "+r"(nb));
        float e[4][4];
#pragma unroll
        for (int i = 0; i < 4; i++) e[i][0] = e[i][1] = e[i][2] = e[i][3] = 0.f;
        uint32_t bp = sb + SC_FR + ((2 * (y0 - ND * isCA) + t0) * 16 + (lane & 7)) * 16, wa = wlane + t0 * 4096, bar = bar_h + t0 * 8;
        uint4 b0 = lds128(bp), b1 = lds128(bp + 128);
        const uint32_t zero = lds32(sb + SB_CNT + 4);
#pragma unroll 1
        for (int t = t0;;) {
            uint32_t a[8][4];
            b0.x ^= zero; b1.x ^= zero;
            asm volatile("" : "+r"(b0.x), "+r"(b1.x));
            mbar_wait(bar, 0);
#pragma unroll
            for (int j = 0; j < 8; j++) ldsm4t(a[j], (wa ^ ((j & 1) * 32)) + (j >> 1) * 1024);
            bp += nw * 256;
            const uint4 n0 = lds128(bp), n1 = lds128(bp + 128);
#pragma unroll
            for (int j = 0; j < 8; j++) {
                const uint4& c = (j & 4) ? b1 : b0;
                mma16816(e[(j & 1) * 2 + ((j >> 1) & 1)], a[j], (j & 2) ? c.z : c.x, (j & 2) ? c.w : c.y);
            }
            t += nw;
            if (t >= 2 * nreq) break;
            wa += nw * 4096; bar += nw * 8;
            b0 = n0; b1 = n1;
        }
        float s4[4];
#pragma unroll
        for (int c = 0; c < 4; c++) s4[c] = (tq & 2) ? e[2][c] + e[3][c] : e[0][c] + e[1][c];
        sts32(rx, __float_as_uint((tq & 1) ? s4[1] : s4[0]));
        sts32(rx + 32, __float_as_uint((tq & 1) ? s4[3] : s4[2]));
        bar_arrive(5, nb);
    }
}

typedef CUresult (*EncodeFn)(CUtensorMap*, CUtensorMapDataType, cuuint32_t, void*, const cuuint64_t*, const cuuint64_t*,
                             const cuuint32_t*, const cuuint32_t*, CUtensorMapInterleave, CUtensorMapSwizzle,
                             CUtensorMapL2promotion, CUtensorMapFloatOOBfill);

void make_map(EncodeFn enc, CUtensorMap* m, const void* base, uint64_t cols, uint64_t rows, uint32_t bc, uint32_t br,
              CUtensorMapL2promotion promo, CUtensorMapSwizzle sw = CU_TENSOR_MAP_SWIZZLE_128B) {
    cuuint64_t dims[2] = {cols, rows};
    cuuint64_t strides[1] = {cols * 2};
    cuuint32_t box[2] = {bc, br};
    cuuint32_t es[2] = {1, 1};
    enc(m, CU_TENSOR_MAP_DATA_TYPE_BFLOAT16, 2, const_cast<void*>(base), dims, strides, box, es,
        CU_TENSOR_MAP_INTERLEAVE_NONE, sw, promo, CU_TENSOR_MAP_FLOAT_OOB_FILL_NONE);
}

}

extern "C" void kernel_launch(void* const* d_in, const int* in_sizes, int n_in, void* d_out, int out_size) {
    (void)in_sizes; (void)n_in; (void)out_size;
    static EncodeFn enc = nullptr;
    static void* scr = nullptr;
    if (!enc) {
        void* fn = nullptr;
        cudaDriverEntryPointQueryResult qr;
        cudaGetDriverEntryPoint("cuTensorMapEncodeTiled", &fn, cudaEnableDefault, &qr);
        enc = (EncodeFn)fn;
        cudaGetSymbolAddress(&scr, g_scr);
        cudaFuncSetAttribute(fused_decode_kernel, cudaFuncAttributeMaxDynamicSharedMemorySize, SMEM_BYTES);
    }
    Maps m;
    make_map(enc, &m.kv[0], d_in[1], 64, 1048576, 64, 64, CU_TENSOR_MAP_L2_PROMOTION_NONE);
    make_map(enc, &m.kv[1], d_in[2], 64, 1048576, 64, 64, CU_TENSOR_MAP_L2_PROMOTION_NONE);
    make_map(enc, &m.qa, d_in[3], 4096, 512, 64, 64, CU_TENSOR_MAP_L2_PROMOTION_NONE);
    make_map(enc, &m.qb, d_in[7], 4096, 512, 64, 256, CU_TENSOR_MAP_L2_PROMOTION_NONE);
    make_map(enc, &m.wo[0], d_in[10], 512, 4096, 32, 64, CU_TENSOR_MAP_L2_PROMOTION_L2_128B, CU_TENSOR_MAP_SWIZZLE_64B);
    make_map(enc, &m.wo[1], d_in[4], 512, 4096, 32, 64, CU_TENSOR_MAP_L2_PROMOTION_L2_128B, CU_TENSOR_MAP_SWIZZLE_64B);
    {
        cuuint64_t dims[4] = {64, 8, 8, 2048}, strides[3] = {1024, 128, 8192};
        cuuint32_t box[4] = {64, 8, 8, 8}, es[4] = {1, 1, 1, 1};
        enc(&m.c, CU_TENSOR_MAP_DATA_TYPE_BFLOAT16, 4, d_in[6], dims, strides, box, es, CU_TENSOR_MAP_INTERLEAVE_NONE,
            CU_TENSOR_MAP_SWIZZLE_128B, CU_TENSOR_MAP_L2_PROMOTION_NONE, CU_TENSOR_MAP_FLOAT_OOB_FILL_NONE);
    }
    make_map(enc, &m.uk, d_in[8], 4096, 512, 64, 256, CU_TENSOR_MAP_L2_PROMOTION_NONE);
    make_map(enc, &m.uv, d_in[9], 4096, 512, 64, 256, CU_TENSOR_MAP_L2_PROMOTION_NONE);
    Params p;
    p.scr = (Scratch*)scr;
    p.ax = (const uint32_t*)d_in[0];
    p.bx = (const uint32_t*)d_in[5];
    p.out = (__nv_bfloat16*)d_out;
    p.wq = (const char*)d_in[3];
    fused_decode_kernel<<<128, 480, SMEM_BYTES, cudaStreamPerThread>>>(p, m);
}
```
